```python
import torch

def _softmax(x, axis=-1):
    return torch.softmax(x, dim=axis)
def _gelu(x):
    return torch.nn.functional.gelu(x, approximate="tanh")
def _silu(x):
    return torch.nn.functional.silu(x)
def _sigmoid(x):
    return torch.sigmoid(x)
def _layernorm(x, axis=-1, eps=1e-5):
    m = x.mean(dim=axis, keepdim=True)
    v = x.var(dim=axis, keepdim=True, unbiased=False)
    return (x - m) / torch.sqrt(v + eps)
def _scatter_add(tgt, idx, src, axis=0):
    return tgt.clone().index_add_(axis, idx, src)
def _segment_sum(src, seg, n):
    out = torch.zeros((n,) + src.shape[1:], dtype=src.dtype)
    return out.index_add_(0, seg, src)
def _pad(x, pw):
    flat = tuple(v for pair in reversed(pw) for v in pair)
    return torch.nn.functional.pad(x, flat)

kernel_name = 'concat_heads__ssm_conv_h3__ssm_conv_s5__prompt'

def setup_inputs():

    _w = (lambda a: (lambda t: t.to(torch.bfloat16) if t.is_floating_point() else t)(torch.as_tensor(a)))
    def _A_setup():
        B, S, D = 1, 2048, 1024
        ks = 4
        return {
            "q": _w((lambda *s: torch.randn(*s, dtype=torch.bfloat16) * 0.05)(B, S, D)),
            "k": _w((lambda *s: torch.randn(*s, dtype=torch.bfloat16) * 0.2)(B, S, D)),
            "v": _w((lambda *s: torch.randn(*s, dtype=torch.bfloat16) * 0.2)(B, S, D)),
            "shift_k": _w((lambda *s: torch.randn(*s, dtype=torch.bfloat16) * 0.2)(D, ks) * 0.5),
            "ssm_k": _w((lambda *s: torch.randn(*s, dtype=torch.bfloat16) * 0.8)(D, S) * (1.0 / S ** 0.5)),
            "ssm_D": _w((lambda *s: torch.randn(*s, dtype=torch.bfloat16) * 0.2)(D)),
        }
    _A_in = _A_setup()

    def _B_setup():
        B, S, D = 1, 2048, 1024
        P = D
        Lambda_re = -0.5 * (lambda _x: torch.exp(torch.as_tensor(_x)))((lambda *s: torch.randn(*s, dtype=torch.bfloat16) * 0.2)(P))
        Lambda_im = (lambda *s: torch.randn(*s, dtype=torch.bfloat16) * 0.4)(P) * 1.0
        B_re = (lambda *s: torch.randn(*s, dtype=torch.bfloat16) * 0.2)(P, D) * (D ** -0.5)
        B_im = (lambda *s: torch.randn(*s, dtype=torch.bfloat16) * 0.2)(P, D) * (D ** -0.5)
        C_re = (lambda *s: torch.randn(*s, dtype=torch.bfloat16) * 0.2)(D, P) * (P ** -0.5)
        C_im = (lambda *s: torch.randn(*s, dtype=torch.bfloat16) * 0.2)(D, P) * (P ** -0.5)
        log_dt = (lambda *s: torch.randn(*s, dtype=torch.bfloat16) * 0.2)(P) * 0.3 - 2.0
        Dskip = (lambda *s: torch.randn(*s, dtype=torch.bfloat16) * 0.05)(D)
        return {
            "x": _w((lambda *s: torch.randn(*s, dtype=torch.bfloat16) * 0.05)(B, S, D)),
            "Lambda_re": _w(Lambda_re),
            "Lambda_im": _w(Lambda_im),
            "B_re": _w(B_re),
            "B_im": _w(B_im),
            "C_re": _w(C_re),
            "C_im": _w(C_im),
            "log_dt": _w(log_dt),
            "Dskip": _w(Dskip),
        }
    _B_in = _B_setup()

    return {
        "A_q": _A_in["q"],
        "A_k": _A_in["k"],
        "A_v": _A_in["v"],
        "A_shift_k": _A_in["shift_k"],
        "A_ssm_k": _A_in["ssm_k"],
        "A_ssm_D": _A_in["ssm_D"],
        "B_x": _B_in["x"],
        "B_Lambda_re": _B_in["Lambda_re"],
        "B_Lambda_im": _B_in["Lambda_im"],
        "B_B_re": _B_in["B_re"],
        "B_B_im": _B_in["B_im"],
        "B_C_re": _B_in["C_re"],
        "B_C_im": _B_in["C_im"],
        "B_log_dt": _B_in["log_dt"],
        "B_Dskip": _B_in["Dskip"],
    }

def reference(A_q, A_k, A_v, A_shift_k, A_ssm_k, A_ssm_D, B_x, B_Lambda_re, B_Lambda_im, B_B_re, B_B_im, B_C_re, B_C_im, B_log_dt, B_Dskip):
    def _A_ref(q, k, v, shift_k, ssm_k, ssm_D):
        B, S, D = q.shape
        ks = shift_k.shape[-1]
        k_pad = _pad(k, ((0, 0), (ks - 1, 0), (0, 0)))
        k_shift = torch.zeros_like(k)
        for t in range(ks):
            k_shift = k_shift + k_pad[:, t:t + S, :] * shift_k[:, ks - 1 - t][None, None, :]
        kv = k_shift * v
        L = 2 * S
        kv_pad = _pad(kv, ((0, 0), (0, S), (0, 0)))
        kf_pad = _pad(ssm_k, ((0, 0), (0, S)))
        kv_f = (lambda x, axes=(-2,-1): torch.fft.rfft2(x.float(), dim=axes))(kv_pad[:, None, :, :], axes=(1, 2))
        kf_f = (lambda x, axes=(-2,-1): torch.fft.rfft2(x.float(), dim=axes))(kf_pad[:, None, :], axes=(1, 2))
        kf_f = (lambda x, *d: x.permute(*d))(kf_f, 1, 2, 0)
        y_f = kv_f * kf_f[None, :, :, :]
        y = (lambda x, s, axes=(-2,-1): torch.fft.irfft2(x, s=s, dim=axes).to(torch.bfloat16))(y_f, (1, L), axes=(1, 2))[:, 0, :S, :]
        y = y + kv * ssm_D[None, None, :]
        return q * y

    def _B_ref(x, Lambda_re, Lambda_im, B_re, B_im, C_re, C_im, log_dt, Dskip):
        Bsz, L, H = x.shape
        Lam = Lambda_re + 1j * Lambda_im
        Bmat = B_re + 1j * B_im
        Cmat = C_re + 1j * C_im
        dt = torch.exp(log_dt)
        Lam_bar = torch.exp(dt * Lam)
        B_bar = ((Lam_bar - 1.0) / Lam)[:, None] * Bmat
        Bu = torch.einsum("bld,pd->blp", x + 0j, B_bar)
        h = torch.zeros_like(Bu[:, 0, :])
        hs = []
        for t in range(L):
            h = Lam_bar[None, :] * h + Bu[:, t, :]
            hs.append(h)
        hseq = torch.stack(hs, 1)
        y = 2.0 * torch.einsum("blp,dp->bld", hseq, Cmat).real + x * Dskip[None, None, :]
        return y

    a = _A_ref(A_q, A_k, A_v, A_shift_k, A_ssm_k, A_ssm_D)
    b = _B_ref(B_x, B_Lambda_re, B_Lambda_im, B_B_re, B_B_im, B_C_re, B_C_im, B_log_dt, B_Dskip)
    return torch.concatenate([a, b], axis=-1)
```

```cpp
#include <cuda_runtime.h>
#include <cuda_bf16.h>
#include <cuda.h>
#include <stdint.h>
#include <type_traits>

#define PROFILE 0

namespace {

constexpr int S_LEN = 2048;
constexpr int D_DIM = 1024;
constexpr int NCTA = 128;

#define STAGES 5
constexpr int STAGE_BYTES = 32768;
constexpr int OFF_RING = 0;
constexpr int OFF_F1 = STAGES * STAGE_BYTES, OFF_F2 = OFF_F1 + 4096, OFF_K = OFF_F2 + 2048, OFF_VP = OFF_K + 2 * 4096, OFF_Q = OFF_VP + 4096;
constexpr int OFF_KV = OFF_K, OFF_IN = OFF_F1 + 32;
constexpr int OFF_U = OFF_Q + 3 * 4096 + 128, U_CH = 528, U_N8 = 8 * U_CH;
constexpr int OFF_COEF = OFF_U + 8 * U_N8;
constexpr int OFF_DS = OFF_COEF + 2048, OFF_D = OFF_DS + 256;
constexpr int OFF_BAR = OFF_D + 64;
constexpr int OFF_PROF = OFF_BAR + 512;
constexpr int SMEM_BYTES = OFF_PROF + 512;
static_assert(SMEM_BYTES <= 232448 && OFF_IN + 4 * U_N8 <= OFF_Q && OFF_K % 1024 == 0 && OFF_U % 128 == 0, "smem map");
constexpr int B_FULL = 0, B_EMPTY = 8, B_COEF = 16, B_HR = 17, B_HP = 18, B_KVF = 19, B_KVE = 22, B_KF = 25, B_KE = 28, B_QF = 31, B_QE = 34, B_IN = 37, B_UF = 41, B_RDY = 45, B_UA = 46, B_ACK = 47, B_EPOCH = 48;

#define WAIT_NS 100
#define QD 8
#define PF_AHEAD 0
#define TAILB 4
#define ST_DELAY 300
#define REL 2
#define FLAG_CNT (REL ? 8 : 32)
#define POLL_NS 30
#define PFENCE 1
#define MAPMODE 1
#define VMAP 1
#define COUPLE MC
#define XFENCE 1
#define XPOS 30
#define MC 1
#define H_PACE 200
#define KV_T0 3000
#define KV_DT 600
#define KV_DV (KV_DT - 50)
#define PF 0
#define PF_MID 10
#define PF_T1 1800
#define PF_T2 1200
#define PF_T3 0
#define PF_T4 11500
#define PF_DT 200
#define PF_DT4 400
#define PF_KV 1500
#define KV_PF 0
#define KV_PROMO CU_TENSOR_MAP_L2_PROMOTION_L2_128B
#define G_PROMO CU_TENSOR_MAP_L2_PROMOTION_L2_128B
#define O_PACE 200
#define Q_AT 6
#define CARRY_WAIT 900
#define P2_SPLIT 1
#define ROT 2
#define GREEDY 1
#define SCALE_G 2
#define XB 4
#define CARRY_AT 56
#define MBAR_LONG mbar_wait
constexpr int SPIN_LIMIT = 1 << 14;

struct Params {
  const __nv_bfloat16 *q, *k, *v, *shift_k, *ssm_k, *ssm_D, *x, *lam_re, *lam_im, *B_re, *B_im, *C_re, *C_im, *log_dt, *Dskip;
  float* out;
  int swapB;
  unsigned zero;
};

__device__ __align__(1024) uint4 g_h[16 * 32 * 1024];
__device__ __align__(128) uint4 g_carry[16 * 16 * 32];
__device__ unsigned g_flagH[2 * 16 * 32];
__device__ unsigned g_epoch[NCTA * 32];
#define STAMP(i)
#define TSTAMP(k, n)

#define KSTAMP(k, n)
__device__ __forceinline__ uint64_t make_desc(uint32_t addr, uint32_t lbo, uint32_t sbo, uint32_t swz) {
  return (uint64_t)((addr & 0x3FFFF) >> 4) | ((uint64_t)(lbo >> 4) << 16) | ((uint64_t)(sbo >> 4) << 32) | ((uint64_t)swz << 62);
}
__device__ __forceinline__ void wg_fence() { asm volatile("wgmma.fence.sync.aligned;" ::: "memory"); }
__device__ __forceinline__ void wg_commit() { asm volatile("wgmma.commit_group.sync.aligned;" ::: "memory"); }
template <int N> __device__ __forceinline__ void wg_wait() { asm volatile("wgmma.wait_group.sync.aligned %0;" ::"n"(N) : "memory"); }
__device__ __forceinline__ void mbar_init(uint32_t bar, int cnt) { asm volatile("mbarrier.init.shared::cta.b64 [%0], %1;" ::"r"(bar), "r"(cnt) : "memory"); }
__device__ __forceinline__ void mbar_expect(uint32_t bar, uint32_t bytes) { asm volatile("mbarrier.arrive.expect_tx.shared::cta.b64 _, [%0], %1;" ::"r"(bar), "r"(bytes) : "memory"); }
__device__ __forceinline__ void mbar_wait(uint32_t bar, uint32_t parity) {
  uint32_t ok; int n = 0;
  do {
    asm volatile("{\n.reg .pred p;\nmbarrier.try_wait.parity.shared::cta.b64 p, [%1], %2;\nselp.u32 %0, 1, 0, p;\n}\n" : "=r"(ok) : "r"(bar), "r"(parity) : "memory");
    if (++n > SPIN_LIMIT) break;
  } while (!ok);
}
__device__ __forceinline__ void mbar_wait_cluster(uint32_t bar) {
  uint32_t ok; int n = 0;
  do {
    asm volatile("{\n.reg .pred p;\nmbarrier.try_wait.parity.acquire.cluster.shared::cta.b64 p, [%1], 0;\nselp.u32 %0, 1, 0, p;\n}\n" : "=r"(ok) : "r"(bar) : "memory");
  } while (!ok && ++n <= SPIN_LIMIT);
}
__device__ __forceinline__ void mbar_wait_sleep(uint32_t bar, uint32_t parity) {
  uint32_t ok; int n = 0;
  while (true) {
    asm volatile("{\n.reg .pred p;\nmbarrier.test_wait.parity.shared::cta.b64 p, [%1], %2;\nselp.u32 %0, 1, 0, p;\n}\n" : "=r"(ok) : "r"(bar), "r"(parity) : "memory");
    if (ok || ++n > SPIN_LIMIT) break;
    __nanosleep(WAIT_NS);
  }
}
__device__ __forceinline__ void mbar_arrive(uint32_t bar) { asm volatile("mbarrier.arrive.shared::cta.b64 _, [%0];" ::"r"(bar) : "memory"); }
__device__ __forceinline__ void mbar_arrive_cta(uint32_t bar, uint32_t cta) {
  asm volatile("{\n.reg .b32 ra;\nmapa.shared::cluster.u32 ra, %0, %1;\nmbarrier.arrive.shared::cluster.b64 _, [ra];\n}\n" ::"r"(bar), "r"(cta) : "memory");
}
__device__ __forceinline__ bool elect_one() {
  uint32_t p;
  asm volatile("{\n.reg .pred P;\nelect.sync _|P, 0xffffffff;\nselp.u32 %0, 1, 0, P;\n}\n" : "=r"(p));
  return p != 0;
}
__device__ __forceinline__ void bar_sync(int id, int n) { asm volatile("bar.sync %0, %1;" ::"r"(id), "r"(n) : "memory"); }
__device__ __forceinline__ void tma2d_mc(uint32_t dst, const CUtensorMap* m, int c0, int c1, uint32_t bar) {
  asm volatile("cp.async.bulk.tensor.2d.shared::cluster.global.mbarrier::complete_tx::bytes.multicast::cluster [%0], [%1, {%3, %4}], [%2], %5;"
               ::"r"(dst), "l"(m), "r"(bar), "r"(c0), "r"(c1), "h"((uint16_t)3) : "memory");
}
__device__ __forceinline__ void tma2d(uint32_t dst, const CUtensorMap* m, int c0, int c1, uint32_t bar) {
  asm volatile("cp.async.bulk.tensor.2d.shared::cluster.global.mbarrier::complete_tx::bytes [%0], [%1, {%3, %4}], [%2];"
               ::"r"(dst), "l"(m), "r"(bar), "r"(c0), "r"(c1) : "memory");
}
__device__ __forceinline__ void tma3d(uint32_t dst, const CUtensorMap* m, int c0, int c1, int c2, uint32_t bar) {
  asm volatile("cp.async.bulk.tensor.3d.shared::cluster.global.mbarrier::complete_tx::bytes [%0], [%1, {%3, %4, %5}], [%2];"
               ::"r"(dst), "l"(m), "r"(bar), "r"(c0), "r"(c1), "r"(c2) : "memory");
}
__device__ __forceinline__ void tma4d(uint32_t dst, const CUtensorMap* m, int c0, int c1, int c2, int c3, uint32_t bar) {
  asm volatile("cp.async.bulk.tensor.4d.shared::cluster.global.mbarrier::complete_tx::bytes [%0], [%1, {%3, %4, %5, %6}], [%2];"
               ::"r"(dst), "l"(m), "r"(bar), "r"(c0), "r"(c1), "r"(c2), "r"(c3) : "memory");
}
__device__ __forceinline__ void tma4d_mc(uint32_t dst, const CUtensorMap* m, int c0, int c1, int c2, int c3, uint32_t bar) {
  asm volatile("cp.async.bulk.tensor.4d.shared::cluster.global.mbarrier::complete_tx::bytes.multicast::cluster [%0], [%1, {%3, %4, %5, %6}], [%2], %7;"
               ::"r"(dst), "l"(m), "r"(bar), "r"(c0), "r"(c1), "r"(c2), "r"(c3), "h"((uint16_t)3) : "memory");
}
__device__ __forceinline__ void tma5d(uint32_t dst, const CUtensorMap* m, int c0, int c1, int c2, int c3, int c4, uint32_t bar) {
  asm volatile("cp.async.bulk.tensor.5d.shared::cluster.global.mbarrier::complete_tx::bytes [%0], [%1, {%3, %4, %5, %6, %7}], [%2];"
               ::"r"(dst), "l"(m), "r"(bar), "r"(c0), "r"(c1), "r"(c2), "r"(c3), "r"(c4) : "memory");
}
__device__ __forceinline__ void tma4d_store(const CUtensorMap* m, uint32_t src, int c0, int c1, int c2, int c3) {
  asm volatile("cp.async.bulk.tensor.4d.global.shared::cta.bulk_group [%0, {%2, %3, %4, %5}], [%1];"
               ::"l"(m), "r"(src), "r"(c0), "r"(c1), "r"(c2), "r"(c3) : "memory");
}
__device__ __forceinline__ void bulk_store(void* dst, uint32_t src, uint32_t bytes) {
  asm volatile("cp.async.bulk.global.shared::cta.bulk_group [%0], [%1], %2;" ::"l"(dst), "r"(src), "r"(bytes) : "memory");
}
__device__ __forceinline__ void bulk_commit() { asm volatile("cp.async.bulk.commit_group;" ::: "memory"); }
template <int N> __device__ __forceinline__ void bulk_wait() { asm volatile("cp.async.bulk.wait_group %0;" ::"n"(N) : "memory"); }
template <int N> __device__ __forceinline__ void bulk_wait_read() { asm volatile("cp.async.bulk.wait_group.read %0;" ::"n"(N) : "memory"); }
__device__ __forceinline__ void fence_proxy_async_smem() { asm volatile("fence.proxy.async.shared::cta;" ::: "memory"); }
__device__ __forceinline__ void red_release(unsigned* p, unsigned v) { asm volatile("red.release.gpu.global.add.u32 [%0], %1;" ::"l"(p), "r"(v) : "memory"); }
__device__ __forceinline__ uint32_t clk32() { uint32_t c; asm volatile("mov.u32 %0, %%clock;" : "=r"(c)::"memory"); return c; }
__device__ __forceinline__ void wait_until(uint32_t t0, uint32_t dt) { while (clk32() - t0 < dt) __nanosleep(32); }
__device__ __forceinline__ void spin_until(uint32_t t0, uint32_t dt) { while (clk32() - t0 < dt) {} }
__device__ __forceinline__ void prefetch_l2(const void* p, uint32_t bytes) {
  asm volatile("cp.async.bulk.prefetch.L2.global [%0], %1;" ::"l"(p), "r"(bytes) : "memory");
}
__device__ __forceinline__ void prefetch_line(const void* p) { asm volatile("prefetch.global.L2 [%0];" ::"l"(p) : "memory"); }
__device__ __forceinline__ void prefetch_map(const CUtensorMap* m) { asm volatile("prefetch.tensormap [%0];" ::"l"(m) : "memory"); }
__device__ __forceinline__ unsigned ld_acquire(const unsigned* p) { unsigned v; asm volatile("ld.acquire.gpu.global.u32 %0, [%1];" : "=r"(v) : "l"(p) : "memory"); return v; }
__device__ __forceinline__ unsigned ld_relaxed(const unsigned* p) { unsigned v; asm volatile("ld.relaxed.gpu.global.u32 %0, [%1];" : "=r"(v) : "l"(p) : "memory"); return v; }
__device__ __forceinline__ void st_release(unsigned* p, unsigned v) { asm volatile("st.release.gpu.global.u32 [%0], %1;" ::"l"(p), "r"(v) : "memory"); }
__device__ __forceinline__ void st_relaxed(unsigned* p, unsigned v) { asm volatile("st.relaxed.gpu.global.u32 [%0], %1;" ::"l"(p), "r"(v) : "memory"); }
__device__ __forceinline__ void wait_flags(const unsigned* p, unsigned val) {
  int n = 0;
  while (!__all_sync(0xffffffffu, ld_acquire(p) == val)) { if (++n > SPIN_LIMIT) break; }
}
__device__ __forceinline__ void fence_proxy_async_global() { asm volatile("fence.proxy.async.global;" ::: "memory"); }
__device__ __forceinline__ uint32_t lds32(uint32_t a) { uint32_t v; asm volatile("ld.shared.u32 %0, [%1];" : "=r"(v) : "r"(a)); return v; }
__device__ __forceinline__ uint4 lds128(uint32_t a) { uint4 v; asm volatile("ld.shared.v4.u32 {%0,%1,%2,%3}, [%4];" : "=r"(v.x), "=r"(v.y), "=r"(v.z), "=r"(v.w) : "r"(a) : "memory"); return v; }
__device__ __forceinline__ void sts128(uint32_t a, uint4 v) { asm volatile("st.shared.v4.u32 [%0], {%1,%2,%3,%4};" ::"r"(a), "r"(v.x), "r"(v.y), "r"(v.z), "r"(v.w) : "memory"); }
__device__ __forceinline__ void stsm4t(uint32_t a, uint32_t r0, uint32_t r1, uint32_t r2, uint32_t r3) {
  asm volatile("stmatrix.sync.aligned.m8n8.x4.trans.shared.b16 [%0], {%1,%2,%3,%4};" ::"r"(a), "r"(r0), "r"(r1), "r"(r2), "r"(r3) : "memory");
}
__device__ __forceinline__ uint4 ldg128_nc(const void* p) { uint4 v; asm volatile("ld.global.nc.L1::no_allocate.v4.u32 {%0,%1,%2,%3}, [%4];" : "=r"(v.x), "=r"(v.y), "=r"(v.z), "=r"(v.w) : "l"(p)); return v; }
__device__ __forceinline__ uint2 ldg64_nc(const void* p) { uint2 v; asm volatile("ld.global.nc.L1::no_allocate.v2.u32 {%0,%1}, [%2];" : "=r"(v.x), "=r"(v.y) : "l"(p)); return v; }
__device__ __forceinline__ uint32_t ldg32_nc(const void* p) { uint32_t v; asm volatile("ld.global.nc.u32 %0, [%1];" : "=r"(v) : "l"(p)); return v; }
__device__ __forceinline__ uint4 ldg128_cg(const void* p) { uint4 v; asm volatile("ld.global.cg.v4.u32 {%0,%1,%2,%3}, [%4];" : "=r"(v.x), "=r"(v.y), "=r"(v.z), "=r"(v.w) : "l"(p) : "memory"); return v; }
__device__ __forceinline__ uint4 ldg128_relaxed(const void* p) { uint4 v; asm volatile("ld.relaxed.gpu.global.v4.u32 {%0,%1,%2,%3}, [%4];" : "=r"(v.x), "=r"(v.y), "=r"(v.z), "=r"(v.w) : "l"(p) : "memory"); return v; }
__device__ __forceinline__ void stg128(void* p, uint4 v) { asm volatile("st.global.v4.u32 [%0], {%1,%2,%3,%4};" ::"l"(p), "r"(v.x), "r"(v.y), "r"(v.z), "r"(v.w) : "memory"); }
__device__ __forceinline__ void stg128_cs(void* p, uint4 v) { asm volatile("st.global.cs.v4.u32 [%0], {%1,%2,%3,%4};" ::"l"(p), "r"(v.x), "r"(v.y), "r"(v.z), "r"(v.w) : "memory"); }
__device__ __forceinline__ void stg128_ef(void* p, uint4 v) { asm volatile("st.global.L1::no_allocate.v4.u32 [%0], {%1,%2,%3,%4};" ::"l"(p), "r"(v.x), "r"(v.y), "r"(v.z), "r"(v.w) : "memory"); }
__device__ __forceinline__ void stg128_relaxed(void* p, uint4 v) { asm volatile("st.relaxed.gpu.global.v4.u32 [%0], {%1,%2,%3,%4};" ::"l"(p), "r"(v.x), "r"(v.y), "r"(v.z), "r"(v.w) : "memory"); }
__device__ __forceinline__ uint32_t pack_bf16(float lo, float hi) { uint32_t r; asm("cvt.rn.bf16x2.f32 %0, %1, %2;" : "=r"(r) : "f"(hi), "f"(lo)); return r; }
__device__ __forceinline__ uint32_t bmul2(uint32_t a, uint32_t b) { uint32_t r; asm("mul.rn.bf16x2 %0, %1, %2;" : "=r"(r) : "r"(a), "r"(b)); return r; }
__device__ __forceinline__ uint32_t badd2(uint32_t a, uint32_t b) { uint32_t r; asm("add.rn.bf16x2 %0, %1, %2;" : "=r"(r) : "r"(a), "r"(b)); return r; }
__device__ __forceinline__ uint32_t bfma2(uint32_t a, uint32_t b, uint32_t c) { uint32_t r; asm("fma.rn.bf16x2 %0, %1, %2, %3;" : "=r"(r) : "r"(a), "r"(b), "r"(c)); return r; }
__device__ __forceinline__ float bf_lo(uint32_t w) { return __uint_as_float(w << 16); }
__device__ __forceinline__ float bf_hi(uint32_t w) { return __uint_as_float(w & 0xffff0000u); }
__device__ __forceinline__ float bf2f(__nv_bfloat16 v) { return __bfloat162float(v); }

#define R8(d, o) "+f"(d[o]), "+f"(d[o + 1]), "+f"(d[o + 2]), "+f"(d[o + 3]), "+f"(d[o + 4]), "+f"(d[o + 5]), "+f"(d[o + 6]), "+f"(d[o + 7])
#define R16(d, o) R8(d, o), R8(d, o + 8)
#define R64(d, o) R16(d, o), R16(d, o + 16), R16(d, o + 32), R16(d, o + 48)
template <int TA> __device__ __forceinline__ void wgmma_n128(float* d, uint64_t da, uint64_t db, int scale_d) {
  asm volatile("{\n.reg .pred p;\nsetp.ne.b32 p, %66, 0;\n"
    "wgmma.mma_async.sync.aligned.m64n128k16.f32.bf16.bf16 {"
    "%0,%1,%2,%3,%4,%5,%6,%7,%8,%9,%10,%11,%12,%13,%14,%15,%16,%17,%18,%19,%20,%21,%22,%23,%24,%25,%26,%27,%28,%29,%30,%31,"
    "%32,%33,%34,%35,%36,%37,%38,%39,%40,%41,%42,%43,%44,%45,%46,%47,%48,%49,%50,%51,%52,%53,%54,%55,%56,%57,%58,%59,%60,%61,%62,%63"
    "}, %64, %65, p, 1, 1, %67, 0;\n}\n"
    : R64(d, 0)
    : "l"(da), "l"(db), "r"(scale_d), "n"(TA));
}
__device__ __forceinline__ void bulk_load(uint32_t dst, const void* src, uint32_t bytes, uint32_t bar) {
  asm volatile("cp.async.bulk.shared::cluster.global.mbarrier::complete_tx::bytes [%0], [%1], %2, [%3];" ::"r"(dst), "l"(src), "r"(bytes), "r"(bar) : "memory");
}
__device__ __forceinline__ void release_stage(uint32_t bar, int t) {
  if (COUPLE) { if (t < 2) mbar_arrive_cta(bar, t); }
  else if (t == 0) mbar_arrive(bar);
}
__device__ __forceinline__ void bulk_load_mc(uint32_t dst, const void* src, uint32_t bytes, uint32_t bar) {
  asm volatile("cp.async.bulk.shared::cluster.global.mbarrier::complete_tx::bytes.multicast::cluster [%0], [%1], %2, [%3], %4;" ::"r"(dst), "l"(src), "r"(bytes), "r"(bar), "h"((uint16_t)3) : "memory");
}
template <int N> __device__ __forceinline__ void fence_regs(float* d) {
#pragma unroll
  for (int i = 0; i < N; i++) asm volatile("" : "+f"(d[i])::"memory");
}
#define PMFENCE() asm volatile("pmevent 0;" ::: "memory")
#define W8(d, o) "=f"(d[o]), "=f"(d[o + 1]), "=f"(d[o + 2]), "=f"(d[o + 3]), "=f"(d[o + 4]), "=f"(d[o + 5]), "=f"(d[o + 6]), "=f"(d[o + 7])
#define L16 "{%0,%1,%2,%3,%4,%5,%6,%7,%8,%9,%10,%11,%12,%13,%14,%15}"
#define L32 "{%0,%1,%2,%3,%4,%5,%6,%7,%8,%9,%10,%11,%12,%13,%14,%15,%16,%17,%18,%19,%20,%21,%22,%23,%24,%25,%26,%27,%28,%29,%30,%31}"
template <int ACC, int TB> __device__ __forceinline__ void rs_n32(float* d, const uint32_t* a, uint64_t db) {
  if constexpr (ACC) asm volatile("wgmma.mma_async.sync.aligned.m64n32k16.f32.bf16.bf16 " L16 ", {%16,%17,%18,%19}, %20, 1, 1, 1, %21;" : R16(d, 0) : "r"(a[0]), "r"(a[1]), "r"(a[2]), "r"(a[3]), "l"(db), "n"(TB));
  else asm volatile("wgmma.mma_async.sync.aligned.m64n32k16.f32.bf16.bf16 " L16 ", {%16,%17,%18,%19}, %20, 0, 1, 1, %21;" : W8(d, 0), W8(d, 8) : "r"(a[0]), "r"(a[1]), "r"(a[2]), "r"(a[3]), "l"(db), "n"(TB));
}
template <int ACC, int TB> __device__ __forceinline__ void ss_n64(float* d, uint64_t da, uint64_t db) {
  if constexpr (ACC) asm volatile("wgmma.mma_async.sync.aligned.m64n64k16.f32.bf16.bf16 " L32 ", %32, %33, 1, 1, 1, 0, %34;" : R16(d, 0), R16(d, 16) : "l"(da), "l"(db), "n"(TB));
  else asm volatile("wgmma.mma_async.sync.aligned.m64n64k16.f32.bf16.bf16 " L32 ", %32, %33, 0, 1, 1, 0, %34;" : W8(d, 0), W8(d, 8), W8(d, 16), W8(d, 24) : "l"(da), "l"(db), "n"(TB));
}
template <int ACC> __device__ __forceinline__ void ss_n32_tt(float* d, uint64_t da, uint64_t db) {
  if constexpr (ACC) asm volatile("wgmma.mma_async.sync.aligned.m64n32k16.f32.bf16.bf16 " L16 ", %16, %17, 1, 1, 1, 1, 1;" : R16(d, 0) : "l"(da), "l"(db));
  else asm volatile("wgmma.mma_async.sync.aligned.m64n32k16.f32.bf16.bf16 " L16 ", %16, %17, 0, 1, 1, 1, 1;" : W8(d, 0), W8(d, 8) : "l"(da), "l"(db));
}
__device__ __forceinline__ void stsm4(uint32_t a, uint32_t r0, uint32_t r1, uint32_t r2, uint32_t r3) {
  asm volatile("stmatrix.sync.aligned.m8n8.x4.shared.b16 [%0], {%1,%2,%3,%4};" ::"r"(a), "r"(r0), "r"(r1), "r"(r2), "r"(r3) : "memory");
}
__device__ __forceinline__ uint32_t bneg2(uint32_t a) { uint32_t r; asm("neg.bf16x2 %0, %1;" : "=r"(r) : "r"(a)); return r; }
template <int N> __device__ __forceinline__ void fence_u32(uint32_t* d) {
#pragma unroll
  for (int i = 0; i < N; i++) asm volatile("" : "+r"(d[i])::"memory");
}
__device__ __forceinline__ void pack32(uint32_t* f, const float* z) {
#pragma unroll
  for (int i = 0; i < 16; i++) f[i] = pack_bf16(z[2 * i], z[2 * i + 1]);
}
template <int INV> __device__ __forceinline__ void twiddle(uint32_t* f, const uint32_t* tp, const uint32_t* ts) {
#pragma unroll
  for (int i = 0; i < 8; i++) {
    uint32_t x = f[2 * i + INV], y = f[2 * i + 1 - INV];
    x = bfma2(tp[i & 3], y, x); y = bfma2(ts[i & 3], x, y); x = bfma2(tp[i & 3], y, x);
    f[2 * i + INV] = x; f[2 * i + 1 - INV] = y;
  }
}
#define NEGOP(x) ((x) ^ 0x80008000u)
template <int FIRST> __device__ __forceinline__ void bimac(uint32_t* o, const uint32_t* a, const uint32_t* b, const uint32_t* c) {
#pragma unroll
  for (int J = 0; J < 2; J++) {
    const uint32_t Pr = a[2 * J], Pi = a[2 * J + 1], Qr = a[2 * J + 4], Qi = a[2 * J + 5], pr = b[2 * J], pi = b[2 * J + 1], qr = b[2 * J + 4], qi = b[2 * J + 5];
    uint32_t x0 = FIRST ? bmul2(Pr, pr) : bfma2(Pr, pr, c[2 * J]), x1 = FIRST ? bmul2(Pr, pi) : bfma2(Pr, pi, c[2 * J + 1]);
    uint32_t x2 = FIRST ? bmul2(Pr, qr) : bfma2(Pr, qr, c[2 * J + 4]), x3 = FIRST ? bmul2(Pr, qi) : bfma2(Pr, qi, c[2 * J + 5]);
    x0 = bfma2(NEGOP(Pi), pi, x0); x1 = bfma2(Pi, pr, x1); x2 = bfma2(NEGOP(Pi), qi, x2); x3 = bfma2(Pi, qr, x3);
    x0 = bfma2(NEGOP(Qr), qr, x0); x1 = bfma2(NEGOP(Qr), qi, x1); x2 = bfma2(Qr, pr, x2); x3 = bfma2(Qr, pi, x3);
    x0 = bfma2(Qi, qi, x0); x1 = bfma2(NEGOP(Qi), qr, x1); x2 = bfma2(NEGOP(Qi), pi, x2); x3 = bfma2(Qi, pr, x3);
    o[2 * J] = x0; o[2 * J + 1] = x1; o[2 * J + 4] = x2; o[2 * J + 5] = x3;
  }
}
__device__ __forceinline__ void sincos8k(int n, float& s, float& c) {
  const float x = (float)((n << 19) >> 19) * (6.283185307179586f / 8192.f);
  s = __sinf(x); c = __cosf(x);
}
__device__ __forceinline__ void fft_tables(uint32_t f1a, uint32_t f2a, int w, int lane, uint32_t* tp, uint32_t* ts, float& d0r, float& d0i) {
  const int g = lane >> 2, c = lane & 3, f1 = 8 * w + g;
  uint32_t r[4], im[4], f2[4];
#pragma unroll
  for (int J = 0; J < 4; J++) {
    const int a = 8 * J + 2 * c;
    float s0, c0, s1, c1;
    sincos8k(64 * (4 * f1 + 1) * a + 31 * (4 * f1 - 63), s0, c0); sincos8k(64 * (4 * f1 + 1) * (a + 1) + 31 * (4 * f1 - 63), s1, c1);
    r[J] = pack_bf16(0.125f * c0, 0.125f * c1); im[J] = pack_bf16(0.125f * s0, 0.125f * s1);
    if (J == 0) { d0r = c == 0 ? 0.125f * c0 : 0.f; d0i = c == 0 ? 0.125f * s0 : 0.f; }
    sincos8k((4 * f1 - 63) * (2 * a - 31), s0, c0); sincos8k((4 * f1 - 63) * (2 * a - 29), s1, c1);
    ts[J] = pack_bf16(s0, s1); tp[J] = pack_bf16(-__fdividef(s0, 1.f + c0), -__fdividef(s1, 1.f + c1));
    if (J < 2) {
      sincos8k(128 * (2 * a + 1) * f1, s0, c0); sincos8k(128 * (2 * a + 3) * f1, s1, c1);
      f2[J] = pack_bf16(c0, c1); f2[J + 2] = pack_bf16(s0, s1);
    }
  }
  stsm4(f1a + w * 1024 + lane * 16, r[0], r[1], r[2], r[3]);
  stsm4(f1a + w * 1024 + 512 + lane * 16, im[0], im[1], im[2], im[3]);
  stsm4(f2a + w * 512 + lane * 16, f2[0], f2[1], f2[2], f2[3]);
}
__device__ __forceinline__ void tma3d_mc(uint32_t dst, const CUtensorMap* m, int c0, int c1, int c2, uint32_t bar) {
  asm volatile("cp.async.bulk.tensor.3d.shared::cluster.global.mbarrier::complete_tx::bytes.multicast::cluster [%0], [%1, {%3, %4, %5}], [%2], %6;"
               ::"r"(dst), "l"(m), "r"(bar), "r"(c0), "r"(c1), "r"(c2), "h"((uint16_t)3) : "memory");
}
__device__ __forceinline__ void ldsm4(uint32_t* r, uint32_t a) { asm volatile("ldmatrix.sync.aligned.m8n8.x4.shared.b16 {%0,%1,%2,%3}, [%4];" : "=r"(r[0]), "=r"(r[1]), "=r"(r[2]), "=r"(r[3]) : "r"(a) : "memory"); }
__device__ __forceinline__ void ldsm4t(uint32_t* r, uint32_t a) { asm volatile("ldmatrix.sync.aligned.m8n8.x4.trans.shared.b16 {%0,%1,%2,%3}, [%4];" : "=r"(r[0]), "=r"(r[1]), "=r"(r[2]), "=r"(r[3]) : "r"(a) : "memory"); }
__device__ __forceinline__ uint2 lds64(uint32_t a) { uint2 v; asm volatile("ld.shared.v2.u32 {%0,%1}, [%2];" : "=r"(v.x), "=r"(v.y) : "r"(a) : "memory"); return v; }
__device__ __forceinline__ void cmul(float ar, float ai, float br, float bi, float& cr, float& ci) {
  cr = ar * br - ai * bi; ci = ar * bi + ai * br;
}
__device__ __forceinline__ void csq(float& r, float& i) { const float x = fmaf(r, r, -i * i), y = (r + r) * i; r = x; i = y; }

template <int SWAPB>
__global__ void __cluster_dims__(2, 1, 1) __launch_bounds__(512, 1)
fused_kernel(const __grid_constant__ CUtensorMap mX, const __grid_constant__ CUtensorMap mB,
             const __grid_constant__ CUtensorMap mCre, const __grid_constant__ CUtensorMap mCim, const __grid_constant__ CUtensorMap mXs,
             const __grid_constant__ CUtensorMap mK, const __grid_constant__ CUtensorMap mV, const __grid_constant__ CUtensorMap mQ, const __grid_constant__ CUtensorMap mS,
             const __grid_constant__ Params P) {
  extern __shared__ __align__(1024) uint8_t smem_raw[];
  const uint32_t sb = (uint32_t)__cvta_generic_to_shared(smem_raw);
  const uint32_t bars = sb + OFF_BAR;
  int b = blockIdx.x, vb = b;
  if (MAPMODE) {
    const int cl = b >> 1;
    int col = 0, row = 4 + cl;
    if (cl >= 36) { row = 4 + (cl - 36) / 7; col = 1 + (cl - 36) % 7; }
    else if (cl >= 4) { row = (cl - 4) >> 3; col = (cl - 4) & 7; }
    if (VMAP) vb = 16 * col + 2 * row + (b & 1);
    if (MAPMODE == 1) b = 64 * (col >> 2) + 8 * row + 2 * (col & 3) + (b & 1);
    if (MAPMODE == 2) b = 8 * (4 * (col >> 1) + (row >> 1)) + 4 * (col & 1) + 2 * (row & 1) + (b & 1);
    if (MAPMODE == 3) b = 8 * (4 * (col >> 1) + (row & 3)) + 4 * (col & 1) + 2 * (row >> 2) + (b & 1);
    if (MAPMODE == 4) b = 8 * (2 * col + (row >> 2)) + 2 * (row & 3) + (b & 1);
  }
  const int tid = threadIdx.x;
  const int warp = __shfl_sync(0xffffffffu, tid >> 5, 0);
  const int wg = warp >> 2;
  const int rank = b & 1, j = b & 7, tc = b >> 3;
  const uint32_t c_start = clk32();
  auto kblock = [&](int n) { return (n & 16) + (ROT == 2 ? (n + 2 * (j & 6)) & 15 : ROT == 1 ? (n & 15) ^ (2 * (j & 4)) ^ ((n & 8) ? 0 : 2 * (j & 2)) : n & 15); };

  if (warp == 13 && elect_one()) { prefetch_map(&mB); prefetch_map(&mX); }
  if (warp == 12 && elect_one()) {
    STAMP(0);
#pragma unroll
    for (int s = 0; s < STAGES; s++) mbar_init(bars + (B_FULL + s) * 8, 1);
    asm volatile("fence.mbarrier_init.release.cluster;" ::: "memory");
  }
  if (warp == 14 && elect_one()) {
#pragma unroll
    for (int s = 0; s < STAGES; s++) mbar_init(bars + (B_EMPTY + s) * 8, COUPLE ? 2 : 1);
    mbar_init(bars + B_COEF * 8, 128);
    mbar_init(bars + B_HR * 8, 1);
    mbar_init(bars + B_HP * 8, 2);
    asm volatile("fence.mbarrier_init.release.cluster;" ::: "memory");
  }
  if (warp == 15 && elect_one()) {
#pragma unroll
    for (int s = B_KVF; s < B_QF; s++) mbar_init(bars + s * 8, s >= B_KVE && s < B_KF ? 4 : 1);
    asm volatile("fence.mbarrier_init.release.cluster;" ::: "memory");
  }
  if (warp == 11 && elect_one()) {
#pragma unroll
    for (int s = B_QF; s <= B_ACK; s++) mbar_init(bars + s * 8, (s >= B_QE && s < B_IN) || s == B_ACK ? 4 : 1);
    asm volatile("fence.mbarrier_init.release.cluster;" ::: "memory");
  }
  __syncwarp();
  asm volatile("barrier.cluster.arrive.relaxed.aligned;" ::: "memory");
  if (warp == 12 && elect_one()) {
    mbar_expect(bars + B_FULL * 8, STAGE_BYTES);
    tma4d(sb + OFF_RING, &mB, 0, 0, 0, 8 * j, bars + B_FULL * 8);
    if (!MC) { tma4d(sb + OFF_RING + 16384, &mX, 0, 0, 4 * tc, 0, bars + B_FULL * 8); STAMP(1); }
  }
  __syncwarp();
  asm volatile("barrier.cluster.wait.aligned;" ::: "memory");

  if (wg == 3) {
    asm volatile("setmaxnreg.dec.sync.aligned.u32 24;");
    const int lane = tid & 31;
    if (warp == 12) {
      uint32_t so = 8, ph = 1;
#pragma unroll 1
      for (int m = 1; m < 65; m++) {
        const int n = m - (m > XPOS);
        if (n < STAGES && ST_DELAY) spin_until(clk32(), ST_DELAY);
        mbar_wait(bars + B_EMPTY * 8 + so, ph);
        if (elect_one()) {
          const uint32_t fb = bars + B_FULL * 8 + so, dst = sb + OFF_RING + (so << 12);
          mbar_expect(fb, STAGE_BYTES);
          if (m == XPOS) tma4d(dst, &mXs, 128 * j, 0, 0, 16 * tc, fb);
          else if (n < 32) tma4d(dst, &mB, (n & 15) * 64, 0, 0, 8 * j + 4 * (n & 16), fb);
          else tma5d(dst, (n & 1) ? &mCim : &mCre, (kblock(n) & ~1) * 32, 0, 0, 0, 8 * j, fb);
        }
        __syncwarp();
        if (m == XPOS) asm volatile("bar.arrive 6, 160;" ::: "memory");
        so += 8;
        if (so == 8 * STAGES) { so = 0; ph ^= 1; }
      }
    } else if (warp == 13) {
      uint32_t so = MC ? 0 : 8, ph = 1;
#pragma unroll 1
      for (int m = MC ? 0 : 1; m < 65; m++) {
        const int n = m - (m > XPOS);
        if (n > 0 && n < STAGES && ST_DELAY) spin_until(clk32(), ST_DELAY);
        if (n == 32 || n == 48) {
          if (lane == 0) STAMP(2 + (n >> 4));
          mbar_wait(bars + (ROT ? B_HP : B_HR) * 8, (n >> 4) & 1);
          fence_proxy_async_global();
          if (lane == 0) STAMP(4 + (n >> 4));
        }
        if (n == 36 || n == 52) { mbar_wait(bars + B_HR * 8, (n >> 4) & 1); fence_proxy_async_global(); }
        mbar_wait(bars + B_EMPTY * 8 + so, ph);
        if (elect_one()) {
          const uint32_t fb = bars + B_FULL * 8 + so, dst = sb + OFF_RING + (so << 12) + 16384;
          if (m == XPOS) tma4d(dst, &mXs, 128 * j + 64, 0, 0, 16 * tc, fb);
          else if (MC) {
            if (n < 32) tma4d_mc(dst + rank * 8192, &mX, (n & 15) * 64, 0, 4 * tc, 8 * rank, fb);
            else bulk_load_mc(dst + rank * 8192, g_h + (32 * tc + kblock(n)) * 1024 + 512 * rank, 8192, fb);
          } else {
            if (n < 32) tma4d(dst, &mX, (n & 15) * 64, 0, 4 * tc, 0, fb);
            else bulk_load(dst, g_h + (32 * tc + kblock(n)) * 1024, 16384, fb);
          }
          if (n == 0) STAMP(1);
          TSTAMP(1, n);
        }
        __syncwarp();
        so += 8;
        if (so == 8 * STAGES) { so = 0; ph ^= 1; }
      }
    } else if (warp == 15) {
      auto pf_rows = [&](const __nv_bfloat16* p, int rows, int l0, int l1, uint32_t t0, uint32_t dt) {
        const int nl = l1 - l0;
#pragma unroll 1
        for (int i = lane; i < rows * nl + lane; i += 32) {
          wait_until(c_start, t0); t0 += dt;
          if (i < rows * nl) prefetch_line(p + (size_t)(i / nl) * D_DIM + 64 * (l0 + i % nl));
        }
      };
      if (PF & 1) {
#pragma unroll
        for (int r = 0; r < 2; r++) {
          const int l0 = r ? PF_MID : STAGES, l1 = r ? 16 : PF_MID;
          pf_rows(P.x + (size_t)16 * b * D_DIM, 16, l0, l1, PF_T1 + r * PF_T2, PF_DT);
          pf_rows(P.B_re + (size_t)4 * b * D_DIM, 4, l0, l1, 0, 0);
          pf_rows(P.B_im + (size_t)4 * b * D_DIM, 4, l0, l1, 0, 0);
        }
      }
      if (PF & 2) {
#pragma unroll 1
        for (int e = 0; e < 8; e++) {
          const int row = 32 * (b >> 1) + ((4 * e - 4) & 31) + 2 * (b & 1);
          pf_rows(P.k + (size_t)row * D_DIM, 2, 0, 16, KV_T0 - PF_KV + 2 * e * KV_DT, 0);
          pf_rows(P.v + (size_t)(32 * (b >> 1) + 4 * e + 2 * (b & 1)) * D_DIM, 2, 0, 16, KV_T0 - PF_KV + (2 * e + 1) * KV_DT, 0);
        }
      }
      if (PF & 4) {
        pf_rows(P.B_re + (size_t)(512 + 4 * b) * D_DIM, 4, 0, 16, PF_T3, PF_DT);
        pf_rows(P.B_im + (size_t)(512 + 4 * b) * D_DIM, 4, 0, 16, 0, PF_DT);
      }
      if (PF & 8) {
        pf_rows(P.C_re + (size_t)(8 * b) * D_DIM, 8, 0, 16, PF_T4, PF_DT4);
        pf_rows(P.C_im + (size_t)(8 * b) * D_DIM, 8, 0, 16, PF_T4 + 4 * PF_DT4, PF_DT4);
      }
      mbar_wait(bars + B_COEF * 8, 0);
      const unsigned epoch = lds32(bars + B_EPOCH * 8);
#pragma unroll 1
      for (int v = 0; v < 2; v++) {
        unsigned* fp = &g_flagH[(16 * v + tc) * 32];
        bar_sync(4 + v, 160);
        if (elect_one()) red_release(fp, 1);
        __syncwarp();
        if (lane < 2) mbar_arrive_cta(bars + B_HP * 8, lane);
        if (lane == 0) STAMP(16 + 10 * v);
        int it = 0;
        while (ld_acquire(fp) != 8 * epoch && ++it < (SPIN_LIMIT << 4)) __nanosleep(POLL_NS);
        if (lane == 0) STAMP(2 + v);
        if (lane == 0) mbar_arrive(bars + B_HR * 8);
      }
    } else if (warp == 14) {
      if (elect_one()) { prefetch_map(&mK); prefetch_map(&mV); }
      __syncwarp();
      const int ch0 = 16 * (vb >> 1);
      {
        uint32_t so = 16, ph = 1;
#pragma unroll 1
        for (int e = 0; e < 9; e++) {
          const uint32_t fb = bars + B_KVF * 8 + so, dst = sb + OFF_KV + (so << 10);
          wait_until(c_start, KV_T0 + (e ? 2 * e - 1 : 0) * KV_DT);
          if (e == 2 && elect_one()) { prefetch_map(&mS); prefetch_map(&mCre); prefetch_map(&mCim); prefetch_map(&mXs); prefetch_map(&mQ); }
          if (e >= 3) mbar_wait(bars + B_KVE * 8 + so, ph);
          const uint32_t c1 = clk32();
          if (elect_one()) {
            mbar_expect(fb, e ? 8192 : 4096);
            if (e > 0) KSTAMP(1, e - 1);
            tma3d(dst, &mK, ch0, 32 * rank - (e == 0), (4 * e - 4) & 31, fb);
            if (KV_PF && e + KV_PF <= 8) {
              const int row = 32 * (b >> 1) + 4 * (e + KV_PF - 1) + 2 * (b & 1);
              prefetch_l2(P.k + (size_t)row * D_DIM, 4096); prefetch_l2(P.v + (size_t)row * D_DIM, 4096);
            }
            if (e == 5) prefetch_l2(P.ssm_k + (size_t)(8 * vb) * S_LEN, 8192);
          }
          __syncwarp();
          if (e > 0) {
            wait_until(c1, KV_DV);
            if (elect_one()) tma3d(dst + 4096, &mV, ch0, 32 * rank, 4 * e - 4, fb);
            __syncwarp();
          }
          so += 8;
          if (so == 24) so = 0;
          if (so == 16) ph ^= 1;
        }
      }
      auto load_q = [&](int i, uint32_t so) {
        if (elect_one()) { mbar_expect(bars + B_QF * 8 + so, 4096); tma3d(sb + OFF_Q + (so << 9), &mQ, ch0, 32 * rank, 4 * i, bars + B_QF * 8 + so); }
        __syncwarp();
      };
      {
#pragma unroll 1
        for (int s = 0; s < 8; s++) {
          const uint32_t so = 8 * (s & 1);
          if (s == 0) mbar_wait(bars + B_KVE * 8, 0);
          if (s >= 2) mbar_wait(bars + B_KE * 8 + so, ((s >> 1) & 1) ^ 1);
          if (elect_one()) { mbar_expect(bars + B_KF * 8 + so, 4096); tma2d(sb + OFF_K + (so << 9), &mS, 0, 64 * (8 * vb + s), bars + B_KF * 8 + so); }
          __syncwarp();
          if (s == 7) mbar_wait(bars + B_UA * 8, 0);
          if (s >= 5) load_q(s - 5, 8 * (s - 5));
        }
        uint32_t so = 0, ph = 0;
#pragma unroll 1
        for (int i = 3; i < 8; i++) {
          mbar_wait(bars + B_QE * 8 + so, ph);
          load_q(i, so);
          so += 8;
          if (so == 24) { so = 0; ph ^= 1; }
        }
      }
    }
  } else if (wg == 2) {
    asm volatile("setmaxnreg.inc.sync.aligned.u32 136;");
    const int t = tid & 127, w = warp & 3, lane = t & 31, g = lane >> 2, c = lane & 3;
    const uint4 s2[2] = {ldg128_nc(P.shift_k + (8 * vb + 2 * c) * 4), ldg128_nc(P.shift_k + (8 * (vb ^ 1) + 2 * c) * 4)};
    if (t < 8) asm volatile("st.shared.u32 [%0], %1;" ::"r"(sb + OFF_D + 4 * t), "r"((uint32_t)__bfloat16_as_ushort(P.ssm_D[8 * vb + t]) << 16) : "memory");
    if (t < 8) mbar_expect(bars + (B_IN + t) * 8, U_N8);
    uint32_t tp[4], ts[4];
    float d0r, d0i;
    fft_tables(sb + OFF_F1, sb + OFF_F2, w, lane, tp, ts, d0r, d0i);
    if (t == 0) STAMP(19);
    auto send = [&](uint32_t dst, uint32_t src, uint32_t bar) {
      asm volatile("{\n.reg .b32 rd, rb;\nmapa.shared::cluster.u32 rd, %0, %3;\nmapa.shared::cluster.u32 rb, %2, %3;\n"
                   "cp.async.bulk.shared::cluster.shared::cta.mbarrier::complete_tx::bytes [rd], [%1], %4, [rb];\n}\n"
                   ::"r"(dst), "r"(src), "r"(bar), "r"(rank ^ 1), "n"(U_N8) : "memory");
    };
    {
      uint32_t sk[2][4], kx[2][8];
#pragma unroll
      for (int o = 0; o < 2; o++) {
        sk[o][0] = __byte_perm(s2[o].x, s2[o].z, 0x5410); sk[o][1] = __byte_perm(s2[o].x, s2[o].z, 0x7632);
        sk[o][2] = __byte_perm(s2[o].y, s2[o].w, 0x5410); sk[o][3] = __byte_perm(s2[o].y, s2[o].w, 0x7632);
      }
      const uint32_t la = sb + OFF_KV + (lane >> 3) * 1024 + (8 * w + (lane & 7)) * 32 + ((rank ^ ((lane >> 2) & 1)) << 4);
      const uint32_t uo = (lane & 7) * U_CH + w * 128 + (lane >> 3) * 16;
      MBAR_LONG(bars + (B_KVF + 2) * 8, 0);
      if (t == 0) STAMP(27);
      ldsm4(kx[0], la + 16384); ldsm4(kx[1], (la ^ 16) + 16384);
      __syncwarp();
      if (lane == 0) mbar_arrive(bars + (B_KVE + 2) * 8 + ((kx[0][1] ^ kx[1][1]) & P.zero));
      uint32_t so = 0, ph = 0;
#pragma unroll 1
      for (int e = 0; e < 8; e++) {
        const int n = e >> 1;
        const uint32_t own = sb + OFF_U + (4 * rank + n) * U_N8, box = n < 3 ? sb + OFF_U + (4 * (rank ^ 1) + n + 1) * U_N8 : sb + OFF_Q + 8192;
        uint32_t vx[2][4];
        MBAR_LONG(bars + B_KVF * 8 + so, ph);
        if (t == 0) KSTAMP(2, e);
#pragma unroll
        for (int o = 0; o < 2; o++) { ldsm4(kx[o] + 4, (la ^ (16 * o)) + (so << 10)); ldsm4(vx[o], (la ^ (16 * o)) + (so << 10) + 4096); }
#pragma unroll
        for (int o = 0; o < 2; o++) {
#pragma unroll
          for (int i = 0; i < 4; i++) vx[o][i] = bmul2(bfma2(kx[o][i + 4], sk[o][0], bfma2(kx[o][i + 3], sk[o][1], bfma2(kx[o][i + 2], sk[o][2], bmul2(kx[o][i + 1], sk[o][3])))), vx[o][i]);
          stsm4t((o ? box : own) + uo + (e & 1) * 64, vx[o][0], vx[o][1], vx[o][2], vx[o][3]);
          kx[o][1] = kx[o][5]; kx[o][2] = kx[o][6]; kx[o][3] = kx[o][7];
        }
        if (lane == 0) mbar_arrive(bars + B_KVE * 8 + so + (vx[0][3] & vx[1][3] & P.zero));
        if (e & 1) {
          fence_proxy_async_smem();
          bar_sync(7, 128);
          if (w == 0) {
            if (n > 0) mbar_wait(bars + B_UF * 8 + 8 * (n - 1), 0);
            if (elect_one()) send(own, box, bars + B_UF * 8 + 8 * n);
            __syncwarp();
          }
        }
        if (t == 0) KSTAMP(3, e);
        so += 8;
        if (so == 24) so = 0;
        if (so == 16) ph ^= 1;
      }
      if (t == 0) STAMP(28);
    }
    constexpr int nch = 8;
    {
#define ORDER 0
      const uint64_t dF1a = make_desc(sb + OFF_F1, 128, 512, 0), dF1b = make_desc(sb + OFF_F1, 512, 128, 0);
      const uint64_t dF2f = make_desc(sb + OFF_F2, 512, 128, 0), dF2i = make_desc(sb + OFF_F2, 128, 512, 0);
      auto T1k = [&](float* z, uint32_t ks) {
        const uint64_t dk = make_desc(sb + OFF_K, 2048, 512, 2) + (ks << 5);
        ss_n64<0, 1>(z, dF1a, dk); ss_n64<1, 1>(z, dF1a + 16, dk + 64);
      };
      auto T1u = [&](float* z, int ch) {
        const uint64_t du = make_desc(sb + OFF_U, 128, U_N8, 0) + ch * (U_CH / 16);
        ss_n64<0, 0>(z, dF1a, du); ss_n64<1, 0>(z, dF1a + 16, du + 16);
      };
      auto T2 = [&](float* s, const uint32_t* f) {
        rs_n32<0, 1>(s, f, dF2f); rs_n32<0, 1>(s + 16, f + 8, dF2f); rs_n32<1, 1>(s, f + 4, dF2f + 64); rs_n32<1, 1>(s + 16, f + 12, dF2f + 64);
      };
#define CP(i)
#define CF(i) PMFENCE()
      const uint32_t vs = w < 2 ? 512 : U_N8, vo = ((lane >> 4) & 1) * vs + (w & 1) * 256 + (lane & 15) * 16;
      uint32_t pr[16];
      float zk[32] = {};
      auto body = [&](int ch, auto inv, auto fwd) {
        constexpr bool INV = decltype(inv)::value, FWD = decltype(fwd)::value;
        float zu[32], sk[32], su[32], v[32], y[16];
        uint32_t kh[16], uh[16], fk[16], fu[16], fv[16];
        if (INV) {
          wg_fence();
          rs_n32<0, 0>(v, pr, dF2i); rs_n32<0, 0>(v + 16, pr + 8, dF2i); rs_n32<1, 0>(v, pr + 4, dF2i + 16); rs_n32<1, 0>(v + 16, pr + 12, dF2i + 16);
          wg_commit();
        }
        CF(0);
        if (FWD) {
          const float dd = __uint_as_float(lds32(sb + OFF_D + 4 * (ch + 1)));
          zk[0] = fmaf(d0r, dd, zk[0]); zk[2] = fmaf(d0i, dd, zk[2]);
          pack32(fk, zk); twiddle<0>(fk, tp, ts); fence_u32<16>(fk);
          CP(1);
          wg_fence(); T2(sk, fk); wg_commit();
          CF(2);
        }
        if (INV) {
          if (FWD) wg_wait<1>(); else wg_wait<0>();
          fence_regs<32>(v); fence_u32<16>(pr); CP(3);
          pack32(fv, v); fence_u32<16>(fv);
        }
        CF(4);
        if (!INV) {
#pragma unroll
          for (int n = 0; n < 4; n++) mbar_wait(bars + (B_UF + n) * 8, 0);
          if (t == 0) mbar_arrive_cta(bars + B_UA * 8, rank ^ 1);
        }
        if (FWD) { wg_fence(); T1u(zu, ch + 1); wg_commit(); }
        CF(5);
        if (INV) {
          twiddle<1>(fv, tp, ts);
          const uint32_t va = (w < 2 ? sb + OFF_VP : sb + OFF_U + ch * U_CH) + vo;
#pragma unroll
          for (int i = 0; i < 4; i++) stsm4(va + 2 * i * vs, fv[4 * i], fv[4 * i + 1], fv[4 * i + 2], fv[4 * i + 3]);
        }
        CF(6);
        if (FWD) {
          wg_wait<1>(); fence_regs<32>(sk); fence_u32<16>(fk); pack32(kh, sk); fence_u32<16>(kh);
          CF(7);
          if (ch < 6) mbar_wait(bars + B_KF * 8 + 8 * (ch & 1), ((ch >> 1) & 1) ^ 1);
          wg_fence(); T1k(zk, 8 * (ch & 1)); wg_commit();
          CF(8);
          wg_wait<1>(); fence_regs<32>(zu);
          pack32(fu, zu); twiddle<0>(fu, tp, ts); fence_u32<16>(fu);
          CP(9);
          if (ORDER == 1 && INV) fence_proxy_async_smem();
          wg_fence(); T2(su, fu); wg_commit();
          CF(10);
        }
        if (INV) {
          if (ORDER == 0 || !FWD) fence_proxy_async_smem();
          bar_sync(7, 128);
          CP(11);
          const uint64_t dk = make_desc(sb + OFF_VP, 128, 512, 0), du = make_desc(sb + OFF_U, 128, U_N8, 0) + ch * (U_CH / 16);
          wg_fence();
          ss_n32_tt<0>(y, dk, dF1b); ss_n32_tt<1>(y, dk + 16, dF1b + 64); ss_n32_tt<1>(y, du, dF1b + 128); ss_n32_tt<1>(y, du + 16, dF1b + 192);
          wg_commit();
        }
        CF(12);
        if (FWD) {
          if (INV) wg_wait<1>(); else wg_wait<0>();
          fence_regs<32>(su); fence_u32<16>(fu); CP(13);
          pack32(uh, su);
          bimac<1>(pr, kh, uh, pr);
#pragma unroll
          for (int i = 0; i < 4; i++) { pr[8 + 2 * i] = pr[2 * i + 1]; pr[9 + 2 * i] = NEGOP(pr[2 * i]); }
          bimac<0>(pr + 8, kh + 8, uh, pr + 8); bimac<0>(pr + 8, kh, uh + 8, pr + 8);
          fence_u32<16>(pr);
        }
        CF(14);
        wg_wait<0>();
        if (FWD) { fence_regs<32>(zk); if (t == 0) mbar_arrive(bars + B_KE * 8 + 8 * (ch & 1)); }
        if (INV) {
          fence_regs<16>(y); CP(15);
          const uint32_t ya = sb + OFF_U + ch * U_CH + (2 * w + ((lane >> 3) & 1)) * U_N8 + (lane >> 4) * 128 + (lane & 7) * 16;
#pragma unroll
          for (int i = 0; i < 2; i++) stsm4(ya + i * 256, pack_bf16(y[8 * i], y[8 * i + 1]), pack_bf16(y[8 * i + 2], y[8 * i + 3]), pack_bf16(y[8 * i + 4], y[8 * i + 5]), pack_bf16(y[8 * i + 6], y[8 * i + 7]));
        }
        if (t == 0) STAMP(55 + ch);
      };
      mbar_wait(bars + B_KF * 8, 0);
      wg_fence(); T1k(zk, 0); wg_commit(); wg_wait<0>(); fence_regs<32>(zk);
      if (t == 0) mbar_arrive(bars + B_KE * 8);
      body(-1, std::false_type(), std::true_type());
#pragma unroll 1
      for (int ch = 0; ch < nch - 1; ch++) body(ch, std::true_type(), std::true_type());
      body(nch - 1, std::true_type(), std::false_type());
    }
    {
      fence_proxy_async_smem();
      bar_sync(7, 128);
      if (t == 0) STAMP(29);
      if (w == 0) {
        if (lane == 0) mbar_arrive_cta(bars + B_RDY * 8, rank ^ 1);
        mbar_wait(bars + B_RDY * 8, 0);
        if (lane < 4) send(sb + OFF_IN + lane * U_N8, sb + OFF_U + (4 * (rank ^ 1) + lane) * U_N8, bars + (B_IN + lane) * 8);
        __syncwarp();
      }
      uint32_t ya = (((lane >> 2) & 1) == rank ? sb + OFF_U + 4 * rank * U_N8 : sb + OFF_IN) + (2 * (lane & 2) + (lane & 1) + ((lane >> 2) & 2)) * U_CH + w * 128 + (lane >> 4) * 16;
      const uint32_t qa = sb + OFF_Q + (8 * w + g) * 32 + 8 * c;
      float* op = P.out + (size_t)(1024 * rank + 32 * (8 * w + g)) * 2048 + 16 * (vb >> 1) + 4 * c;
      uint32_t so = 0, ph = 0, oc = 0;
#pragma unroll 1
      for (int i = 0; i < 8; i++) {
        if (!(i & 1)) mbar_wait(bars + B_IN * 8 + 4 * i, 0);
        if (i == 6 && lane == 0) mbar_arrive_cta(bars + B_ACK * 8, rank ^ 1);
        mbar_wait(bars + B_QF * 8 + so, ph);
        if (i == 0) { oc = clk32() + w * (O_PACE / 4); if (t == 0) STAMP(30); }
        uint32_t y[8];
        ldsm4t(y, ya); ldsm4t(y + 4, ya + 32);
#pragma unroll
        for (int r = 0; r < 4; r++) { const uint2 q = lds64(qa + (so << 9) + r * 1024); y[2 * r] = bmul2(y[2 * r], q.x); y[2 * r + 1] = bmul2(y[2 * r + 1], q.y); }
        if (lane == 0) mbar_arrive(bars + B_QE * 8 + so + (y[0] & y[2] & y[4] & y[6] & P.zero));
#pragma unroll
        for (int r = 0; r < 4; r++) {
          while ((int)(clk32() - oc) < 0) __nanosleep(20);
          oc += O_PACE;
          stg128(op + (size_t)r * 2048, make_uint4(y[2 * r] << 16, y[2 * r] & 0xffff0000u, y[2 * r + 1] << 16, y[2 * r + 1] & 0xffff0000u));
        }
        op += 4 * 2048;
        ya += (i & 1) ? U_N8 - 64 : 64;
        so += 8;
        if (so == 24) { so = 0; ph ^= 1; }
      }
      if (t == 0) STAMP(31);
      mbar_wait(bars + B_ACK * 8, 0);
    }
  } else {
    asm volatile("setmaxnreg.inc.sync.aligned.u32 176;");
    const int t = tid & 127, w = warp & 3, lane = t & 31, g = lane >> 2, c = lane & 3;
    if (wg == 1) {
      if (t < 16) sts128(sb + OFF_DS + 16 * t, ldg128_nc(P.Dskip + 128 * j + 8 * t));
      const unsigned epoch = ld_relaxed(&g_epoch[b * 32]) + 1;
      const int p = 64 * j + (t & 63) + 8 * (t & 64);
      const float Lr = bf2f(P.lam_re[p]), Li = bf2f(P.lam_im[p]);
      const float dt = bf2f(__float2bfloat16_rn(expf(bf2f(P.log_dt[p]))));
      const float e = expf(dt * Lr);
      float sn, cs;
      sincosf(dt * Li, &sn, &cs);
      const float lr = e * cs, li = e * sn;
      const float nr = lr - 1.0f, ni = li;
      float br, bi;
      if (fabsf(Lr) >= fabsf(Li)) { const float r = Li / Lr, den = Lr + Li * r; br = (nr + ni * r) / den; bi = (ni - nr * r) / den; }
      else { const float r = Lr / Li, den = Lr * r + Li; br = (nr * r + ni) / den; bi = (ni * r - nr) / den; }
      sts128(sb + OFF_COEF + t * 16, make_uint4(__float_as_uint(lr), __float_as_uint(li), pack_bf16(2.f * br, 2.f * br), pack_bf16(-2.f * bi, -2.f * bi)));
      if (t == 0) asm volatile("st.shared.u32 [%0], %1;" ::"r"(bars + B_EPOCH * 8), "r"(epoch) : "memory");
      mbar_arrive(bars + B_COEF * 8);
    }
    float d[128];
    uint32_t so = 0, ph = 0, po = 0;
    auto block = [&](auto ta, uint64_t da0, uint64_t db0, bool first, bool zero, int nn) {
      constexpr int TA = decltype(ta)::value, KS = TA ? 128 : 2;
      if (t == 0) TSTAMP(2, nn);
      mbar_wait(bars + B_FULL * 8 + so, ph);
      if (t == 0) TSTAMP(3, nn);
      const uint64_t da = da0 + (so << 8), db = db0 + (so << 8);
      wg_fence();
      wgmma_n128<TA>(d, da, db, !zero);
      wgmma_n128<TA>(d + 64, da + 512, db, !zero);
      wg_commit();
      wg_wait<1>();
      if (!first) release_stage(bars + B_EMPTY * 8 + po, t);
#pragma unroll
      for (int k = 1; k < 4; k++) {
        if (QD == 2 || (QD == 4 && k == 2)) wg_fence();
        wgmma_n128<TA>(d, da + KS * k, db + 2 * k, 1);
        wgmma_n128<TA>(d + 64, da + 512 + KS * k, db + 2 * k, 1);
        if (QD == 2) { wg_commit(); if (k < 3) wg_wait<1>(); }
        if (QD == 4 && k == 1) { wg_commit(); wg_wait<1>(); }
      }
      if (QD != 2) wg_commit();
      po = so;
      so += 8;
      if (so == 8 * STAGES) { so = 0; ph ^= 1; }
    };
    {
      so = wg ? 8 * (16 % STAGES) : 0; ph = wg ? (16 / STAGES) & 1 : 0; po = 0;
      const uint64_t da0 = make_desc(sb + OFF_RING, 16, 1024, 1), db0 = make_desc(sb + OFF_RING + 16384, 16, 1024, 1);
      if (wg == 1) bar_sync(1, 256);
#pragma unroll 1
      for (int kb = 0; kb < 16; kb++) {
        if ((kb & 3) == 0 && t == 0) STAMP(32 + 4 * wg + (kb >> 2));
        if (16 * wg + kb == XPOS) { so += 8; if (so == 8 * STAGES) { so = 0; ph ^= 1; } }
        block(std::false_type(), da0, db0, kb == 0, kb == 0, 16 * wg + kb);
        if (kb == 0 && tid == 0) STAMP(8);
      }
      asm volatile("bar.arrive %0, 256;" ::"r"(1 + wg) : "memory");
    }
    mbar_wait(bars + B_COEF * 8, 0);
    const unsigned epoch = lds32(bars + B_EPOCH * 8);
    const uint32_t ca = sb + OFF_COEF + (64 * wg + 8 * w + g) * 16;
    const uint32_t tag = epoch & 3;
    uint4* cp = &g_carry[((8 * wg + j) * 16 + tc) * 32 + 8 * w + g];
    constexpr int RE = SWAPB ? 2 : 0, IM = 2 - RE;
    float lr[2], li[2], wr[2], wi[2], vr[2], vi[2], qr[2], qi[2], er[2], ei[2];
    uint32_t c0;
    {
      float pr[2], pi[2];
#pragma unroll
      for (int i = 0; i < 2; i++) {
        const uint4 cf = lds128(ca + 512 * i);
        pr[i] = lr[i] = __uint_as_float(cf.x); pi[i] = li[i] = __uint_as_float(cf.y);
#pragma unroll
        for (int s = 0; s < 5; s++) csq(pr[i], pi[i]);
        qr[i] = pr[i]; qi[i] = pi[i];
        csq(qr[i], qi[i]);
        asm volatile("" : "+f"(pr[i]), "+f"(pi[i]), "+f"(qr[i]), "+f"(qi[i]));
      }
      PMFENCE();
      wg_wait<0>();
      fence_regs<128>(d);
      release_stage(bars + B_EMPTY * 8 + po, t);
      if (t == 0) STAMP(10 + 10 * wg);
      float sr[2], si[2];
#pragma unroll
      for (int i = 0; i < 2; i++) {
        const float* e = d + 64 * i;
        sr[i] = e[RE]; si[i] = e[IM];
#pragma unroll
        for (int s = 1; s < 32; s++) {
          const int ia = 4 * (s >> 1) + (s & 1);
          const float nr = fmaf(-li[i], si[i], fmaf(lr[i], sr[i], e[ia + RE])), ni = fmaf(li[i], sr[i], fmaf(lr[i], si[i], e[ia + IM]));
          sr[i] = nr; si[i] = ni;
        }
        if (!(GREEDY & 1)) asm volatile("pmevent 0;" : "+f"(sr[i]), "+f"(si[i])::"memory");
      }
#pragma unroll
      for (int i = 0; i < 2; i++) {
        float ur = __shfl_up_sync(0xffffffffu, sr[i], 1, 4), ui = __shfl_up_sync(0xffffffffu, si[i], 1, 4);
        if (c >= 1) { sr[i] = fmaf(pr[i], ur, fmaf(-pi[i], ui, sr[i])); si[i] = fmaf(pr[i], ui, fmaf(pi[i], ur, si[i])); }
        ur = __shfl_up_sync(0xffffffffu, sr[i], 2, 4); ui = __shfl_up_sync(0xffffffffu, si[i], 2, 4);
        if (c >= 2) { sr[i] = fmaf(qr[i], ur, fmaf(-qi[i], ui, sr[i])); si[i] = fmaf(qr[i], ui, fmaf(qi[i], ur, si[i])); }
      }
      if (c == 3 && tc < 15)
        asm volatile("{\n.reg .b64 a, b;\n.reg .b128 v;\nmov.b64 a, {%1,%2};\nmov.b64 b, {%3,%4};\nmov.b128 v, {a,b};\nst.relaxed.gpu.global.b128 [%0], v;\n}\n"
                     ::"l"(cp), "r"((__float_as_uint(sr[0]) & ~3u) | tag), "r"(__float_as_uint(si[0])), "r"(__float_as_uint(sr[1])), "r"(__float_as_uint(si[1])) : "memory");
      PMFENCE();
      if (t == 0) STAMP(11 + 10 * wg);
      c0 = clk32();
#pragma unroll
      for (int i = 0; i < 2; i++) {
        er[i] = __shfl_up_sync(0xffffffffu, sr[i], 1, 4); ei[i] = __shfl_up_sync(0xffffffffu, si[i], 1, 4);
        if (c == 0) er[i] = ei[i] = 0.f;
        wr[i] = (c & 1) ? pr[i] : 1.f; wi[i] = (c & 1) ? pi[i] : 0.f;
        if (c & 2) { float x, y; cmul(wr[i], wi[i], qr[i], qi[i], x, y); wr[i] = x; wi[i] = y; }
        vr[i] = wr[i]; vi[i] = wi[i];
        csq(vr[i], vi[i]); csq(vr[i], vi[i]);
        csq(qr[i], qi[i]); csq(qr[i], qi[i]); csq(qr[i], qi[i]);
        asm volatile("pmevent 0;" : "+f"(wr[i]), "+f"(wi[i]), "+f"(vr[i]), "+f"(vi[i]), "+f"(qr[i]), "+f"(qi[i]), "+f"(er[i]), "+f"(ei[i]));
      }
    }
    float sr[2], si[2];
    uint32_t gp[2], gn[2], gms[2];
    {
      uint4 cv[4];
      cp -= 32 * (1 + c);
      auto load_carry = [&]() {
#pragma unroll
        for (int m = 0; m < 4; m++)
          asm volatile("{\n.reg .pred p;\nsetp.lt.s32 p, %5, %6;\n.reg .b64 a, b;\n.reg .b128 v;\nmov.b64 a, {%0,%1};\nmov.b64 b, {%2,%3};\nmov.b128 v, {a,b};\n"
                       "@p ld.relaxed.gpu.global.b128 v, [%4];\nmov.b128 {a,b}, v;\nmov.b64 {%0,%1}, a;\nmov.b64 {%2,%3}, b;\n}\n"
                       : "+r"(cv[m].x), "+r"(cv[m].y), "+r"(cv[m].z), "+r"(cv[m].w) : "l"(cp - 128 * m), "r"(c), "r"(tc - 4 * m) : "memory");
      };
#pragma unroll
      for (int m = 0; m < 4; m++) cv[m] = make_uint4(tag, 0, 0, 0);
      wait_until(c0, CARRY_WAIT);
      if (t == 0) STAMP(12 + 10 * wg);
      load_carry();
      int n = 0;
#pragma unroll 1
      while (true) {
        uint32_t bad = 0;
#pragma unroll
        for (int m = 0; m < 4; m++) bad |= cv[m].x ^ tag;
        if (__all_sync(0xffffffffu, (bad & 3) == 0) || ++n > (SPIN_LIMIT << 4)) break;
        load_carry();
      }
      if (t == 0) STAMP(13 + 10 * wg);
#pragma unroll
      for (int i = 0; i < 2; i++) {
        float hr = __uint_as_float((i ? cv[3].z : cv[3].x)), hi = __uint_as_float((i ? cv[3].w : cv[3].y));
#pragma unroll
        for (int m = 2; m >= 0; m--) {
          const float x = __uint_as_float((i ? cv[m].z : cv[m].x)), y = __uint_as_float((i ? cv[m].w : cv[m].y));
          const float nr = fmaf(qr[i], hr, fmaf(-qi[i], hi, x)), ni = fmaf(qr[i], hi, fmaf(qi[i], hr, y));
          hr = nr; hi = ni;
        }
        { float x, y; cmul(hr, hi, vr[i], vi[i], x, y); hr = x; hi = y; }
        const uint4 cf = lds128(ca + 512 * i);
        lr[i] = __uint_as_float(cf.x); li[i] = __uint_as_float(cf.y); gp[i] = cf.z; gn[i] = cf.z ^ 0x80008000u; gms[i] = cf.w;
        hr += __shfl_xor_sync(0xffffffffu, hr, 1); hi += __shfl_xor_sync(0xffffffffu, hi, 1);
        hr += __shfl_xor_sync(0xffffffffu, hr, 2); hi += __shfl_xor_sync(0xffffffffu, hi, 2);
        sr[i] = fmaf(wr[i], hr, fmaf(-wi[i], hi, er[i])); si[i] = fmaf(wr[i], hi, fmaf(wi[i], hr, ei[i]));
      }
    }
    if (t == 0) STAMP(14 + 10 * wg);
    const int trow = 128 * tc + 64 * (w & 1) + 8 * (w >> 1) + g;
    const int dcol = 128 * j + 4 * c;
    {
      const uint32_t hc0 = H_PACE ? clk32() - (3 - w) * (H_PACE / 4) : 0;
      uint4* hp = g_h + (32 * tc + 16 * wg + 2 * j) * 1024 + 64 * w + 4 * g + (c ^ (g >> 1));
#pragma unroll
      for (int u = 0; u < 8; u++) {
        const int i = (GREEDY & 2) ? u & 1 : u >> 2, i8 = (GREEDY & 2) ? u >> 1 : u & 3;
        float* e = d + 64 * i;
        if (!(GREEDY & 2) || i == 0) asm volatile("pmevent 0;" : "+f"(sr[0]), "+f"(si[0]), "+f"(sr[1]), "+f"(si[1])::"memory");
#pragma unroll
        for (int s = 8 * i8; s < 8 * i8 + 8; s++) {
          const int ia = 4 * (s >> 1) + (s & 1);
          const float nr = fmaf(-li[i], si[i], fmaf(lr[i], sr[i], e[ia + RE])), ni = fmaf(li[i], sr[i], fmaf(lr[i], si[i], e[ia + IM]));
          sr[i] = nr; si[i] = ni;
          e[ia + RE] = nr; e[ia + IM] = ni;
        }
        if (P2_SPLIT) PMFENCE();
        uint32_t hr[4], hn[4];
#pragma unroll
        for (int m = 0; m < 4; m++) {
          const float* f = e + 16 * i8 + 4 * m;
          const uint32_t x = pack_bf16(f[RE], f[RE + 1]), y = pack_bf16(f[IM], f[IM + 1]);
          hr[m] = bfma2(gp[i], x, bmul2(gms[i], y)); hn[m] = bfma2(gn[i], y, bmul2(gms[i], x));
        }
#pragma unroll
        for (int part = 0; part < 2; part++) {
          if (H_PACE) { while (clk32() - hc0 < (2 * u + part) * H_PACE) __nanosleep(20); }
          const uint32_t* f = part ? hn : hr;
          stg128(hp + 1024 * part + 512 * (i8 >> 1) + 256 * i + 32 * (i8 & 1), make_uint4(f[0], f[1], f[2], f[3]));
        }
      }
      if (t == 0) STAMP(15 + 10 * wg);
    }
    asm volatile("bar.arrive %0, 160;" ::"r"(4 + wg) : "memory");
    if (wg == 0) {
      uint2 ds[8], xv[32];
#pragma unroll
      for (int J = 0; J < 8; J++) asm volatile("ld.shared.v2.u32 {%0,%1}, [%2];" : "=r"(ds[J].x), "=r"(ds[J].y) : "r"(sb + OFF_DS + 8 * c + 32 * J));
      {
        const int gp = 2 * (g & 3) + (g >> 2);
        const uint32_t xa = sb + OFF_RING + (XPOS % STAGES) * STAGE_BYTES + (64 * (w & 1) + 8 * (w >> 1) + gp) * 128 + (c & 1) * 8;
        bar_sync(6, 160);
        mbar_wait(bars + (B_FULL + XPOS % STAGES) * 8, (XPOS / STAGES) & 1);
        if (t == 0) STAMP(18);
#pragma unroll
        for (int u = 0; u < 32; u++) {
          const int J = (u >> 1) & 7;
          asm volatile("ld.shared.v2.u32 {%0,%1}, [%2];" : "=r"(xv[u].x), "=r"(xv[u].y) : "r"(xa + (J >> 2) * 16384 + (u >> 4) * 2048 + (u & 1) * 4096 + (((2 * (J & 3) + (c >> 1)) ^ gp) << 4)) : "memory");
        }
        uint32_t dep = P.zero;
#pragma unroll
        for (int u = 0; u < 32; u++) dep &= xv[u].x;
        bar_sync(3 + dep, 128);
        release_stage(bars + (B_EMPTY + XPOS % STAGES) * 8, t);
      }
#pragma unroll
      for (int u = 0; u < 32; u++) {
        float* e = d + 8 * (u >> 1) + 2 * (u & 1);
        const uint32_t a = bmul2(xv[u].x, ds[(u >> 1) & 7].x), bb = bmul2(xv[u].y, ds[(u >> 1) & 7].y);
        e[0] = bf_lo(a); e[1] = bf_hi(a); e[4] = bf_lo(bb); e[5] = bf_hi(bb);
        if (XFENCE) asm volatile("pmevent 0;" : "+f"(e[0]), "+f"(e[1]), "+f"(e[4]), "+f"(e[5]));
      }
      fence_regs<128>(d);
      if (t == 0) STAMP(17);
      so = 8 * (33 % STAGES); ph = (33 / STAGES) & 1;
      const uint64_t da0 = make_desc(sb + OFF_RING + 16384, 512, 1024, 2), db0 = make_desc(sb + OFF_RING, 16, 1024, 1);
      bar_sync(2, 256);
#pragma unroll 1
      for (int kb = 0; kb < 32 - TAILB; kb++) {
        if ((kb & 3) == 0 && t == 0) STAMP(40 + (kb >> 2));
        block(std::true_type(), da0, db0, kb == 0, false, 32 + kb);
        if (kb == 0 && t == 0) STAMP(9);
      }
      if (t == 0) STAMP(47);
      float* op = P.out + (size_t)trow * 2048 + 1024 + dcol;
      auto mma = [&](int i, int kb) {
        const int s = (33 + kb) % STAGES;
        wg_fence();
#pragma unroll
        for (int k = 0; k < 4; k++) wgmma_n128<1>(d + 64 * i, da0 + s * 2048 + 512 * i + 128 * k, db0 + s * 2048 + 2 * k, 1);
        wg_commit();
      };
      auto store = [&](int i, int J0, int J1) {
#pragma unroll
        for (int J = J0; J < J1; J++) {
#pragma unroll
          for (int h = 0; h < 2; h++) {
            const float* e = d + 64 * i + 8 * J + 2 * h;
            stg128(op + (size_t)(16 * i + 32 * h) * 2048 + 16 * J, make_uint4(__float_as_uint(e[0]), __float_as_uint(e[1]), __float_as_uint(e[4]), __float_as_uint(e[5])));
          }
        }
        PMFENCE();
      };
#pragma unroll
      for (int kb = 28; kb < 32; kb++) { mbar_wait(bars + (B_FULL + (33 + kb) % STAGES) * 8, ((33 + kb) / STAGES) & 1); mma(0, kb); }
      mma(1, 28);
      wg_wait<1>();
      fence_regs<64>(d);
      if (t == 0) STAMP(48);
      mma(1, 29);
      store(0, 0, 2);
      mma(1, 30);
      store(0, 2, 4);
      mma(1, 31);
      store(0, 4, 8);
      if (t == 0) STAMP(49);
      wg_wait<0>();
      fence_regs<64>(d + 64);
      if (t == 0) STAMP(50);
      store(1, 0, 8);
      if (t == 0) STAMP(51);
      if (t == 0) g_epoch[b * 32] = epoch;
    }
  }
}

typedef CUresult (*EncodeFn)(CUtensorMap*, CUtensorMapDataType, cuuint32_t, void*, const cuuint64_t*, const cuuint64_t*, const cuuint32_t*,
                             const cuuint32_t*, CUtensorMapInterleave, CUtensorMapSwizzle, CUtensorMapL2promotion, CUtensorMapFloatOOBfill);

bool encode(EncodeFn fn, CUtensorMap* m, int rank, const void* base, const cuuint64_t* dims, const cuuint64_t* strides, const cuuint32_t* box, CUtensorMapSwizzle swz,
            CUtensorMapL2promotion promo = CU_TENSOR_MAP_L2_PROMOTION_L2_128B) {
  const cuuint32_t es[5] = {1, 1, 1, 1, 1};
  return fn(m, CU_TENSOR_MAP_DATA_TYPE_BFLOAT16, rank, const_cast<void*>(base), dims, strides, box, es, CU_TENSOR_MAP_INTERLEAVE_NONE, swz,
            promo, CU_TENSOR_MAP_FLOAT_OOB_FILL_NONE) == CUDA_SUCCESS;
}

}

extern "C" void kernel_launch(void* const* d_in, const int* in_sizes, int n_in, void* d_out, int out_size) {
  (void)in_sizes; (void)n_in; (void)out_size;
  Params P;
  P.q = (const __nv_bfloat16*)d_in[0]; P.k = (const __nv_bfloat16*)d_in[1]; P.v = (const __nv_bfloat16*)d_in[2];
  P.shift_k = (const __nv_bfloat16*)d_in[3]; P.ssm_k = (const __nv_bfloat16*)d_in[4]; P.ssm_D = (const __nv_bfloat16*)d_in[5];
  P.x = (const __nv_bfloat16*)d_in[6]; P.lam_re = (const __nv_bfloat16*)d_in[7]; P.lam_im = (const __nv_bfloat16*)d_in[8];
  P.B_re = (const __nv_bfloat16*)d_in[9]; P.B_im = (const __nv_bfloat16*)d_in[10]; P.C_re = (const __nv_bfloat16*)d_in[11];
  P.C_im = (const __nv_bfloat16*)d_in[12]; P.log_dt = (const __nv_bfloat16*)d_in[13]; P.Dskip = (const __nv_bfloat16*)d_in[14];
  P.out = (float*)d_out;
  P.zero = 0;
  P.swapB = (uintptr_t)P.B_im < (uintptr_t)P.B_re ? 1 : 0;

  EncodeFn fn = nullptr;
  cudaDriverEntryPointQueryResult qr;
  cudaGetDriverEntryPoint("cuTensorMapEncodeTiled", (void**)&fn, cudaEnableDefault, &qr);
  if (!fn) return;

  CUtensorMap mX, mB, mCre, mCim, mXs, mK, mV, mQ, mS;
  bool ok = true;
  {
    const cuuint64_t dims[4] = {1024, 2, 64, 16}, str[3] = {2048, 32 * 2048, 2 * 2048};
    const cuuint32_t box[4] = {64, 2, 4, MC ? 8 : 16};
    ok &= encode(fn, &mX, 4, P.x, dims, str, box, CU_TENSOR_MAP_SWIZZLE_128B, G_PROMO);
  }
  {
    const uintptr_t lo = P.swapB ? (uintptr_t)P.B_im : (uintptr_t)P.B_re, hi = P.swapB ? (uintptr_t)P.B_re : (uintptr_t)P.B_im;
    const cuuint64_t dims[4] = {1024, 8, 2, 128}, str[3] = {2048, (cuuint64_t)(hi - lo), 8 * 2048};
    const cuuint32_t box[4] = {64, 8, 2, 8};
    ok &= encode(fn, &mB, 4, (const void*)lo, dims, str, box, CU_TENSOR_MAP_SWIZZLE_128B, G_PROMO);
  }
  {
    const cuuint64_t dims[5] = {1024, 2, 4, 2, 64}, str[4] = {2048, 4 * 2048, 2 * 2048, 16 * 2048};
    const cuuint32_t box[5] = {64, 2, 4, 2, 8};
    ok &= encode(fn, &mCre, 5, P.C_re, dims, str, box, CU_TENSOR_MAP_SWIZZLE_128B);
    ok &= encode(fn, &mCim, 5, P.C_im, dims, str, box, CU_TENSOR_MAP_SWIZZLE_128B);
  }
  {
    const cuuint64_t dims[4] = {1024, 2, 4, 256}, str[3] = {4 * 2048, 2048, 8 * 2048};
    const cuuint32_t box[4] = {64, 2, 4, 16};
    ok &= encode(fn, &mXs, 4, P.x, dims, str, box, CU_TENSOR_MAP_SWIZZLE_128B);
  }
  {
    const cuuint64_t dims[3] = {1024, 64, 32}, str[2] = {32 * 2048, 2048};
    const cuuint32_t box[3] = {16, 32, 4};
    ok &= encode(fn, &mQ, 3, P.q, dims, str, box, CU_TENSOR_MAP_SWIZZLE_NONE, KV_PROMO);
    ok &= encode(fn, &mK, 3, P.k, dims, str, box, CU_TENSOR_MAP_SWIZZLE_32B, KV_PROMO);
    ok &= encode(fn, &mV, 3, P.v, dims, str, box, CU_TENSOR_MAP_SWIZZLE_32B, KV_PROMO);
  }
  {
    const cuuint64_t dims[2] = {32, 65536}, str[1] = {64};
    const cuuint32_t box[2] = {32, 64};
    ok &= encode(fn, &mS, 2, P.ssm_k, dims, str, box, CU_TENSOR_MAP_SWIZZLE_64B);
  }
  if (!ok) return;
  auto kern = P.swapB ? fused_kernel<1> : fused_kernel<0>;
  cudaFuncSetAttribute(kern, cudaFuncAttributeMaxDynamicSharedMemorySize, SMEM_BYTES);
  kern<<<NCTA, 512, SMEM_BYTES, cudaStreamPerThread>>>(mX, mB, mCre, mCim, mXs, mK, mV, mQ, mS, P);
}
```

```cpp
#include <cuda_runtime.h>
#include <cuda_bf16.h>
#include <cuda.h>
#include <stdint.h>
#include <type_traits>

#define PROFILE 0

namespace {

constexpr int D_DIM = 1024;
constexpr int NCTA = 128;

constexpr int STAGES = 5, STAGE_BYTES = 32768;
constexpr int OFF_RING = 0;
constexpr int OFF_F1 = STAGES * STAGE_BYTES, OFF_F2 = OFF_F1 + 4096, OFF_K = OFF_F2 + 2048, OFF_VP = OFF_K + 8192, OFF_Q = OFF_VP + 4096, OFF_IN = OFF_Q + 8192;
constexpr int OFF_KV = OFF_K;
constexpr int U_CH = 528, U_N8 = 8 * U_CH, OFF_U = OFF_IN + U_N8;
constexpr int OFF_COEF = OFF_U + 8 * U_N8;
constexpr int OFF_DS = OFF_COEF + 2048, OFF_D = OFF_DS + 512;
constexpr int OFF_BAR = OFF_D + 64;
constexpr int OFF_PROF = OFF_BAR + 448;
constexpr int SMEM_BYTES = OFF_PROF + 512;
static_assert(SMEM_BYTES <= 232448 && OFF_K % 1024 == 0 && (OFF_U + 3 * U_N8) % 512 == 0 && (4 * U_N8) % 512 == 0, "smem map");
constexpr int B_FULL = 0, B_XI = 5, B_HR = 6, B_HP = 7, B_KVF = 8, B_KF = 11, B_KE = 13, B_QF = 15, B_IN = 19, B_UF = 27, B_Y = 31, B_CD = 35, B_ACK = 36,
              B_EMPTY = 37, B_PEER = 42, B_COEF = 47, B_KVE = 48, B_QE = 51, B_EPOCH = 54;
__host__ __device__ constexpr int q_slot(int i) { return i < 2 ? OFF_Q + 4096 * i : i < 5 ? OFF_K + 4096 * (i - 2) : i == 5 ? OFF_F1 : OFF_Q + 4096 * (i - 6); }
__host__ __device__ constexpr int q_bar(int i) { return 8 * (i < 2 ? B_QF + i : i < 4 ? B_KF + i - 2 : i < 6 ? B_QF + i - 2 : B_QF + i - 6); }

#define QD 4
#define HEAD 2
#define ST_T0 200
#define ST_DELAY 300
#define XPOS 28
#define K_T0 800
#define KV_T0 1500
#define KV_DT 500
#define KV_DV (KV_DT - 50)
#define O_PACE 170
#define H_PACE 0
#define CARRY_WAIT 600
#define POLL_NS 30
#define GREEDY 0
#define P2_SPLIT 1
#define TAILB 4
#define GREG 176
#define O_WAIT 2
#define COEF_T0 2500
#define O_EVERY 1
#define X_P1 32
#define X_P2 8
#define X_NOXI 0
#define RELPOS 0
#define CFM 0x40f1
constexpr int SPIN_LIMIT = 1 << 14;

struct Params {
  const __nv_bfloat16 *q, *k, *v, *shift_k, *ssm_k, *ssm_D, *x, *lam_re, *lam_im, *B_re, *B_im, *C_re, *C_im, *log_dt, *Dskip;
  float* out;
  int swapB;
  unsigned zero;
  int slot[64];
};

__device__ __align__(1024) uint4 g_h[16 * 32 * 1024];
__device__ __align__(128) uint4 g_carry[16 * 16 * 32];
__device__ unsigned g_flagH[2 * 16 * 32];
__device__ unsigned g_epoch[NCTA * 32];
#define STAMP(i)
#define GSTAMP(i)
#define TSTAMP(k, n)
#define KSTAMP(k, n)

__device__ __forceinline__ uint64_t make_desc(uint32_t addr, uint32_t lbo, uint32_t sbo, uint32_t swz) {
  return (uint64_t)((addr & 0x3FFFF) >> 4) | ((uint64_t)(lbo >> 4) << 16) | ((uint64_t)(sbo >> 4) << 32) | ((uint64_t)swz << 62);
}
__device__ __forceinline__ void wg_fence() { asm volatile("wgmma.fence.sync.aligned;" ::: "memory"); }
__device__ __forceinline__ void wg_commit() { asm volatile("wgmma.commit_group.sync.aligned;" ::: "memory"); }
template <int N> __device__ __forceinline__ void wg_wait() { asm volatile("wgmma.wait_group.sync.aligned %0;" ::"n"(N) : "memory"); }
__device__ __forceinline__ void mbar_init(uint32_t bar, int cnt) { asm volatile("mbarrier.init.shared::cta.b64 [%0], %1;" ::"r"(bar), "r"(cnt) : "memory"); }
__device__ __forceinline__ void mbar_expect(uint32_t bar, uint32_t bytes) { asm volatile("mbarrier.arrive.expect_tx.shared::cta.b64 _, [%0], %1;" ::"r"(bar), "r"(bytes) : "memory"); }
__device__ __forceinline__ void mbar_wait(uint32_t bar, uint32_t parity) {
  uint32_t ok; int n = 0;
  do {
    asm volatile("{\n.reg .pred p;\nmbarrier.try_wait.parity.shared::cta.b64 p, [%1], %2;\nselp.u32 %0, 1, 0, p;\n}\n" : "=r"(ok) : "r"(bar), "r"(parity) : "memory");
    if (++n > SPIN_LIMIT) break;
  } while (!ok);
}
__device__ __forceinline__ void mbar_arrive(uint32_t bar) { asm volatile("mbarrier.arrive.shared::cta.b64 _, [%0];" ::"r"(bar) : "memory"); }
__device__ __forceinline__ void mbar_arrive_cta(uint32_t bar, uint32_t cta) {
  asm volatile("{\n.reg .b32 ra;\nmapa.shared::cluster.u32 ra, %0, %1;\nmbarrier.arrive.shared::cluster.b64 _, [ra];\n}\n" ::"r"(bar), "r"(cta) : "memory");
}
__device__ __forceinline__ void release_stage(uint32_t bar, int t) { if (t == 0) mbar_arrive(bar); }
__device__ __forceinline__ bool elect_one() {
  uint32_t p;
  asm volatile("{\n.reg .pred P;\nelect.sync _|P, 0xffffffff;\nselp.u32 %0, 1, 0, P;\n}\n" : "=r"(p));
  return p != 0;
}
__device__ __forceinline__ void bar_sync(int id, int n) { asm volatile("bar.sync %0, %1;" ::"r"(id), "r"(n) : "memory"); }
#define TMA_LD(dim) "cp.async.bulk.tensor." dim ".shared::cluster.global.mbarrier::complete_tx::bytes"
__device__ __forceinline__ void tma2d(uint32_t dst, const CUtensorMap* m, int c0, int c1, uint32_t bar) {
  asm volatile(TMA_LD("2d") " [%0], [%1, {%3, %4}], [%2];" ::"r"(dst), "l"(m), "r"(bar), "r"(c0), "r"(c1) : "memory");
}
__device__ __forceinline__ void tma3d(uint32_t dst, const CUtensorMap* m, int c0, int c1, int c2, uint32_t bar) {
  asm volatile(TMA_LD("3d") " [%0], [%1, {%3, %4, %5}], [%2];" ::"r"(dst), "l"(m), "r"(bar), "r"(c0), "r"(c1), "r"(c2) : "memory");
}
__device__ __forceinline__ void tma4d(uint32_t dst, const CUtensorMap* m, int c0, int c1, int c2, int c3, uint32_t bar) {
  asm volatile(TMA_LD("4d") " [%0], [%1, {%3, %4, %5, %6}], [%2];" ::"r"(dst), "l"(m), "r"(bar), "r"(c0), "r"(c1), "r"(c2), "r"(c3) : "memory");
}
__device__ __forceinline__ void tma4d_mc(uint32_t dst, const CUtensorMap* m, int c0, int c1, int c2, int c3, uint32_t bar) {
  asm volatile(TMA_LD("4d") ".multicast::cluster [%0], [%1, {%3, %4, %5, %6}], [%2], %7;" ::"r"(dst), "l"(m), "r"(bar), "r"(c0), "r"(c1), "r"(c2), "r"(c3), "h"((uint16_t)3) : "memory");
}
__device__ __forceinline__ void tma5d_mc(uint32_t dst, const CUtensorMap* m, int c0, int c1, int c2, int c3, int c4, uint32_t bar) {
  asm volatile(TMA_LD("5d") ".multicast::cluster [%0], [%1, {%3, %4, %5, %6, %7}], [%2], %8;" ::"r"(dst), "l"(m), "r"(bar), "r"(c0), "r"(c1), "r"(c2), "r"(c3), "r"(c4), "h"((uint16_t)3) : "memory");
}
__device__ __forceinline__ void bulk_load(uint32_t dst, const void* src, uint32_t bytes, uint32_t bar) {
  asm volatile("cp.async.bulk.shared::cluster.global.mbarrier::complete_tx::bytes [%0], [%1], %2, [%3];" ::"r"(dst), "l"(src), "r"(bytes), "r"(bar) : "memory");
}
__device__ __forceinline__ void bulk_send(uint32_t dst, uint32_t src, uint32_t bytes, uint32_t bar, uint32_t cta) {
  asm volatile("{\n.reg .b32 rd, rb;\nmapa.shared::cluster.u32 rd, %0, %3;\nmapa.shared::cluster.u32 rb, %2, %3;\n"
               "cp.async.bulk.shared::cluster.shared::cta.mbarrier::complete_tx::bytes [rd], [%1], %4, [rb];\n}\n"
               ::"r"(dst), "r"(src), "r"(bar), "r"(cta), "r"(bytes) : "memory");
}
__device__ __forceinline__ void fence_proxy_async_smem() { asm volatile("fence.proxy.async.shared::cta;" ::: "memory"); }
__device__ __forceinline__ void fence_proxy_async_global() { asm volatile("fence.proxy.async.global;" ::: "memory"); }
__device__ __forceinline__ void red_release(unsigned* p, unsigned v) { asm volatile("red.release.gpu.global.add.u32 [%0], %1;" ::"l"(p), "r"(v) : "memory"); }
__device__ __forceinline__ uint32_t clk32() { uint32_t c; asm volatile("mov.u32 %0, %%clock;" : "=r"(c)::"memory"); return c; }
__device__ __forceinline__ void wait_until(uint32_t t0, uint32_t dt) { while (clk32() - t0 < dt) __nanosleep(32); }
__device__ __forceinline__ void spin_until(uint32_t t0, uint32_t dt) { while (clk32() - t0 < dt) {} }
__device__ __forceinline__ void prefetch_map(const CUtensorMap* m) { asm volatile("prefetch.tensormap [%0];" ::"l"(m) : "memory"); }
__device__ __forceinline__ void prefetch_line(const void* p) { asm volatile("prefetch.global.L2 [%0];" ::"l"(p) : "memory"); }
__device__ __forceinline__ unsigned ld_acquire(const unsigned* p) { unsigned v; asm volatile("ld.acquire.gpu.global.u32 %0, [%1];" : "=r"(v) : "l"(p) : "memory"); return v; }
__device__ __forceinline__ unsigned ld_relaxed(const unsigned* p) { unsigned v; asm volatile("ld.relaxed.gpu.global.u32 %0, [%1];" : "=r"(v) : "l"(p) : "memory"); return v; }
__device__ __forceinline__ uint32_t lds32(uint32_t a) { uint32_t v; asm volatile("ld.shared.u32 %0, [%1];" : "=r"(v) : "r"(a)); return v; }
__device__ __forceinline__ uint2 lds64(uint32_t a) { uint2 v; asm volatile("ld.shared.v2.u32 {%0,%1}, [%2];" : "=r"(v.x), "=r"(v.y) : "r"(a) : "memory"); return v; }
__device__ __forceinline__ uint4 lds128(uint32_t a) { uint4 v; asm volatile("ld.shared.v4.u32 {%0,%1,%2,%3}, [%4];" : "=r"(v.x), "=r"(v.y), "=r"(v.z), "=r"(v.w) : "r"(a) : "memory"); return v; }
__device__ __forceinline__ void sts32(uint32_t a, uint32_t v) { asm volatile("st.shared.u32 [%0], %1;" ::"r"(a), "r"(v) : "memory"); }
__device__ __forceinline__ void sts128(uint32_t a, uint4 v) { asm volatile("st.shared.v4.u32 [%0], {%1,%2,%3,%4};" ::"r"(a), "r"(v.x), "r"(v.y), "r"(v.z), "r"(v.w) : "memory"); }
__device__ __forceinline__ void ldsm4(uint32_t* r, uint32_t a) { asm volatile("ldmatrix.sync.aligned.m8n8.x4.shared.b16 {%0,%1,%2,%3}, [%4];" : "=r"(r[0]), "=r"(r[1]), "=r"(r[2]), "=r"(r[3]) : "r"(a) : "memory"); }
__device__ __forceinline__ void ldsm4t(uint32_t* r, uint32_t a) { asm volatile("ldmatrix.sync.aligned.m8n8.x4.trans.shared.b16 {%0,%1,%2,%3}, [%4];" : "=r"(r[0]), "=r"(r[1]), "=r"(r[2]), "=r"(r[3]) : "r"(a) : "memory"); }
__device__ __forceinline__ void stsm4t(uint32_t a, uint32_t r0, uint32_t r1, uint32_t r2, uint32_t r3) {
  asm volatile("stmatrix.sync.aligned.m8n8.x4.trans.shared.b16 [%0], {%1,%2,%3,%4};" ::"r"(a), "r"(r0), "r"(r1), "r"(r2), "r"(r3) : "memory");
}
__device__ __forceinline__ uint4 ldg128_nc(const void* p) { uint4 v; asm volatile("ld.global.nc.L1::no_allocate.v4.u32 {%0,%1,%2,%3}, [%4];" : "=r"(v.x), "=r"(v.y), "=r"(v.z), "=r"(v.w) : "l"(p)); return v; }
__device__ __forceinline__ void stg128(void* p, uint4 v) { asm volatile("st.global.L1::no_allocate.v4.u32 [%0], {%1,%2,%3,%4};" ::"l"(p), "r"(v.x), "r"(v.y), "r"(v.z), "r"(v.w) : "memory"); }
__device__ __forceinline__ uint32_t pack_bf16(float lo, float hi) { uint32_t r; asm("cvt.rn.bf16x2.f32 %0, %1, %2;" : "=r"(r) : "f"(hi), "f"(lo)); return r; }
__device__ __forceinline__ uint32_t bmul2(uint32_t a, uint32_t b) { uint32_t r; asm("mul.rn.bf16x2 %0, %1, %2;" : "=r"(r) : "r"(a), "r"(b)); return r; }
__device__ __forceinline__ uint32_t bfma2(uint32_t a, uint32_t b, uint32_t c) { uint32_t r; asm("fma.rn.bf16x2 %0, %1, %2, %3;" : "=r"(r) : "r"(a), "r"(b), "r"(c)); return r; }
__device__ __forceinline__ uint32_t blo2(uint32_t a) { uint32_t r; asm("{\n.reg .b16 l, h;\nmov.b32 {l, h}, %1;\nmov.b32 %0, {l, l};\n}" : "=r"(r) : "r"(a)); return r; }
__device__ __forceinline__ float bf2f(__nv_bfloat16 v) { return __bfloat162float(v); }

#define R8(d, o) "+f"(d[o]), "+f"(d[o + 1]), "+f"(d[o + 2]), "+f"(d[o + 3]), "+f"(d[o + 4]), "+f"(d[o + 5]), "+f"(d[o + 6]), "+f"(d[o + 7])
#define R16(d, o) R8(d, o), R8(d, o + 8)
#define R64(d, o) R16(d, o), R16(d, o + 16), R16(d, o + 32), R16(d, o + 48)
template <int TA> __device__ __forceinline__ void wgmma_n128(float* d, uint64_t da, uint64_t db, int scale_d) {
  asm volatile("{\n.reg .pred p;\nsetp.ne.b32 p, %66, 0;\n"
    "wgmma.mma_async.sync.aligned.m64n128k16.f32.bf16.bf16 {"
    "%0,%1,%2,%3,%4,%5,%6,%7,%8,%9,%10,%11,%12,%13,%14,%15,%16,%17,%18,%19,%20,%21,%22,%23,%24,%25,%26,%27,%28,%29,%30,%31,"
    "%32,%33,%34,%35,%36,%37,%38,%39,%40,%41,%42,%43,%44,%45,%46,%47,%48,%49,%50,%51,%52,%53,%54,%55,%56,%57,%58,%59,%60,%61,%62,%63"
    "}, %64, %65, p, 1, 1, %67, 0;\n}\n"
    : R64(d, 0)
    : "l"(da), "l"(db), "r"(scale_d), "n"(TA));
}
template <int N> __device__ __forceinline__ void fence_regs(float* d) {
#pragma unroll
  for (int i = 0; i < N; i++) asm volatile("" : "+f"(d[i])::"memory");
}
#define PMFENCE() asm volatile("pmevent 0;" ::: "memory")
__device__ __forceinline__ void cmul(float ar, float ai, float br, float bi, float& cr, float& ci) {
  cr = ar * br - ai * bi; ci = ar * bi + ai * br;
}
__device__ __forceinline__ void csq(float& r, float& i) { const float x = fmaf(r, r, -i * i), y = (r + r) * i; r = x; i = y; }

#define W8(d, o) "=f"(d[o]), "=f"(d[o + 1]), "=f"(d[o + 2]), "=f"(d[o + 3]), "=f"(d[o + 4]), "=f"(d[o + 5]), "=f"(d[o + 6]), "=f"(d[o + 7])
#define L16 "{%0,%1,%2,%3,%4,%5,%6,%7,%8,%9,%10,%11,%12,%13,%14,%15}"
#define L32 "{%0,%1,%2,%3,%4,%5,%6,%7,%8,%9,%10,%11,%12,%13,%14,%15,%16,%17,%18,%19,%20,%21,%22,%23,%24,%25,%26,%27,%28,%29,%30,%31}"
template <int ACC, int TB> __device__ __forceinline__ void rs_n32(float* d, const uint32_t* a, uint64_t db) {
  if constexpr (ACC) asm volatile("wgmma.mma_async.sync.aligned.m64n32k16.f32.bf16.bf16 " L16 ", {%16,%17,%18,%19}, %20, 1, 1, 1, %21;" : R16(d, 0) : "r"(a[0]), "r"(a[1]), "r"(a[2]), "r"(a[3]), "l"(db), "n"(TB));
  else asm volatile("wgmma.mma_async.sync.aligned.m64n32k16.f32.bf16.bf16 " L16 ", {%16,%17,%18,%19}, %20, 0, 1, 1, %21;" : W8(d, 0), W8(d, 8) : "r"(a[0]), "r"(a[1]), "r"(a[2]), "r"(a[3]), "l"(db), "n"(TB));
}
template <int ACC, int TB> __device__ __forceinline__ void ss_n64(float* d, uint64_t da, uint64_t db) {
  if constexpr (ACC) asm volatile("wgmma.mma_async.sync.aligned.m64n64k16.f32.bf16.bf16 " L32 ", %32, %33, 1, 1, 1, 0, %34;" : R16(d, 0), R16(d, 16) : "l"(da), "l"(db), "n"(TB));
  else asm volatile("wgmma.mma_async.sync.aligned.m64n64k16.f32.bf16.bf16 " L32 ", %32, %33, 0, 1, 1, 0, %34;" : W8(d, 0), W8(d, 8), W8(d, 16), W8(d, 24) : "l"(da), "l"(db), "n"(TB));
}
template <int ACC> __device__ __forceinline__ void ss_n32_tt(float* d, uint64_t da, uint64_t db) {
  if constexpr (ACC) asm volatile("wgmma.mma_async.sync.aligned.m64n32k16.f32.bf16.bf16 " L16 ", %16, %17, 1, 1, 1, 1, 1;" : R16(d, 0) : "l"(da), "l"(db));
  else asm volatile("wgmma.mma_async.sync.aligned.m64n32k16.f32.bf16.bf16 " L16 ", %16, %17, 0, 1, 1, 1, 1;" : W8(d, 0), W8(d, 8) : "l"(da), "l"(db));
}
__device__ __forceinline__ void stsm4(uint32_t a, uint32_t r0, uint32_t r1, uint32_t r2, uint32_t r3) {
  asm volatile("stmatrix.sync.aligned.m8n8.x4.shared.b16 [%0], {%1,%2,%3,%4};" ::"r"(a), "r"(r0), "r"(r1), "r"(r2), "r"(r3) : "memory");
}
__device__ __forceinline__ uint32_t bneg2(uint32_t a) { uint32_t r; asm("neg.bf16x2 %0, %1;" : "=r"(r) : "r"(a)); return r; }
template <int N> __device__ __forceinline__ void fence_u32(uint32_t* d) {
#pragma unroll
  for (int i = 0; i < N; i++) asm volatile("" : "+r"(d[i])::"memory");
}
__device__ __forceinline__ void pack32(uint32_t* f, const float* z) {
#pragma unroll
  for (int i = 0; i < 16; i++) f[i] = pack_bf16(z[2 * i], z[2 * i + 1]);
}
template <int INV> __device__ __forceinline__ void twiddle(uint32_t* f, const uint32_t* tp, const uint32_t* ts) {
#pragma unroll
  for (int i = 0; i < 8; i++) {
    uint32_t x = f[2 * i + INV], y = f[2 * i + 1 - INV];
    x = bfma2(tp[i & 3], y, x); y = bfma2(ts[i & 3], x, y); x = bfma2(tp[i & 3], y, x);
    f[2 * i + INV] = x; f[2 * i + 1 - INV] = y;
  }
}
#define NEGOP(x) ((x) ^ 0x80008000u)
template <int FIRST> __device__ __forceinline__ void bimac(uint32_t* o, const uint32_t* a, const uint32_t* b, const uint32_t* c) {
#pragma unroll
  for (int J = 0; J < 2; J++) {
    const uint32_t Pr = a[2 * J], Pi = a[2 * J + 1], Qr = a[2 * J + 4], Qi = a[2 * J + 5], pr = b[2 * J], pi = b[2 * J + 1], qr = b[2 * J + 4], qi = b[2 * J + 5];
    uint32_t x0 = FIRST ? bmul2(Pr, pr) : bfma2(Pr, pr, c[2 * J]), x1 = FIRST ? bmul2(Pr, pi) : bfma2(Pr, pi, c[2 * J + 1]);
    uint32_t x2 = FIRST ? bmul2(Pr, qr) : bfma2(Pr, qr, c[2 * J + 4]), x3 = FIRST ? bmul2(Pr, qi) : bfma2(Pr, qi, c[2 * J + 5]);
    x0 = bfma2(NEGOP(Pi), pi, x0); x1 = bfma2(Pi, pr, x1); x2 = bfma2(NEGOP(Pi), qi, x2); x3 = bfma2(Pi, qr, x3);
    x0 = bfma2(NEGOP(Qr), qr, x0); x1 = bfma2(NEGOP(Qr), qi, x1); x2 = bfma2(Qr, pr, x2); x3 = bfma2(Qr, pi, x3);
    x0 = bfma2(Qi, qi, x0); x1 = bfma2(NEGOP(Qi), qr, x1); x2 = bfma2(NEGOP(Qi), pi, x2); x3 = bfma2(Qi, pr, x3);
    o[2 * J] = x0; o[2 * J + 1] = x1; o[2 * J + 4] = x2; o[2 * J + 5] = x3;
  }
}
__device__ __forceinline__ void sincos8k(int n, float& s, float& c) {
  const float x = (float)((n << 19) >> 19) * (6.283185307179586f / 8192.f);
  s = __sinf(x); c = __cosf(x);
}
__device__ __forceinline__ void fft_tables(uint32_t f1a, uint32_t f2a, int w, int lane, uint32_t* tp, uint32_t* ts, float& d0r, float& d0i) {
  const int c = lane & 3, f1 = 8 * w + (lane >> 2);
#pragma unroll 1
  for (int J = 3; J >= 0; J--) {
    const int a = 8 * J + 2 * c;
    float s0, c0, s1, c1;
    sincos8k(64 * (4 * f1 + 1) * a + 31 * (4 * f1 - 63), d0i, d0r); sincos8k(64 * (4 * f1 + 1) * (a + 1) + 31 * (4 * f1 - 63), s1, c1);
    d0r *= 0.125f; d0i *= 0.125f;
    sts32(f1a + w * 1024 + J * 128 + lane * 4, pack_bf16(d0r, 0.125f * c1)); sts32(f1a + w * 1024 + 512 + J * 128 + lane * 4, pack_bf16(d0i, 0.125f * s1));
    sincos8k(128 * (2 * (a & 15) + 1) * f1 - 128 * (a & 16), s0, c0); sincos8k(128 * (2 * (a & 15) + 3) * f1 - 128 * (a & 16), s1, c1);
    sts32(f2a + w * 512 + J * 128 + lane * 4, pack_bf16(c0, c1));
    sincos8k((4 * f1 - 63) * (2 * a - 31), s0, c0); sincos8k((4 * f1 - 63) * (2 * a - 29), s1, c1);
#pragma unroll
    for (int i = 3; i > 0; i--) { ts[i] = ts[i - 1]; tp[i] = tp[i - 1]; }
    ts[0] = pack_bf16(s0, s1); tp[0] = pack_bf16(-__fdividef(s0, 1.f + c0), -__fdividef(s1, 1.f + c1));
  }
  if (c != 0) d0r = d0i = 0.f;
}

template <int SWAPB>
__global__ void __cluster_dims__(2, 1, 1) __launch_bounds__(512, 1)
fused_kernel(const __grid_constant__ CUtensorMap mX, const __grid_constant__ CUtensorMap mB,
             const __grid_constant__ CUtensorMap mCre, const __grid_constant__ CUtensorMap mCim, const __grid_constant__ CUtensorMap mXs,
             const __grid_constant__ CUtensorMap mK, const __grid_constant__ CUtensorMap mV, const __grid_constant__ CUtensorMap mQ, const __grid_constant__ CUtensorMap mS,
             const __grid_constant__ Params P) {
  extern __shared__ __align__(1024) uint8_t smem_raw[];
  const uint32_t sb = (uint32_t)__cvta_generic_to_shared(smem_raw);
  const uint32_t bars = sb + OFF_BAR;
  const int slot = P.slot[blockIdx.x >> 1], rank = blockIdx.x & 1;
  const int j = slot & 7, tc = 2 * (slot >> 3) + rank, b = 2 * slot + rank;
  const int tid = threadIdx.x;
  const int warp = __shfl_sync(0xffffffffu, tid >> 5, 0);
  const int wg = warp >> 2;
  const uint32_t c_start = clk32();
  auto kblock = [&](int n) { return ((n & 14) == 0 || (n & 14) == 2 * j ? n ^ (2 * j) : n) & 31; };
  auto send_y = [&](int r) {
    const uint32_t src = sb + OFF_U + 4 * (rank ^ 1) * U_N8 + r * U_CH, dst = r >= 2 ? sb + OFF_U + 4 * rank * U_N8 + (r - 2) * U_CH : sb + OFF_IN + 96 + r * 2064;
#pragma unroll
    for (int n = 0; n < 4; n++) bulk_send(dst + n * (r >= 2 ? U_N8 : 512), src + n * U_N8, 512, bars + (B_IN + r) * 8, rank ^ 1);
  };
  auto head = [&](int n) {
    const uint32_t fb = bars + (B_FULL + n) * 8, dst = sb + OFF_RING + n * STAGE_BYTES;
    mbar_expect(fb, STAGE_BYTES);
    tma4d(dst + 16384, &mX, 64 * n, 0, 4 * tc, 0, fb);
    tma4d(dst, &mB, 64 * n, 0, 0, 8 * j, fb);
    tma4d(dst + 8192, &mB, 64 * n, 0, 0, 8 * j + 4, fb);
  };
  if (warp == 0 && elect_one()) {
    STAMP(0); GSTAMP(0);
#pragma unroll
    for (int s = 0; s < STAGES; s++) mbar_init(bars + (B_FULL + s) * 8, 1);
    head(0);
    STAMP(1);
    asm volatile("fence.mbarrier_init.release.cluster;" ::: "memory");
  }
  if (wg == 3 && elect_one()) {
    if (warp < 15) {
#pragma unroll
      for (int s = 0; s < 12; s++) mbar_init(bars + 8 * B_XI + (warp & 3) * 96 + 8 * s, 1);
    } else {
#pragma unroll
      for (int s = B_XI + 36; s < B_QE + 2; s++) mbar_init(bars + 8 * s, s < B_COEF ? 1 : s == B_COEF ? 128 : 4);
    }
    asm volatile("fence.mbarrier_init.release.cluster;" ::: "memory");
  }
  __syncwarp();
  asm volatile("barrier.cluster.arrive.relaxed.aligned;" ::: "memory");
  if (warp == 0 && elect_one()) {
#pragma unroll 1
    for (int n = 1; n < HEAD; n++) { spin_until(c_start, ST_T0 + n * ST_DELAY); head(n); }
  }
  __syncwarp();
#define CLUSTER_WAIT() asm volatile("barrier.cluster.wait.aligned;" ::: "memory")

  if (wg == 3) {
    asm volatile("setmaxnreg.dec.sync.aligned.u32 24;");
    CLUSTER_WAIT();
    if (warp < 14) {
      if (elect_one()) {
        uint32_t so = 8 * (HEAD % STAGES), ph = HEAD < STAGES;
        auto step = [&](auto issue) {
          mbar_wait(bars + B_EMPTY * 8 + so, ph);
          issue(sb + OFF_RING + (so << 12), bars + B_FULL * 8 + so);
          so += 8;
          if (so == 8 * STAGES) { so = 0; ph ^= 1; }
        };
        if (warp == 12) {
          uint64_t pp = 0;
          auto shake = [&](uint32_t fb) {
            mbar_arrive_cta(bars + B_PEER * 8 + so, rank ^ 1);
            mbar_expect(fb, STAGE_BYTES);
            mbar_wait(bars + B_PEER * 8 + so, (uint32_t)(pp >> so) & 1);
            pp ^= 1ull << so;
          };
          auto g1 = [&](int n0, int n1, int grp) {
#pragma unroll 1
            for (int n = n0; n < n1; n++) step([&](uint32_t dst, uint32_t fb) { shake(fb); tma4d_mc(dst + rank * 8192, &mB, n * 64, 0, 0, grp + 4 * rank, fb); });
          };
#pragma unroll 1
          for (int n = HEAD; n < STAGES; n++) { spin_until(c_start, ST_T0 + n * ST_DELAY); g1(n, n + 1, 8 * j); }
          g1(STAGES, 16, 8 * j);
          g1(0, XPOS - 16, 8 * j + 64);
          step([&](uint32_t dst, uint32_t fb) { mbar_expect(fb, STAGE_BYTES); tma4d(dst, &mXs, 128 * j, 0, 0, 16 * tc, fb); mbar_arrive(bars + B_XI * 8); });
          g1(XPOS - 16, 16, 8 * j + 64);
#pragma unroll 1
          for (int n = 0; n < 32; n += 2) {
            const int col = kblock(n) * 32;
#pragma unroll
            for (int part = 0; part < 2; part++)
              step([&](uint32_t dst, uint32_t fb) { shake(fb); tma5d_mc(dst + rank * 8192, part ? &mCim : &mCre, col, 0, 0, 0, 8 * j + 4 * rank, fb); });
          }
        } else {
          auto g1 = [&](int n0, int n1, int nb) {
#pragma unroll 1
            for (int n = n0; n < n1; n++) step([&](uint32_t dst, uint32_t fb) { tma4d(dst + 16384, &mX, n * 64, 0, 4 * tc, 0, fb); TSTAMP(1, n + nb); });
          };
          auto g2 = [&](int n0, int n1) {
#pragma unroll 1
            for (int n = n0; n < n1; n++) step([&](uint32_t dst, uint32_t fb) { bulk_load(dst + 16384, g_h + (32 * tc + kblock(n)) * 1024, 16384, fb); TSTAMP(1, n + 32); });
          };
#pragma unroll 1
          for (int n = HEAD; n < STAGES; n++) { spin_until(c_start, ST_T0 + n * ST_DELAY); g1(n, n + 1, 0); }
          g1(STAGES, 16, 0);
          g1(0, XPOS - 16, 16);
          step([&](uint32_t dst, uint32_t fb) { tma4d(dst + 16384, &mXs, 128 * j + 64, 0, 0, 16 * tc, fb); });
          g1(XPOS - 16, 16, 16);
#pragma unroll 1
          for (int v = 0; v < 2; v++) {
            STAMP(4 + v);
            mbar_wait(bars + B_HP * 8, v);
            fence_proxy_async_global();
            STAMP(6 + v);
            g2(16 * v, 16 * v + 2);
            mbar_wait(bars + B_HR * 8, v);
            fence_proxy_async_global();
            g2(16 * v + 2, 16 * v + 16);
          }
        }
      }
    } else if (warp == 15) {
      mbar_wait(bars + B_COEF * 8, 0);
      const unsigned epoch = lds32(bars + B_EPOCH * 8);
#pragma unroll 1
      for (int v = 0; v < 2; v++) {
        unsigned* fp = &g_flagH[(16 * v + tc) * 32];
        bar_sync(4 + v, 160);
        if (elect_one()) {
          red_release(fp, 1);
          mbar_arrive(bars + B_HP * 8);
          STAMP(16 + 10 * v);
          int it = 0;
          while (ld_acquire(fp) != 8 * epoch && ++it < (SPIN_LIMIT << 4)) __nanosleep(POLL_NS);
          STAMP(2 + v);
          mbar_arrive(bars + B_HR * 8);
        }
        __syncwarp();
      }
    } else if (elect_one()) {
      const int ch0 = 16 * slot;
      auto load_k = [&](int s, uint32_t dst) { const uint32_t fb = bars + (B_KF + (s & 1)) * 8; mbar_expect(fb, 4096); tma2d(dst, &mS, 0, 64 * (8 * b + s), fb); };
      auto load_q = [&](int i) { mbar_expect(bars + q_bar(i), 4096); tma3d(sb + q_slot(i), &mQ, ch0, 32 * rank, 4 * i, bars + q_bar(i)); };
      prefetch_map(&mS); prefetch_map(&mK); prefetch_map(&mV);
      wait_until(c_start, K_T0);
      load_k(0, sb + OFF_U + (4 * rank + 3) * U_N8); load_k(1, sb + OFF_U + (4 * rank + 3) * U_N8 - 4096);
      {
        uint32_t so = 16, ph = 1;
#pragma unroll 1
        for (int e = 0; e < 9; e++) {
          const uint32_t fb = bars + B_KVF * 8 + so, dst = sb + OFF_KV + (so << 10);
          wait_until(c_start, KV_T0 + (e ? 2 * e - 1 : 0) * KV_DT);
          mbar_wait(bars + B_KVE * 8 + so, ph);
          const uint32_t c1 = clk32();
          mbar_expect(fb, e ? 8192 : 4096);
          if (e > 0) KSTAMP(1, e - 1);
          tma3d(dst, &mK, ch0, 32 * rank - (e == 0), (4 * e - 4) & 31, fb);
          if (e > 0) { wait_until(c1, KV_DV); tma3d(dst + 4096, &mV, ch0, 32 * rank, 4 * e - 4, fb); }
          so += 8;
          if (so == 24) so = 0;
          if (so == 16) ph ^= 1;
        }
      }
      prefetch_map(&mCre); prefetch_map(&mCim); prefetch_map(&mXs); prefetch_map(&mQ);
      mbar_wait(bars + B_KVE * 8, 0);
      load_k(2, sb + OFF_K); load_k(3, sb + OFF_K + 4096);
      mbar_wait(bars + (B_UF + 3) * 8, 0);
#pragma unroll
      for (int ch = 0; ch < 8; ch++) {
        if (ch > 0) {
          mbar_wait(bars + (B_Y + (ch & 3)) * 8, ch >> 2);
          if (ch > 2) mbar_wait(bars + (B_IN + ch - 3) * 8, 0);
          send_y(ch - 1);
        }
        if (ch < 6) mbar_wait(bars + (B_KE + (ch & 1)) * 8, (ch >> 1) & 1);
        if (ch < 4) load_k(ch + 4, sb + OFF_K + (ch & 1) * 4096);
        if (ch >= 2 && ch < 6) load_q(ch - 2);
      }
      mbar_wait(bars + B_CD * 8, 0);
      load_q(4); load_q(5);
#pragma unroll
      for (int i = 6; i < 8; i++) { mbar_wait(bars + (B_QE + i - 6) * 8, 0); load_q(i); }
    }
  } else if (wg == 2) {
    asm volatile("setmaxnreg.inc.sync.aligned.u32 %0;" ::"n"(488 - 2 * GREG));
    const int t = tid & 127, w = warp & 3, lane = t & 31, g = lane >> 2, c = lane & 3;
    const uint4 s2[2] = {ldg128_nc(P.shift_k + (8 * b + 2 * c) * 4), ldg128_nc(P.shift_k + (8 * (b ^ 1) + 2 * c) * 4)};
    const uint32_t dskip = __bfloat16_as_ushort(P.ssm_D[8 * b + (t & 7)]);
    uint32_t tp[4] = {}, ts[4] = {};
    float d0r, d0i;
    fft_tables(sb + OFF_F1, sb + OFF_F2, w, lane, tp, ts, d0r, d0i);
    if (t == 0) STAMP(19);
    CLUSTER_WAIT();
    if (t < 12) mbar_expect(bars + (B_IN + t) * 8, t < 8 ? 2048 : U_N8);
    if (t < 8) sts32(sb + OFF_D + 4 * t, dskip << 16);
    const uint64_t dF1a = make_desc(sb + OFF_F1, 128, 512, 0), dF1b = make_desc(sb + OFF_F1, 512, 128, 0);
    const uint64_t dF2f = make_desc(sb + OFF_F2, 512, 128, 0), dF2i = make_desc(sb + OFF_F2, 128, 512, 0);
    auto T1k = [&](float* z, uint64_t dk) { wg_fence(); ss_n64<0, 1>(z, dF1a, dk); ss_n64<1, 1>(z, dF1a + 16, dk + 64); wg_commit(); };
    auto T1u = [&](float* z, uint64_t du) { wg_fence(); ss_n64<0, 0>(z, dF1a, du); ss_n64<1, 0>(z, dF1a + 16, du + 16); wg_commit(); };
    auto T2 = [&](float* s, const uint32_t* f) {
      wg_fence();
      rs_n32<0, 1>(s, f, dF2f); rs_n32<0, 1>(s + 16, f + 8, dF2f); rs_n32<1, 1>(s, f + 4, dF2f + 64); rs_n32<1, 1>(s + 16, f + 12, dF2f + 64);
      wg_commit();
    };
    auto product = [&](uint32_t* pr, const uint32_t* kh, const uint32_t* uh) {
      bimac<1>(pr, kh, uh, pr);
#pragma unroll
      for (int i = 0; i < 4; i++) { pr[8 + 2 * i] = pr[2 * i + 1]; pr[9 + 2 * i] = NEGOP(pr[2 * i]); }
      bimac<0>(pr + 8, kh + 8, uh, pr + 8); bimac<0>(pr + 8, kh, uh + 8, pr + 8);
      fence_u32<16>(pr);
    };
    float zk[32] = {};
    uint32_t pr[16];
    {
      uint32_t kh0[16];
      {
        float z0[32], sk[32];
        uint32_t fk[16];
        const uint64_t dk = make_desc(sb + OFF_U + (4 * rank + 3) * U_N8, 2048, 512, 2);
        fence_proxy_async_smem();
        bar_sync(7, 128);
        mbar_wait(bars + B_KF * 8, 0);
        T1k(z0, dk);
        mbar_wait(bars + (B_KF + 1) * 8, 0);
        T1k(zk, dk - 256);
        wg_wait<0>(); fence_regs<32>(z0); fence_regs<32>(zk);
        const float dd = __uint_as_float(lds32(sb + OFF_D));
        z0[0] = fmaf(d0r, dd, z0[0]); z0[2] = fmaf(d0i, dd, z0[2]);
        pack32(fk, z0); twiddle<0>(fk, tp, ts); fence_u32<16>(fk);
        T2(sk, fk);
        wg_wait<0>(); fence_regs<32>(sk); fence_u32<16>(fk);
        pack32(kh0, sk); fence_u32<16>(kh0);
      }
      {
        uint32_t sk[2][4], kx[2][8];
#pragma unroll
        for (int o = 0; o < 2; o++) {
          sk[o][0] = __byte_perm(s2[o].x, s2[o].z, 0x5410); sk[o][1] = __byte_perm(s2[o].x, s2[o].z, 0x7632);
          sk[o][2] = __byte_perm(s2[o].y, s2[o].w, 0x5410); sk[o][3] = __byte_perm(s2[o].y, s2[o].w, 0x7632);
        }
        const uint32_t la = sb + OFF_KV + (lane >> 3) * 1024 + (8 * w + (lane & 7)) * 32 + ((rank ^ ((lane >> 2) & 1)) << 4);
        const uint32_t uo = (lane & 7) * U_CH + w * 128 + (lane >> 3) * 16;
        mbar_wait(bars + (B_KVF + 2) * 8, 0);
        if (t == 0) STAMP(27);
        ldsm4(kx[0], la + 16384); ldsm4(kx[1], (la ^ 16) + 16384);
        if (lane == 0) mbar_arrive(bars + (B_KVE + 2) * 8 + (kx[0][1] & kx[1][1] & P.zero));
        uint32_t so = 0, ph = 0;
#pragma unroll 1
        for (int n = 0; n < 4; n++) {
          const uint32_t own = sb + OFF_U + (4 * rank + n) * U_N8, box = n < 3 ? sb + OFF_U + (4 * (rank ^ 1) + n + 1) * U_N8 : sb + OFF_IN;
#pragma unroll
          for (int e = 0; e < 2; e++) {
            uint32_t vx[2][4];
            mbar_wait(bars + B_KVF * 8 + so, ph);
            if (t == 0) KSTAMP(2, 2 * n + e);
#pragma unroll
            for (int o = 0; o < 2; o++) { ldsm4(kx[o] + 4, (la ^ (16 * o)) + (so << 10)); ldsm4(vx[o], (la ^ (16 * o)) + (so << 10) + 4096); }
            if (lane == 0) mbar_arrive(bars + B_KVE * 8 + so + (kx[0][4] & kx[1][4] & vx[0][0] & vx[1][0] & P.zero));
#pragma unroll
            for (int o = 0; o < 2; o++) {
#pragma unroll
              for (int i = 0; i < 4; i++) vx[o][i] = bmul2(bfma2(kx[o][i + 4], sk[o][0], bfma2(kx[o][i + 3], sk[o][1], bfma2(kx[o][i + 2], sk[o][2], bmul2(kx[o][i + 1], sk[o][3])))), vx[o][i]);
              stsm4t((o ? box : own) + uo + e * 64, vx[o][0], vx[o][1], vx[o][2], vx[o][3]);
              kx[o][1] = kx[o][5]; kx[o][2] = kx[o][6]; kx[o][3] = kx[o][7];
            }
            if (t == 0) KSTAMP(3, 2 * n + e);
            so += 8;
            if (so == 24) so = 0;
            if (so == 16) ph ^= 1;
          }
          fence_proxy_async_smem();
          bar_sync(7, 128);
          if (w == 0 && elect_one()) {
            if (n > 0) mbar_wait(bars + B_UF * 8 + 8 * (n - 1), 0);
            bulk_send(own, box, U_N8, bars + B_UF * 8 + 8 * n, rank ^ 1);
          }
          __syncwarp();
        }
        if (t == 0) STAMP(28);
      }
      float zu[32], su[32];
      uint32_t fu[16], uh[16];
#pragma unroll
      for (int n = 0; n < 4; n++) mbar_wait(bars + (B_UF + n) * 8, 0);
      T1u(zu, make_desc(sb + OFF_U, 128, U_N8, 0));
      wg_wait<0>(); fence_regs<32>(zu);
      pack32(fu, zu); twiddle<0>(fu, tp, ts); fence_u32<16>(fu);
      T2(su, fu);
      wg_wait<0>(); fence_regs<32>(su); fence_u32<16>(fu);
      pack32(uh, su);
      product(pr, kh0, uh);
      if (t == 0) STAMP(54);
    }
    {
#define CF(i) do { if ((CFM >> (i)) & 1) PMFENCE(); } while (0)
#define CP(i)
      const uint32_t vs = w < 2 ? 512 : U_N8;
      uint32_t va = (w < 2 ? sb + OFF_VP : sb + OFF_U) + ((lane >> 4) & 1) * vs + (w & 1) * 256 + (lane & 15) * 16;
      uint32_t ya = sb + OFF_U + (2 * w + ((lane >> 3) & 1)) * U_N8 + (lane >> 4) * 128 + (lane & 7) * 16;
      uint64_t du = make_desc(sb + OFF_U, 128, U_N8, 0), dk = make_desc(sb + OFF_K, 2048, 512, 2);
      const uint64_t dv = make_desc(sb + OFF_VP, 128, 512, 0);
      uint32_t yp[8] = {};
      uint32_t yq = sb + OFF_Q + lane * 16;
      auto store_y = [&]() { stsm4(yq, yp[0], yp[1], yp[2], yp[3]); stsm4(yq + 256, yp[4], yp[5], yp[6], yp[7]); };
      auto step = [&](int ch, auto fwd) {
        constexpr bool FWD = decltype(fwd)::value;
        float zu[32], sk[32], su[32], v[32], y[16];
        uint32_t kh[16], uh[16], fk[16], fu[16], fv[16];
        CP(16);
        wg_fence();
        rs_n32<0, 0>(v, pr, dF2i); rs_n32<0, 0>(v + 16, pr + 8, dF2i); rs_n32<1, 0>(v, pr + 4, dF2i + 16); rs_n32<1, 0>(v + 16, pr + 12, dF2i + 16);
        wg_commit();
        CF(0);
        store_y();
        if (FWD) {
          const float dd = __uint_as_float(lds32(sb + OFF_D + 4 * (ch + 1)));
          zk[0] = fmaf(d0r, dd, zk[0]); zk[2] = fmaf(d0i, dd, zk[2]);
          pack32(fk, zk); twiddle<0>(fk, tp, ts); fence_u32<16>(fk);
          CP(1);
          T2(sk, fk);
          CF(2);
          mbar_wait(bars + (B_KF + (ch & 1)) * 8, ((ch >> 1) & 1) ^ 1);
          wg_wait<1>();
        } else wg_wait<0>();
        fence_regs<32>(v); fence_u32<16>(pr); CP(3);
        pack32(fv, v); fence_u32<16>(fv);
        CF(4);
        if (FWD) T1u(zu, du + U_CH / 16);
        CF(5);
        twiddle<1>(fv, tp, ts);
#pragma unroll
        for (int i = 0; i < 4; i++) stsm4(va + 2 * i * vs, fv[4 * i], fv[4 * i + 1], fv[4 * i + 2], fv[4 * i + 3]);
        if (FWD) {
          CF(6);
          wg_wait<1>(); fence_regs<32>(sk); fence_u32<16>(fk);
          pack32(kh, sk); fence_u32<16>(kh);
          CF(7);
          T1k(zk, dk);
          CF(8);
          wg_wait<1>(); fence_regs<32>(zu);
          pack32(fu, zu); twiddle<0>(fu, tp, ts); fence_u32<16>(fu);
          CP(9);
          T2(su, fu);
          CF(10);
        }
        fence_proxy_async_smem();
        bar_sync(7, 128);
        wg_fence(); CP(11);
        ss_n32_tt<0>(y, dv, dF1b); ss_n32_tt<1>(y, dv + 16, dF1b + 64); ss_n32_tt<1>(y, du, dF1b + 128); ss_n32_tt<1>(y, du + 16, dF1b + 192);
        wg_commit();
        if (t == 0) mbar_arrive(bars + (B_Y + (ch & 3)) * 8);
        CF(12);
        if (FWD) {
          wg_wait<1>(); fence_regs<32>(su); fence_u32<16>(fu); fence_regs<32>(zk); CP(13);
          if (t == 0) mbar_arrive(bars + (B_KE + (ch & 1)) * 8);
          pack32(uh, su);
          product(pr, kh, uh);
          du += U_CH / 16; dk += (ch & 1) ? -256 : 256;
          if (w >= 2) va += U_CH;
        }
        CF(14);
        wg_wait<0>(); fence_regs<16>(y); CP(15);
#pragma unroll
        for (int i = 0; i < 8; i++) yp[i] = pack_bf16(y[2 * i], y[2 * i + 1]);
        fence_u32<8>(yp);
        yq = ya;
        ya += U_CH; CP(17);
        if (t == 0) STAMP(55 + ch);
      };
#pragma unroll 1
      for (int ch = 0; ch < 7; ch++) step(ch, std::true_type());
      step(7, std::false_type());
      store_y();
    }
    {
#pragma unroll
      for (int r = 0; r < 7; r++) mbar_wait(bars + (B_IN + r) * 8, 0);
      fence_proxy_async_smem();
      bar_sync(7, 128);
      if (t == 0) STAMP(29);
      if (w == 0 && elect_one()) { send_y(7); mbar_arrive(bars + B_CD * 8); }
      __syncwarp();
      const int lc = 2 * (lane & 2) + (lane & 1) + ((lane >> 2) & 2);
      const bool own = ((lane >> 2) & 1) == rank, spare = !own && lc < 2;
      const uint32_t ya = (spare ? sb + OFF_IN + 96 + lc * 2064 : sb + OFF_U + (own ? 4 * rank * U_N8 : 4 * (rank ^ 1) * U_N8 - 2 * U_CH) + lc * U_CH) + w * 128 + (lane >> 4) * 16;
      const uint32_t ys = spare ? 512 : U_N8;
      const uint32_t qa = sb + (8 * w + g) * 32 + 8 * c;
      float* op = P.out + (size_t)(1024 * rank + 32 * (8 * w + g)) * 2048 + 16 * slot + 4 * c;
      uint32_t y[2][8];
      uint2 q[2][4];
      auto load = [&](int i) {
        mbar_wait(bars + q_bar(i), i >= 6);
#pragma unroll
        for (int r = 0; r < 4; r++) q[i & 1][r] = lds64(qa + q_slot(i) + r * 1024);
        if (i == 0) mbar_wait(bars + (B_IN + 7) * 8, 0);
        const uint32_t a = ya + (i >> 1) * ys + (i & 1) * 64;
        ldsm4t(y[i & 1], a); ldsm4t(y[i & 1] + 4, a + 32);
      };
      load(0);
      if (t == 0) mbar_arrive_cta(bars + B_ACK * 8, rank ^ 1);
      if (O_WAIT) mbar_wait(bars + (O_WAIT == 1 ? B_HP : B_HR) * 8, 1);
      uint32_t oc = clk32() + w * (O_EVERY * O_PACE / 4);
      if (t == 0) STAMP(30);
#pragma unroll
      for (int i = 0; i < 8; i++) {
        uint32_t* o = y[i & 1];
        if (t == 0) KSTAMP(1, 8 + i);
#pragma unroll
        for (int r = 0; r < 4; r++) { o[2 * r] = bmul2(o[2 * r], q[i & 1][r].x); o[2 * r + 1] = bmul2(o[2 * r + 1], q[i & 1][r].y); }
        if (i < 2 && lane == 0) mbar_arrive(bars + (B_QE + i) * 8 + (o[0] & o[2] & o[4] & o[6] & P.zero));
#pragma unroll
        for (int r = 0; r < 4; r++) {
          if (O_PACE && r % O_EVERY == 0) { while ((int)(clk32() - oc) < 0) {} }
          oc += O_PACE;
          stg128(op + (size_t)(4 * i + r) * 2048, make_uint4(o[2 * r] << 16, o[2 * r] & 0xffff0000u, o[2 * r + 1] << 16, o[2 * r + 1] & 0xffff0000u));
          if (r == 0 && i < 7) load(i + 1);
        }
      }
      if (t == 0) STAMP(31);
      mbar_wait(bars + B_ACK * 8, 0);
    }
  } else {
    asm volatile("setmaxnreg.inc.sync.aligned.u32 %0;" ::"n"(GREG));
    const int t = tid & 127, w = warp & 3, lane = t & 31, g = lane >> 2, c = lane & 3;
    if (wg == 1) {
      wait_until(c_start, COEF_T0);
      const int p = 64 * j + (t & 63) + 8 * (t & 64);
      const float Lr = bf2f(P.lam_re[p]), Li = bf2f(P.lam_im[p]);
      const uint32_t ds = __bfloat16_as_ushort(P.Dskip[128 * j + t]);
      const unsigned epoch = ld_relaxed(&g_epoch[b * 32]) + 1;
      const float dt = bf2f(__float2bfloat16_rn(expf(bf2f(P.log_dt[p]))));
      const float e = expf(dt * Lr);
      float sn, cs;
      sincosf(dt * Li, &sn, &cs);
      const float lr = e * cs, li = e * sn;
      const float nr = lr - 1.0f, ni = li;
      const bool big = fabsf(Lr) >= fabsf(Li);
      const float la = big ? Lr : Li, lb = big ? Li : Lr, r = __fdiv_rn(lb, la), inv = __frcp_rn(fmaf(lb, r, la));
      const float br = (big ? fmaf(ni, r, nr) : fmaf(nr, r, ni)) * inv, bi = (big ? fmaf(-nr, r, ni) : fmaf(ni, r, -nr)) * inv;
      sts128(sb + OFF_COEF + t * 16, make_uint4(__float_as_uint(lr), __float_as_uint(li), pack_bf16(2.f * br, 2.f * br), pack_bf16(-2.f * bi, -2.f * bi)));
      sts32(sb + OFF_DS + 4 * t, ds << 16);
      if (t == 0) sts32(bars + B_EPOCH * 8, epoch);
      if (t == 0) STAMP(52);
    }
    CLUSTER_WAIT();
    if (wg == 1) mbar_arrive(bars + B_COEF * 8);
    float d[128];
    uint32_t so = 0, ph = 0, po = 0;
    auto release = [&](bool first) {
      asm volatile("{\n.reg .pred p;\nsetp.eq.u32 p, %1, 0;\n@p mbarrier.arrive.shared::cta.b64 _, [%0];\n}\n" ::"r"(bars + B_EMPTY * 8 + po), "r"((uint32_t)t | (uint32_t)first) : "memory");
    };
    auto block = [&](auto ta, uint64_t da0, uint64_t db0, bool first, bool zero, int nn) {
      constexpr int TA = decltype(ta)::value, KS = TA ? 128 : 2;
      if (t == 0) TSTAMP(2, nn);
      mbar_wait(bars + B_FULL * 8 + so, ph);
      if (t == 0) TSTAMP(3, nn);
      const uint64_t da = da0 + (so << 8), db = db0 + (so << 8);
      wg_fence();
      wgmma_n128<TA>(d, da, db, !zero);
      wgmma_n128<TA>(d + 64, da + 512, db, !zero);
      wg_commit();
      wg_wait<1>();
      if (RELPOS == 0) release(first);
#pragma unroll
      for (int k = 1; k < 4; k++) {
        if (QD == 2 || (QD == 4 && k == 2)) wg_fence();
        wgmma_n128<TA>(d, da + KS * k, db + 2 * k, 1);
        wgmma_n128<TA>(d + 64, da + 512 + KS * k, db + 2 * k, 1);
        if (QD == 2 || (QD == 4 && k == 1)) wg_commit();
        if (RELPOS == 1 && k == 1) release(first);
        if ((QD == 2 && k < 3) || (QD == 4 && k == 1)) wg_wait<1>();
      }
      if (QD != 2) wg_commit();
      if (RELPOS == 2) release(first);
      po = so;
      so += 8;
      if (so == 8 * STAGES) { so = 0; ph ^= 1; }
    };
    {
      so = wg ? 8 * (16 % STAGES) : 0; ph = wg ? (16 / STAGES) & 1 : 0; po = 0;
      const uint64_t da0 = make_desc(sb + OFF_RING, 16, 1024, 1), db0 = make_desc(sb + OFF_RING + 16384, 16, 1024, 1);
      if (wg == 1) bar_sync(1, 256);
#pragma unroll 1
      for (int kb = 0; kb < 16; kb++) {
        if (16 * wg + kb == XPOS) { so += 8; if (so == 8 * STAGES) { so = 0; ph ^= 1; } }
        block(std::false_type(), da0, db0, kb == 0, kb == 0, 16 * wg + kb);
      }
      asm volatile("bar.arrive %0, 256;" ::"r"(1 + wg) : "memory");
    }
    mbar_wait(bars + B_COEF * 8, 0);
    const unsigned epoch = lds32(bars + B_EPOCH * 8);
    const uint32_t ca = sb + OFF_COEF + (64 * wg + 8 * w + g) * 16;
    const uint32_t tag = epoch & 3;
    uint4* cp = &g_carry[((8 * wg + j) * 16 + tc) * 32 + 8 * w + g];
    constexpr int RE = SWAPB ? 2 : 0, IM = 2 - RE;
    float lr[2], li[2], wr[2], wi[2], vr[2], vi[2], qr[2], qi[2], er[2], ei[2];
    uint32_t c0;
    {
      float pr[2], pi[2];
#pragma unroll
      for (int i = 0; i < 2; i++) {
        const uint4 cf = lds128(ca + 512 * i);
        pr[i] = lr[i] = __uint_as_float(cf.x); pi[i] = li[i] = __uint_as_float(cf.y);
#pragma unroll
        for (int s = 0; s < 5; s++) csq(pr[i], pi[i]);
        qr[i] = pr[i]; qi[i] = pi[i];
        csq(qr[i], qi[i]);
        asm volatile("" : "+f"(pr[i]), "+f"(pi[i]), "+f"(qr[i]), "+f"(qi[i]));
      }
      PMFENCE();
      wg_wait<0>();
      fence_regs<128>(d);
      release_stage(bars + B_EMPTY * 8 + po, t);
      if (t == 0) STAMP(10 + 10 * wg);
      float sr[2], si[2];
#pragma unroll
      for (int i = 0; i < 2; i++) {
        const float* e = d + 64 * i;
        sr[i] = e[RE]; si[i] = e[IM];
#pragma unroll
        for (int s = 1; s < X_P1; s++) {
          const int ia = 4 * (s >> 1) + (s & 1);
          const float nr = fmaf(-li[i], si[i], fmaf(lr[i], sr[i], e[ia + RE])), ni = fmaf(li[i], sr[i], fmaf(lr[i], si[i], e[ia + IM]));
          sr[i] = nr; si[i] = ni;
        }
        if (!(GREEDY & 1)) asm volatile("pmevent 0;" : "+f"(sr[i]), "+f"(si[i])::"memory");
      }
#pragma unroll
      for (int i = 0; i < 2; i++) {
        float ur = __shfl_up_sync(0xffffffffu, sr[i], 1, 4), ui = __shfl_up_sync(0xffffffffu, si[i], 1, 4);
        if (c >= 1) { sr[i] = fmaf(pr[i], ur, fmaf(-pi[i], ui, sr[i])); si[i] = fmaf(pr[i], ui, fmaf(pi[i], ur, si[i])); }
        ur = __shfl_up_sync(0xffffffffu, sr[i], 2, 4); ui = __shfl_up_sync(0xffffffffu, si[i], 2, 4);
        if (c >= 2) { sr[i] = fmaf(qr[i], ur, fmaf(-qi[i], ui, sr[i])); si[i] = fmaf(qr[i], ui, fmaf(qi[i], ur, si[i])); }
      }
      if (c == 3 && tc < 15)
        asm volatile("{\n.reg .b64 a, b;\n.reg .b128 v;\nmov.b64 a, {%1,%2};\nmov.b64 b, {%3,%4};\nmov.b128 v, {a,b};\nst.relaxed.gpu.global.b128 [%0], v;\n}\n"
                     ::"l"(cp), "r"((__float_as_uint(sr[0]) & ~3u) | tag), "r"(__float_as_uint(si[0])), "r"(__float_as_uint(sr[1])), "r"(__float_as_uint(si[1])) : "memory");
      PMFENCE();
      if (t == 0) STAMP(11 + 10 * wg);
      c0 = clk32();
#pragma unroll
      for (int i = 0; i < 2; i++) {
        er[i] = __shfl_up_sync(0xffffffffu, sr[i], 1, 4); ei[i] = __shfl_up_sync(0xffffffffu, si[i], 1, 4);
        if (c == 0) er[i] = ei[i] = 0.f;
        wr[i] = (c & 1) ? pr[i] : 1.f; wi[i] = (c & 1) ? pi[i] : 0.f;
        if (c & 2) { float x, y; cmul(wr[i], wi[i], qr[i], qi[i], x, y); wr[i] = x; wi[i] = y; }
        vr[i] = wr[i]; vi[i] = wi[i];
        csq(vr[i], vi[i]); csq(vr[i], vi[i]);
        csq(qr[i], qi[i]); csq(qr[i], qi[i]); csq(qr[i], qi[i]);
        const int src = 4 * (lane & 7) + (lane >> 3);
        vr[i] = __shfl_sync(0xffffffffu, vr[i], src); vi[i] = __shfl_sync(0xffffffffu, vi[i], src);
        qr[i] = __shfl_sync(0xffffffffu, qr[i], src); qi[i] = __shfl_sync(0xffffffffu, qi[i], src);
        asm volatile("pmevent 0;" : "+f"(wr[i]), "+f"(wi[i]), "+f"(vr[i]), "+f"(vi[i]), "+f"(qr[i]), "+f"(qi[i]), "+f"(er[i]), "+f"(ei[i]));
      }
    }
    float sr[2], si[2];
    uint32_t gp[2], gn[2], gms[2];
    {
      uint4 cv[4];
      const int ct = lane >> 3;
      cp += (lane & 7) - g - 32 * (1 + ct);
      auto load_carry = [&]() {
#pragma unroll
        for (int m = 0; m < 4; m++)
          asm volatile("{\n.reg .pred p;\nsetp.lt.s32 p, %5, %6;\n.reg .b64 a, b;\n.reg .b128 v;\nmov.b64 a, {%0,%1};\nmov.b64 b, {%2,%3};\nmov.b128 v, {a,b};\n"
                       "@p ld.relaxed.gpu.global.b128 v, [%4];\nmov.b128 {a,b}, v;\nmov.b64 {%0,%1}, a;\nmov.b64 {%2,%3}, b;\n}\n"
                       : "+r"(cv[m].x), "+r"(cv[m].y), "+r"(cv[m].z), "+r"(cv[m].w) : "l"(cp - 128 * m), "r"(ct), "r"(tc - 4 * m) : "memory");
      };
#pragma unroll
      for (int m = 0; m < 4; m++) cv[m] = make_uint4(tag, 0, 0, 0);
      wait_until(c0, CARRY_WAIT);
      if (t == 0) STAMP(12 + 10 * wg);
      load_carry();
      int n = 0;
#pragma unroll 1
      while (true) {
        uint32_t bad = 0;
#pragma unroll
        for (int m = 0; m < 4; m++) bad |= cv[m].x ^ tag;
        if (__all_sync(0xffffffffu, (bad & 3) == 0) || ++n > (SPIN_LIMIT << 4)) break;
        load_carry();
      }
      if (t == 0) STAMP(13 + 10 * wg);
#pragma unroll
      for (int i = 0; i < 2; i++) {
        float hr = __uint_as_float((i ? cv[3].z : cv[3].x)), hi = __uint_as_float((i ? cv[3].w : cv[3].y));
#pragma unroll
        for (int m = 2; m >= 0; m--) {
          const float x = __uint_as_float((i ? cv[m].z : cv[m].x)), y = __uint_as_float((i ? cv[m].w : cv[m].y));
          const float nr = fmaf(qr[i], hr, fmaf(-qi[i], hi, x)), ni = fmaf(qr[i], hi, fmaf(qi[i], hr, y));
          hr = nr; hi = ni;
        }
        { float x, y; cmul(hr, hi, vr[i], vi[i], x, y); hr = x; hi = y; }
        const uint4 cf = lds128(ca + 512 * i);
        lr[i] = __uint_as_float(cf.x); li[i] = __uint_as_float(cf.y); gp[i] = cf.z; gn[i] = cf.z ^ 0x80008000u; gms[i] = cf.w;
        hr += __shfl_xor_sync(0xffffffffu, hr, 8); hi += __shfl_xor_sync(0xffffffffu, hi, 8);
        hr = __shfl_sync(0xffffffffu, hr, g) + __shfl_sync(0xffffffffu, hr, g + 16); hi = __shfl_sync(0xffffffffu, hi, g) + __shfl_sync(0xffffffffu, hi, g + 16);
        sr[i] = fmaf(wr[i], hr, fmaf(-wi[i], hi, er[i])); si[i] = fmaf(wr[i], hi, fmaf(wi[i], hr, ei[i]));
      }
    }
    if (t == 0) STAMP(14 + 10 * wg);
    const int trow = 128 * tc + 64 * (w & 1) + 8 * (w >> 1) + g;
    const int dcol = 128 * j + 4 * c;
    {
      const uint32_t hc0 = H_PACE ? clk32() - (3 - w) * (H_PACE / 4) : 0;
      uint4* hp = g_h + (32 * tc + 16 * wg + 2 * j) * 1024 + 64 * w + 4 * g + (c ^ (g >> 1));
#pragma unroll
      for (int u = 0; u < 8; u++) {
        const int i = (GREEDY & 2) ? u & 1 : u >> 2, i8 = (GREEDY & 2) ? u >> 1 : u & 3;
        float* e = d + 64 * i;
        if (!(GREEDY & 2) || i == 0) asm volatile("pmevent 0;" : "+f"(sr[0]), "+f"(si[0]), "+f"(sr[1]), "+f"(si[1])::"memory");
#pragma unroll
        for (int s = 8 * i8; s < 8 * i8 + X_P2; s++) {
          const int ia = 4 * (s >> 1) + (s & 1);
          const float nr = fmaf(-li[i], si[i], fmaf(lr[i], sr[i], e[ia + RE])), ni = fmaf(li[i], sr[i], fmaf(lr[i], si[i], e[ia + IM]));
          sr[i] = nr; si[i] = ni;
          e[ia + RE] = nr; e[ia + IM] = ni;
        }
        if (P2_SPLIT) PMFENCE();
        uint32_t hr[4], hn[4];
#pragma unroll
        for (int m = 0; m < 4; m++) {
          const float* f = e + 16 * i8 + 4 * m;
          const uint32_t x = pack_bf16(f[RE], f[RE + 1]), y = pack_bf16(f[IM], f[IM + 1]);
          hr[m] = bfma2(gp[i], x, bmul2(gms[i], y)); hn[m] = bfma2(gn[i], y, bmul2(gms[i], x));
        }
#pragma unroll
        for (int part = 0; part < 2; part++) {
          if (H_PACE) { while (clk32() - hc0 < (2 * u + part) * H_PACE) __nanosleep(20); }
          const uint32_t* f = part ? hn : hr;
          stg128(hp + 1024 * part + 512 * (i8 >> 1) + 256 * i + 32 * (i8 & 1), make_uint4(f[0], f[1], f[2], f[3]));
        }
      }
      if (t == 0) STAMP(15 + 10 * wg);
    }
    asm volatile("bar.arrive %0, 160;" ::"r"(4 + wg) : "memory");
    if (wg == 0) {
      uint2 xv[32];
      {
        const int gp = 2 * (g & 3) + (g >> 2);
        const uint32_t xa = sb + OFF_RING + (XPOS % STAGES) * STAGE_BYTES + (64 * (w & 1) + 8 * (w >> 1) + gp) * 128 + (c & 1) * 8;
        mbar_wait(bars + B_XI * 8, 0);
        mbar_wait(bars + (B_FULL + XPOS % STAGES) * 8, (XPOS / STAGES) & 1);
        if (t == 0) STAMP(18);
#pragma unroll
        for (int u = 0; u < 32; u++) {
          const int J = (u >> 1) & 7;
          if (X_NOXI) xv[u] = make_uint2(0, 0); else
          asm volatile("ld.shared.v2.u32 {%0,%1}, [%2];" : "=r"(xv[u].x), "=r"(xv[u].y) : "r"(xa + (J >> 2) * 16384 + (u >> 4) * 2048 + (u & 1) * 4096 + (((2 * (J & 3) + (c >> 1)) ^ gp) << 4)) : "memory");
        }
        uint32_t dep = P.zero;
#pragma unroll
        for (int u = 0; u < 32; u++) dep &= xv[u].x;
        bar_sync(3 + dep, 128);
        release_stage(bars + (B_EMPTY + XPOS % STAGES) * 8, t);
      }
#pragma unroll
      for (int J = 0; J < (X_NOXI ? 0 : 8); J++) {
        const uint4 ds = lds128(sb + OFF_DS + 16 * c + 64 * J);
#pragma unroll
        for (int r = 0; r < 4; r++) {
          const int u = 16 * (r >> 1) + 2 * J + (r & 1);
          float* e = d + 8 * (u >> 1) + 2 * (u & 1);
          e[0] = __uint_as_float(bfma2(blo2(xv[u].x), ds.x, 0)); e[1] = __uint_as_float(bfma2(xv[u].x, ds.y, 0));
          e[4] = __uint_as_float(bfma2(blo2(xv[u].y), ds.z, 0)); e[5] = __uint_as_float(bfma2(xv[u].y, ds.w, 0));
        }
      }
      fence_regs<128>(d);
      if (t == 0) STAMP(17);
      so = 8 * (33 % STAGES); ph = (33 / STAGES) & 1;
      const uint64_t da0 = make_desc(sb + OFF_RING + 16384, 512, 1024, 2), db0 = make_desc(sb + OFF_RING, 16, 1024, 1);
      bar_sync(2, 256);
#pragma unroll 1
      for (int kb = 0; kb < 32 - TAILB; kb++) {
        block(std::true_type(), da0, db0, kb == 0, false, 32 + kb);
      }
      float* op = P.out + (size_t)trow * 2048 + 1024 + dcol;
      auto mma = [&](int i, int kb) {
        const int s = (33 + kb) % STAGES;
        wg_fence();
#pragma unroll
        for (int k = 0; k < 4; k++) wgmma_n128<1>(d + 64 * i, da0 + s * 2048 + 512 * i + 128 * k, db0 + s * 2048 + 2 * k, 1);
        wg_commit();
      };
      auto store = [&](int i, int J0, int J1) {
#pragma unroll
        for (int J = J0; J < J1; J++) {
#pragma unroll
          for (int h = 0; h < 2; h++) {
            const float* e = d + 64 * i + 8 * J + 2 * h;
            stg128(op + (size_t)(16 * i + 32 * h) * 2048 + 16 * J, make_uint4(__float_as_uint(e[0]), __float_as_uint(e[1]), __float_as_uint(e[4]), __float_as_uint(e[5])));
          }
        }
        PMFENCE();
      };
#pragma unroll
      for (int kb = 28; kb < 32; kb++) { mbar_wait(bars + (B_FULL + (33 + kb) % STAGES) * 8, ((33 + kb) / STAGES) & 1); mma(0, kb); }
      mma(1, 28);
      wg_wait<1>();
      fence_regs<64>(d);
      if (t == 0) STAMP(48);
      mma(1, 29);
      store(0, 0, 2);
      mma(1, 30);
      store(0, 2, 4);
      mma(1, 31);
      store(0, 4, 8);
      if (t == 0) STAMP(49);
      wg_wait<0>();
      fence_regs<64>(d + 64);
      if (t == 0) STAMP(50);
      store(1, 0, 8);
      if (t == 0) { STAMP(51); GSTAMP(51); }
      if (t == 0) g_epoch[b * 32] = epoch;
    }
  }
}

typedef CUresult (*EncodeFn)(CUtensorMap*, CUtensorMapDataType, cuuint32_t, void*, const cuuint64_t*, const cuuint64_t*, const cuuint32_t*,
                             const cuuint32_t*, CUtensorMapInterleave, CUtensorMapSwizzle, CUtensorMapL2promotion, CUtensorMapFloatOOBfill);

bool encode(EncodeFn fn, CUtensorMap* m, int rank, const void* base, const cuuint64_t* dims, const cuuint64_t* strides, const cuuint32_t* box, CUtensorMapSwizzle swz,
            CUtensorMapL2promotion promo = CU_TENSOR_MAP_L2_PROMOTION_L2_128B) {
  const cuuint32_t es[5] = {1, 1, 1, 1, 1};
  return fn(m, CU_TENSOR_MAP_DATA_TYPE_BFLOAT16, rank, const_cast<void*>(base), dims, strides, box, es, CU_TENSOR_MAP_INTERLEAVE_NONE, swz,
            promo, CU_TENSOR_MAP_FLOAT_OOB_FILL_NONE) == CUDA_SUCCESS;
}

}

extern "C" void kernel_launch(void* const* d_in, const int* in_sizes, int n_in, void* d_out, int out_size) {
  (void)in_sizes; (void)n_in; (void)out_size;
  Params P;
  P.q = (const __nv_bfloat16*)d_in[0]; P.k = (const __nv_bfloat16*)d_in[1]; P.v = (const __nv_bfloat16*)d_in[2];
  P.shift_k = (const __nv_bfloat16*)d_in[3]; P.ssm_k = (const __nv_bfloat16*)d_in[4]; P.ssm_D = (const __nv_bfloat16*)d_in[5];
  P.x = (const __nv_bfloat16*)d_in[6]; P.lam_re = (const __nv_bfloat16*)d_in[7]; P.lam_im = (const __nv_bfloat16*)d_in[8];
  P.B_re = (const __nv_bfloat16*)d_in[9]; P.B_im = (const __nv_bfloat16*)d_in[10]; P.C_re = (const __nv_bfloat16*)d_in[11];
  P.C_im = (const __nv_bfloat16*)d_in[12]; P.log_dt = (const __nv_bfloat16*)d_in[13]; P.Dskip = (const __nv_bfloat16*)d_in[14];
  P.out = (float*)d_out;
  P.zero = 0;
  for (int cl = 0; cl < 64; cl++) P.slot[cl] = cl < 4 ? 4 + cl : cl < 36 ? 8 * ((cl - 4) & 7) + ((cl - 4) >> 3) : 8 * (1 + (cl - 36) % 7) + 4 + (cl - 36) / 7;
  P.swapB = (uintptr_t)P.B_im < (uintptr_t)P.B_re ? 1 : 0;

  EncodeFn fn = nullptr;
  cudaDriverEntryPointQueryResult qr;
  cudaGetDriverEntryPoint("cuTensorMapEncodeTiled", (void**)&fn, cudaEnableDefault, &qr);
  if (!fn) return;

  CUtensorMap mX, mB, mCre, mCim, mXs, mK, mV, mQ, mS;
  bool ok = true;
  {
    const cuuint64_t dims[4] = {1024, 2, 64, 16}, str[3] = {2048, 32 * 2048, 2 * 2048};
    const cuuint32_t box[4] = {64, 2, 4, 16};
    ok &= encode(fn, &mX, 4, P.x, dims, str, box, CU_TENSOR_MAP_SWIZZLE_128B);
  }
  {
    const uintptr_t lo = P.swapB ? (uintptr_t)P.B_im : (uintptr_t)P.B_re, hi = P.swapB ? (uintptr_t)P.B_re : (uintptr_t)P.B_im;
    const cuuint64_t dims[4] = {1024, 8, 2, 128}, str[3] = {2048, (cuuint64_t)(hi - lo), 8 * 2048};
    const cuuint32_t box[4] = {64, 8, 2, 4};
    ok &= encode(fn, &mB, 4, (const void*)lo, dims, str, box, CU_TENSOR_MAP_SWIZZLE_128B);
  }
  {
    const cuuint64_t dims[5] = {1024, 2, 4, 2, 64}, str[4] = {2048, 4 * 2048, 2 * 2048, 16 * 2048};
    const cuuint32_t box[5] = {64, 2, 4, 2, 4};
    ok &= encode(fn, &mCre, 5, P.C_re, dims, str, box, CU_TENSOR_MAP_SWIZZLE_128B);
    ok &= encode(fn, &mCim, 5, P.C_im, dims, str, box, CU_TENSOR_MAP_SWIZZLE_128B);
  }
  {
    const cuuint64_t dims[4] = {1024, 2, 4, 256}, str[3] = {4 * 2048, 2048, 8 * 2048};
    const cuuint32_t box[4] = {64, 2, 4, 16};
    ok &= encode(fn, &mXs, 4, P.x, dims, str, box, CU_TENSOR_MAP_SWIZZLE_128B);
  }
  {
    const cuuint64_t dims[3] = {1024, 64, 32}, str[2] = {32 * 2048, 2048};
    const cuuint32_t box[3] = {16, 32, 4};
    ok &= encode(fn, &mQ, 3, P.q, dims, str, box, CU_TENSOR_MAP_SWIZZLE_NONE);
    ok &= encode(fn, &mK, 3, P.k, dims, str, box, CU_TENSOR_MAP_SWIZZLE_32B);
    ok &= encode(fn, &mV, 3, P.v, dims, str, box, CU_TENSOR_MAP_SWIZZLE_32B);
  }
  {
    const cuuint64_t dims[2] = {32, 65536}, str[1] = {64};
    const cuuint32_t box[2] = {32, 64};
    ok &= encode(fn, &mS, 2, P.ssm_k, dims, str, box, CU_TENSOR_MAP_SWIZZLE_64B);
  }
  if (!ok) return;
  auto kern = P.swapB ? fused_kernel<1> : fused_kernel<0>;
  cudaFuncSetAttribute(kern, cudaFuncAttributeMaxDynamicSharedMemorySize, SMEM_BYTES);
  kern<<<NCTA, 512, SMEM_BYTES, cudaStreamPerThread>>>(mX, mB, mCre, mCim, mXs, mK, mV, mQ, mS, P);
}
```

```cpp
#include <cuda_runtime.h>
#include <cuda_bf16.h>
#include <cuda.h>
#include <stdint.h>
#include <type_traits>

#define PROFILE 0

namespace {

constexpr int D_DIM = 1024;
constexpr int NCTA = 128;

constexpr int STAGES = 5, STAGE_BYTES = 32768;
constexpr int OFF_RING = 0;
constexpr int OFF_F1 = STAGES * STAGE_BYTES, OFF_F2 = OFF_F1 + 4096, OFF_K = OFF_F2 + 2048, OFF_VP = OFF_K + 8192, OFF_Q = OFF_VP + 4096, OFF_IN = OFF_Q + 8192;
constexpr int OFF_KV = OFF_K;
constexpr int U_CH = 528, U_N8 = 8 * U_CH, OFF_U = OFF_IN + U_N8;
constexpr int OFF_COEF = OFF_U + 8 * U_N8;
constexpr int OFF_DS = OFF_COEF + 2048, OFF_D = OFF_DS + 512;
constexpr int OFF_BAR = OFF_D + 64;
constexpr int OFF_PROF = OFF_BAR + 448;
constexpr int SMEM_BYTES = OFF_PROF + 512;
static_assert(SMEM_BYTES <= 232448 && OFF_K % 1024 == 0 && (OFF_U + 3 * U_N8) % 512 == 0 && (4 * U_N8) % 512 == 0, "smem map");
constexpr int B_FULL = 0, B_XI = 5, B_HR = 6, B_HP = 7, B_KVF = 8, B_KF = 11, B_KE = 13, B_QF = 15, B_IN = 19, B_UF = 27, B_Y = 31, B_CD = 35, B_ACK = 36,
              B_EMPTY = 37, B_PEER = 42, B_COEF = 47, B_KVE = 48, B_QE = 51, B_EPOCH = 54;
__host__ __device__ constexpr int q_slot(int i) { return i < 2 ? OFF_Q + 4096 * i : i < 5 ? OFF_K + 4096 * (i - 2) : i == 5 ? OFF_F1 : OFF_Q + 4096 * (i - 6); }
__host__ __device__ constexpr int q_bar(int i) { return 8 * (i < 2 ? B_QF + i : i < 4 ? B_KF + i - 2 : i < 6 ? B_QF + i - 2 : B_QF + i - 6); }

#define QD 4
#define HEAD 3
#define ST_T0 200
#define ST_DELAY 300
#define XPOS 28
#define K_T0 800
#define KV_T0 1500
#define KV_DT 500
#define KV_DV 100
#define O_PACE 170
#define H_PACE 0
#define CARRY_WAIT 600
#define POLL_NS 30
#define GREEDY 0
#define P2_SPLIT 0
#define TAILB 5
#define GREG 176
#define O_WAIT 2
#define COEF_T0 2500
#define O_EVERY 1
#define X_P1 32
#define X_P2 8
#define X_NOXI 0
#define RELPOS 0
#define O_UNR 4
constexpr int O_UNROLL = O_UNR;
#define C_AT 31
#define C_AT2 1
#define T_FENCE 0
#define T_ST 2
#define CFM 0x40f1
constexpr int SPIN_LIMIT = 1 << 14;

struct Params {
  unsigned slot[16];
  unsigned zero;
  const __nv_bfloat16 *shift_k, *ssm_D, *lam_re, *lam_im, *log_dt, *Dskip;
  float* out;
};

__device__ __align__(1024) uint4 g_h[16 * 32 * 1024];
__device__ __align__(128) uint2 g_carry[32 * 16 * 32];
__device__ unsigned g_flagH[2 * 16 * 32];
__device__ unsigned g_epoch[NCTA * 32];
#define STAMP(i)
#define GSTAMP(i)
#define TSTAMP(k, n)
#define KSTAMP(k, n)

__device__ __forceinline__ uint64_t make_desc(uint32_t addr, uint32_t lbo, uint32_t sbo, uint32_t swz) {
  return (uint64_t)((addr & 0x3FFFF) >> 4) | ((uint64_t)(lbo >> 4) << 16) | ((uint64_t)(sbo >> 4) << 32) | ((uint64_t)swz << 62);
}
__device__ __forceinline__ void wg_fence() { asm volatile("wgmma.fence.sync.aligned;" ::: "memory"); }
__device__ __forceinline__ void wg_commit() { asm volatile("wgmma.commit_group.sync.aligned;" ::: "memory"); }
template <int N> __device__ __forceinline__ void wg_wait() { asm volatile("wgmma.wait_group.sync.aligned %0;" ::"n"(N) : "memory"); }
__device__ __forceinline__ void mbar_init(uint32_t bar, int cnt) { asm volatile("mbarrier.init.shared::cta.b64 [%0], %1;" ::"r"(bar), "r"(cnt) : "memory"); }
__device__ __forceinline__ void mbar_expect(uint32_t bar, uint32_t bytes) { asm volatile("mbarrier.arrive.expect_tx.shared::cta.b64 _, [%0], %1;" ::"r"(bar), "r"(bytes) : "memory"); }
__device__ __forceinline__ void mbar_wait(uint32_t bar, uint32_t parity) {
  uint32_t ok; int n = 0;
  do {
    asm volatile("{\n.reg .pred p;\nmbarrier.try_wait.parity.shared::cta.b64 p, [%1], %2;\nselp.u32 %0, 1, 0, p;\n}\n" : "=r"(ok) : "r"(bar), "r"(parity) : "memory");
    if (++n > SPIN_LIMIT) break;
  } while (!ok);
}
__device__ __forceinline__ void mbar_arrive(uint32_t bar) { asm volatile("mbarrier.arrive.shared::cta.b64 _, [%0];" ::"r"(bar) : "memory"); }
__device__ __forceinline__ void mbar_arrive_cta(uint32_t bar, uint32_t cta) {
  asm volatile("{\n.reg .b32 ra;\nmapa.shared::cluster.u32 ra, %0, %1;\nmbarrier.arrive.shared::cluster.b64 _, [ra];\n}\n" ::"r"(bar), "r"(cta) : "memory");
}
__device__ __forceinline__ void release_stage(uint32_t bar, int t) { if (t == 0) mbar_arrive(bar); }
__device__ __forceinline__ bool elect_one() {
  uint32_t p;
  asm volatile("{\n.reg .pred P;\nelect.sync _|P, 0xffffffff;\nselp.u32 %0, 1, 0, P;\n}\n" : "=r"(p));
  return p != 0;
}
__device__ __forceinline__ void bar_sync(int id, int n) { asm volatile("bar.sync %0, %1;" ::"r"(id), "r"(n) : "memory"); }
#define TMA_LD(dim) "cp.async.bulk.tensor." dim ".shared::cluster.global.mbarrier::complete_tx::bytes"
__device__ __forceinline__ void tma2d(uint32_t dst, const CUtensorMap* m, int c0, int c1, uint32_t bar) {
  asm volatile(TMA_LD("2d") " [%0], [%1, {%3, %4}], [%2];" ::"r"(dst), "l"(m), "r"(bar), "r"(c0), "r"(c1) : "memory");
}
__device__ __forceinline__ void tma3d(uint32_t dst, const CUtensorMap* m, int c0, int c1, int c2, uint32_t bar) {
  asm volatile(TMA_LD("3d") " [%0], [%1, {%3, %4, %5}], [%2];" ::"r"(dst), "l"(m), "r"(bar), "r"(c0), "r"(c1), "r"(c2) : "memory");
}
__device__ __forceinline__ void tma4d(uint32_t dst, const CUtensorMap* m, int c0, int c1, int c2, int c3, uint32_t bar) {
  asm volatile(TMA_LD("4d") " [%0], [%1, {%3, %4, %5, %6}], [%2];" ::"r"(dst), "l"(m), "r"(bar), "r"(c0), "r"(c1), "r"(c2), "r"(c3) : "memory");
}
__device__ __forceinline__ void tma4d_mc(uint32_t dst, const CUtensorMap* m, int c0, int c1, int c2, int c3, uint32_t bar) {
  asm volatile(TMA_LD("4d") ".multicast::cluster [%0], [%1, {%3, %4, %5, %6}], [%2], %7;" ::"r"(dst), "l"(m), "r"(bar), "r"(c0), "r"(c1), "r"(c2), "r"(c3), "h"((uint16_t)3) : "memory");
}
__device__ __forceinline__ void tma5d_mc(uint32_t dst, const CUtensorMap* m, int c0, int c1, int c2, int c3, int c4, uint32_t bar) {
  asm volatile(TMA_LD("5d") ".multicast::cluster [%0], [%1, {%3, %4, %5, %6, %7}], [%2], %8;" ::"r"(dst), "l"(m), "r"(bar), "r"(c0), "r"(c1), "r"(c2), "r"(c3), "r"(c4), "h"((uint16_t)3) : "memory");
}
__device__ __forceinline__ void bulk_load(uint32_t dst, const void* src, uint32_t bytes, uint32_t bar) {
  asm volatile("cp.async.bulk.shared::cluster.global.mbarrier::complete_tx::bytes [%0], [%1], %2, [%3];" ::"r"(dst), "l"(src), "r"(bytes), "r"(bar) : "memory");
}
__device__ __forceinline__ void bulk_send(uint32_t dst, uint32_t src, uint32_t bytes, uint32_t bar, uint32_t cta) {
  asm volatile("{\n.reg .b32 rd, rb;\nmapa.shared::cluster.u32 rd, %0, %3;\nmapa.shared::cluster.u32 rb, %2, %3;\n"
               "cp.async.bulk.shared::cluster.shared::cta.mbarrier::complete_tx::bytes [rd], [%1], %4, [rb];\n}\n"
               ::"r"(dst), "r"(src), "r"(bar), "r"(cta), "r"(bytes) : "memory");
}
__device__ __forceinline__ void fence_proxy_async_smem() { asm volatile("fence.proxy.async.shared::cta;" ::: "memory"); }
__device__ __forceinline__ void fence_proxy_async_global() { asm volatile("fence.proxy.async.global;" ::: "memory"); }
__device__ __forceinline__ void red_release(unsigned* p, unsigned v) { asm volatile("red.release.gpu.global.add.u32 [%0], %1;" ::"l"(p), "r"(v) : "memory"); }
__device__ __forceinline__ uint32_t clk32() { uint32_t c; asm volatile("mov.u32 %0, %%clock;" : "=r"(c)::"memory"); return c; }
__device__ __forceinline__ void wait_until(uint32_t t0, uint32_t dt) { while (clk32() - t0 < dt) __nanosleep(32); }
__device__ __forceinline__ void spin_until(uint32_t t0, uint32_t dt) { while (clk32() - t0 < dt) {} }
__device__ __forceinline__ void prefetch_map(const CUtensorMap* m) { asm volatile("prefetch.tensormap [%0];" ::"l"(m) : "memory"); }
__device__ __forceinline__ void prefetch_line(const void* p) { asm volatile("prefetch.global.L2 [%0];" ::"l"(p) : "memory"); }
__device__ __forceinline__ unsigned ld_acquire(const unsigned* p) { unsigned v; asm volatile("ld.acquire.gpu.global.u32 %0, [%1];" : "=r"(v) : "l"(p) : "memory"); return v; }
__device__ __forceinline__ unsigned ld_relaxed(const unsigned* p) { unsigned v; asm volatile("ld.relaxed.gpu.global.u32 %0, [%1];" : "=r"(v) : "l"(p) : "memory"); return v; }
__device__ __forceinline__ uint32_t lds32(uint32_t a) { uint32_t v; asm volatile("ld.shared.u32 %0, [%1];" : "=r"(v) : "r"(a)); return v; }
__device__ __forceinline__ uint2 lds64(uint32_t a) { uint2 v; asm volatile("ld.shared.v2.u32 {%0,%1}, [%2];" : "=r"(v.x), "=r"(v.y) : "r"(a) : "memory"); return v; }
__device__ __forceinline__ uint4 lds128(uint32_t a) { uint4 v; asm volatile("ld.shared.v4.u32 {%0,%1,%2,%3}, [%4];" : "=r"(v.x), "=r"(v.y), "=r"(v.z), "=r"(v.w) : "r"(a) : "memory"); return v; }
__device__ __forceinline__ void sts32(uint32_t a, uint32_t v) { asm volatile("st.shared.u32 [%0], %1;" ::"r"(a), "r"(v) : "memory"); }
__device__ __forceinline__ void sts128(uint32_t a, uint4 v) { asm volatile("st.shared.v4.u32 [%0], {%1,%2,%3,%4};" ::"r"(a), "r"(v.x), "r"(v.y), "r"(v.z), "r"(v.w) : "memory"); }
__device__ __forceinline__ void ldsm4(uint32_t* r, uint32_t a) { asm volatile("ldmatrix.sync.aligned.m8n8.x4.shared.b16 {%0,%1,%2,%3}, [%4];" : "=r"(r[0]), "=r"(r[1]), "=r"(r[2]), "=r"(r[3]) : "r"(a) : "memory"); }
__device__ __forceinline__ void ldsm4t(uint32_t* r, uint32_t a) { asm volatile("ldmatrix.sync.aligned.m8n8.x4.trans.shared.b16 {%0,%1,%2,%3}, [%4];" : "=r"(r[0]), "=r"(r[1]), "=r"(r[2]), "=r"(r[3]) : "r"(a) : "memory"); }
__device__ __forceinline__ void stsm4t(uint32_t a, uint32_t r0, uint32_t r1, uint32_t r2, uint32_t r3) {
  asm volatile("stmatrix.sync.aligned.m8n8.x4.trans.shared.b16 [%0], {%1,%2,%3,%4};" ::"r"(a), "r"(r0), "r"(r1), "r"(r2), "r"(r3) : "memory");
}
__device__ __forceinline__ uint4 ldg128_nc(const void* p) { uint4 v; asm volatile("ld.global.nc.L1::no_allocate.v4.u32 {%0,%1,%2,%3}, [%4];" : "=r"(v.x), "=r"(v.y), "=r"(v.z), "=r"(v.w) : "l"(p)); return v; }
__device__ __forceinline__ void stg128(void* p, uint4 v) { asm volatile("st.global.L1::no_allocate.v4.u32 [%0], {%1,%2,%3,%4};" ::"l"(p), "r"(v.x), "r"(v.y), "r"(v.z), "r"(v.w) : "memory"); }
__device__ __forceinline__ uint32_t pack_bf16(float lo, float hi) { uint32_t r; asm("cvt.rn.bf16x2.f32 %0, %1, %2;" : "=r"(r) : "f"(hi), "f"(lo)); return r; }
__device__ __forceinline__ uint32_t bmul2(uint32_t a, uint32_t b) { uint32_t r; asm("mul.rn.bf16x2 %0, %1, %2;" : "=r"(r) : "r"(a), "r"(b)); return r; }
__device__ __forceinline__ uint32_t bfma2(uint32_t a, uint32_t b, uint32_t c) { uint32_t r; asm("fma.rn.bf16x2 %0, %1, %2, %3;" : "=r"(r) : "r"(a), "r"(b), "r"(c)); return r; }
__device__ __forceinline__ uint32_t blo2(uint32_t a) { uint32_t r; asm("{\n.reg .b16 l, h;\nmov.b32 {l, h}, %1;\nmov.b32 %0, {l, l};\n}" : "=r"(r) : "r"(a)); return r; }
__device__ __forceinline__ float bf2f(__nv_bfloat16 v) { return __bfloat162float(v); }

#define R8(d, o) "+f"(d[o]), "+f"(d[o + 1]), "+f"(d[o + 2]), "+f"(d[o + 3]), "+f"(d[o + 4]), "+f"(d[o + 5]), "+f"(d[o + 6]), "+f"(d[o + 7])
#define R16(d, o) R8(d, o), R8(d, o + 8)
#define R64(d, o) R16(d, o), R16(d, o + 16), R16(d, o + 32), R16(d, o + 48)
template <int TA> __device__ __forceinline__ void wgmma_n128(float* d, uint64_t da, uint64_t db, int scale_d) {
  asm volatile("{\n.reg .pred p;\nsetp.ne.b32 p, %66, 0;\n"
    "wgmma.mma_async.sync.aligned.m64n128k16.f32.bf16.bf16 {"
    "%0,%1,%2,%3,%4,%5,%6,%7,%8,%9,%10,%11,%12,%13,%14,%15,%16,%17,%18,%19,%20,%21,%22,%23,%24,%25,%26,%27,%28,%29,%30,%31,"
    "%32,%33,%34,%35,%36,%37,%38,%39,%40,%41,%42,%43,%44,%45,%46,%47,%48,%49,%50,%51,%52,%53,%54,%55,%56,%57,%58,%59,%60,%61,%62,%63"
    "}, %64, %65, p, 1, 1, %67, 0;\n}\n"
    : R64(d, 0)
    : "l"(da), "l"(db), "r"(scale_d), "n"(TA));
}
template <int N> __device__ __forceinline__ void fence_regs(float* d) {
#pragma unroll
  for (int i = 0; i < N; i++) asm volatile("" : "+f"(d[i])::"memory");
}
#define PMFENCE() asm volatile("pmevent 0;" ::: "memory")
__device__ __forceinline__ void cmul(float ar, float ai, float br, float bi, float& cr, float& ci) {
  cr = ar * br - ai * bi; ci = ar * bi + ai * br;
}
__device__ __forceinline__ void csq(float& r, float& i) { const float x = fmaf(r, r, -i * i), y = (r + r) * i; r = x; i = y; }

#define W8(d, o) "=f"(d[o]), "=f"(d[o + 1]), "=f"(d[o + 2]), "=f"(d[o + 3]), "=f"(d[o + 4]), "=f"(d[o + 5]), "=f"(d[o + 6]), "=f"(d[o + 7])
#define L16 "{%0,%1,%2,%3,%4,%5,%6,%7,%8,%9,%10,%11,%12,%13,%14,%15}"
#define L32 "{%0,%1,%2,%3,%4,%5,%6,%7,%8,%9,%10,%11,%12,%13,%14,%15,%16,%17,%18,%19,%20,%21,%22,%23,%24,%25,%26,%27,%28,%29,%30,%31}"
template <int ACC, int TB> __device__ __forceinline__ void rs_n32(float* d, const uint32_t* a, uint64_t db) {
  if constexpr (ACC) asm volatile("wgmma.mma_async.sync.aligned.m64n32k16.f32.bf16.bf16 " L16 ", {%16,%17,%18,%19}, %20, 1, 1, 1, %21;" : R16(d, 0) : "r"(a[0]), "r"(a[1]), "r"(a[2]), "r"(a[3]), "l"(db), "n"(TB));
  else asm volatile("wgmma.mma_async.sync.aligned.m64n32k16.f32.bf16.bf16 " L16 ", {%16,%17,%18,%19}, %20, 0, 1, 1, %21;" : W8(d, 0), W8(d, 8) : "r"(a[0]), "r"(a[1]), "r"(a[2]), "r"(a[3]), "l"(db), "n"(TB));
}
template <int ACC, int TB> __device__ __forceinline__ void ss_n64(float* d, uint64_t da, uint64_t db) {
  if constexpr (ACC) asm volatile("wgmma.mma_async.sync.aligned.m64n64k16.f32.bf16.bf16 " L32 ", %32, %33, 1, 1, 1, 0, %34;" : R16(d, 0), R16(d, 16) : "l"(da), "l"(db), "n"(TB));
  else asm volatile("wgmma.mma_async.sync.aligned.m64n64k16.f32.bf16.bf16 " L32 ", %32, %33, 0, 1, 1, 0, %34;" : W8(d, 0), W8(d, 8), W8(d, 16), W8(d, 24) : "l"(da), "l"(db), "n"(TB));
}
template <int ACC> __device__ __forceinline__ void ss_n32_tt(float* d, uint64_t da, uint64_t db) {
  if constexpr (ACC) asm volatile("wgmma.mma_async.sync.aligned.m64n32k16.f32.bf16.bf16 " L16 ", %16, %17, 1, 1, 1, 1, 1;" : R16(d, 0) : "l"(da), "l"(db));
  else asm volatile("wgmma.mma_async.sync.aligned.m64n32k16.f32.bf16.bf16 " L16 ", %16, %17, 0, 1, 1, 1, 1;" : W8(d, 0), W8(d, 8) : "l"(da), "l"(db));
}
__device__ __forceinline__ void stsm4(uint32_t a, uint32_t r0, uint32_t r1, uint32_t r2, uint32_t r3) {
  asm volatile("stmatrix.sync.aligned.m8n8.x4.shared.b16 [%0], {%1,%2,%3,%4};" ::"r"(a), "r"(r0), "r"(r1), "r"(r2), "r"(r3) : "memory");
}
__device__ __forceinline__ uint32_t bneg2(uint32_t a) { uint32_t r; asm("neg.bf16x2 %0, %1;" : "=r"(r) : "r"(a)); return r; }
template <int N> __device__ __forceinline__ void fence_u32(uint32_t* d) {
#pragma unroll
  for (int i = 0; i < N; i++) asm volatile("" : "+r"(d[i])::"memory");
}
__device__ __forceinline__ void pack32(uint32_t* f, const float* z) {
#pragma unroll
  for (int i = 0; i < 16; i++) f[i] = pack_bf16(z[2 * i], z[2 * i + 1]);
}
template <int INV> __device__ __forceinline__ void twiddle(uint32_t* f, const uint32_t* tp, const uint32_t* ts) {
#pragma unroll
  for (int i = 0; i < 8; i++) {
    uint32_t x = f[2 * i + INV], y = f[2 * i + 1 - INV];
    x = bfma2(tp[i & 3], y, x); y = bfma2(ts[i & 3], x, y); x = bfma2(tp[i & 3], y, x);
    f[2 * i + INV] = x; f[2 * i + 1 - INV] = y;
  }
}
#define NEGOP(x) ((x) ^ 0x80008000u)
template <int FIRST> __device__ __forceinline__ void bimac(uint32_t* o, const uint32_t* a, const uint32_t* b, const uint32_t* c) {
#pragma unroll
  for (int J = 0; J < 2; J++) {
    const uint32_t Pr = a[2 * J], Pi = a[2 * J + 1], Qr = a[2 * J + 4], Qi = a[2 * J + 5], pr = b[2 * J], pi = b[2 * J + 1], qr = b[2 * J + 4], qi = b[2 * J + 5];
    uint32_t x0 = FIRST ? bmul2(Pr, pr) : bfma2(Pr, pr, c[2 * J]), x1 = FIRST ? bmul2(Pr, pi) : bfma2(Pr, pi, c[2 * J + 1]);
    uint32_t x2 = FIRST ? bmul2(Pr, qr) : bfma2(Pr, qr, c[2 * J + 4]), x3 = FIRST ? bmul2(Pr, qi) : bfma2(Pr, qi, c[2 * J + 5]);
    x0 = bfma2(NEGOP(Pi), pi, x0); x1 = bfma2(Pi, pr, x1); x2 = bfma2(NEGOP(Pi), qi, x2); x3 = bfma2(Pi, qr, x3);
    x0 = bfma2(NEGOP(Qr), qr, x0); x1 = bfma2(NEGOP(Qr), qi, x1); x2 = bfma2(Qr, pr, x2); x3 = bfma2(Qr, pi, x3);
    x0 = bfma2(Qi, qi, x0); x1 = bfma2(NEGOP(Qi), qr, x1); x2 = bfma2(NEGOP(Qi), pi, x2); x3 = bfma2(Qi, pr, x3);
    o[2 * J] = x0; o[2 * J + 1] = x1; o[2 * J + 4] = x2; o[2 * J + 5] = x3;
  }
}
__device__ __forceinline__ void sincos8k(int n, float& s, float& c) {
  const float x = (float)((n << 19) >> 19) * (6.283185307179586f / 8192.f);
  s = __sinf(x); c = __cosf(x);
}
__device__ __forceinline__ void fft_tables(uint32_t f1a, uint32_t f2a, int w, int lane, uint32_t* tp, uint32_t* ts, float& d0r, float& d0i) {
  const int c = lane & 3, f1 = 8 * w + (lane >> 2);
#pragma unroll 1
  for (int J = 3; J >= 0; J--) {
    const int a = 8 * J + 2 * c;
    float s0, c0, s1, c1;
    sincos8k(64 * (4 * f1 + 1) * a + 31 * (4 * f1 - 63), d0i, d0r); sincos8k(64 * (4 * f1 + 1) * (a + 1) + 31 * (4 * f1 - 63), s1, c1);
    d0r *= 0.125f; d0i *= 0.125f;
    sts32(f1a + w * 1024 + J * 128 + lane * 4, pack_bf16(d0r, 0.125f * c1)); sts32(f1a + w * 1024 + 512 + J * 128 + lane * 4, pack_bf16(d0i, 0.125f * s1));
    sincos8k(128 * (2 * (a & 15) + 1) * f1 - 128 * (a & 16), s0, c0); sincos8k(128 * (2 * (a & 15) + 3) * f1 - 128 * (a & 16), s1, c1);
    sts32(f2a + w * 512 + J * 128 + lane * 4, pack_bf16(c0, c1));
    sincos8k((4 * f1 - 63) * (2 * a - 31), s0, c0); sincos8k((4 * f1 - 63) * (2 * a - 29), s1, c1);
#pragma unroll
    for (int i = 3; i > 0; i--) { ts[i] = ts[i - 1]; tp[i] = tp[i - 1]; }
    ts[0] = pack_bf16(s0, s1); tp[0] = pack_bf16(-__fdividef(s0, 1.f + c0), -__fdividef(s1, 1.f + c1));
  }
  if (c != 0) d0r = d0i = 0.f;
}

template <int SWAPB>
__global__ void __cluster_dims__(2, 1, 1) __launch_bounds__(512, 1)
fused_kernel(const __grid_constant__ Params P, const __grid_constant__ CUtensorMap mX, const __grid_constant__ CUtensorMap mB,
             const __grid_constant__ CUtensorMap mCre, const __grid_constant__ CUtensorMap mCim, const __grid_constant__ CUtensorMap mXs,
             const __grid_constant__ CUtensorMap mK, const __grid_constant__ CUtensorMap mV, const __grid_constant__ CUtensorMap mQ, const __grid_constant__ CUtensorMap mS) {
  extern __shared__ __align__(1024) uint8_t smem_raw[];
  const uint32_t sb = (uint32_t)__cvta_generic_to_shared(smem_raw);
  const uint32_t bars = sb + OFF_BAR;
  const int slot = (P.slot[blockIdx.x >> 3] >> (4 * (blockIdx.x & 6))) & 63, rank = blockIdx.x & 1;
  const int j = slot & 7, tc = 2 * (slot >> 3) + rank, b = 2 * slot + rank;
  const int tid = threadIdx.x;
  const int warp = __shfl_sync(0xffffffffu, tid >> 5, 0);
  const int wg = warp >> 2;
  const uint32_t c_start = clk32();
  auto kblock = [&](int n) { return ((n & 14) == 0 || (n & 14) == 2 * j ? n ^ (2 * j) : n) & 31; };
  auto send_y = [&](int r, int n0 = 0, int n1 = 4) {
    const uint32_t src = sb + OFF_U + 4 * (rank ^ 1) * U_N8 + r * U_CH, dst = r >= 2 ? sb + OFF_U + 4 * rank * U_N8 + (r - 2) * U_CH : sb + OFF_IN + 96 + r * 2064;
#pragma unroll 1
    for (int n = n0; n < n1; n++) bulk_send(dst + n * (r >= 2 ? U_N8 : 512), src + n * U_N8, 512, bars + (B_IN + r) * 8, rank ^ 1);
  };
  auto head = [&](int n) {
    const uint32_t fb = bars + (B_FULL + n) * 8, dst = sb + OFF_RING + n * STAGE_BYTES;
    mbar_expect(fb, STAGE_BYTES);
    tma4d(dst + 16384, &mX, 64 * n, 0, 4 * tc, 0, fb);
    tma4d(dst, &mB, 64 * n, 0, 0, 8 * j, fb);
    tma4d(dst + 8192, &mB, 64 * n, 0, 0, 8 * j + 4, fb);
  };
  if (warp == 0 && elect_one()) {
    STAMP(0); GSTAMP(0);
#pragma unroll
    for (int s = 0; s < STAGES; s++) mbar_init(bars + (B_FULL + s) * 8, 1);
    head(0);
    STAMP(1);
    asm volatile("fence.mbarrier_init.release.cluster;" ::: "memory");
  }
  if (wg == 3 && elect_one()) {
    if (warp < 15) {
#pragma unroll
      for (int s = 0; s < 12; s++) mbar_init(bars + 8 * B_XI + (warp & 3) * 96 + 8 * s, 1);
    } else {
#pragma unroll
      for (int s = B_XI + 36; s < B_QE + 2; s++) mbar_init(bars + 8 * s, s < B_COEF ? 1 : s == B_COEF ? 128 : 4);
    }
    asm volatile("fence.mbarrier_init.release.cluster;" ::: "memory");
  }
  __syncwarp();
  asm volatile("barrier.cluster.arrive.relaxed.aligned;" ::: "memory");
  if (warp == 0 && elect_one()) {
#pragma unroll 1
    for (int n = 1; n < HEAD; n++) { spin_until(c_start, ST_T0 + n * ST_DELAY); head(n); }
  }
  __syncwarp();
#define CLUSTER_WAIT() asm volatile("barrier.cluster.wait.aligned;" ::: "memory")

  if (wg == 3) {
    asm volatile("setmaxnreg.dec.sync.aligned.u32 24;");
    CLUSTER_WAIT();
    if (warp < 14) {
      if (elect_one()) {
        uint32_t so = 8 * (HEAD % STAGES), ph = HEAD < STAGES;
        auto step = [&](auto issue) {
          mbar_wait(bars + B_EMPTY * 8 + so, ph);
          issue(sb + OFF_RING + (so << 12), bars + B_FULL * 8 + so);
          so += 8;
          if (so == 8 * STAGES) { so = 0; ph ^= 1; }
        };
        if (warp == 12) {
          uint64_t pp = 0;
          auto shake = [&](uint32_t fb) {
            mbar_arrive_cta(bars + B_PEER * 8 + so, rank ^ 1);
            mbar_expect(fb, STAGE_BYTES);
            mbar_wait(bars + B_PEER * 8 + so, (uint32_t)(pp >> so) & 1);
            pp ^= 1ull << so;
          };
          auto g1 = [&](int n0, int n1, int grp) {
#pragma unroll 1
            for (int n = n0; n < n1; n++) step([&](uint32_t dst, uint32_t fb) { shake(fb); tma4d_mc(dst + rank * 8192, &mB, n * 64, 0, 0, grp + 4 * rank, fb); });
          };
#pragma unroll 1
          for (int n = HEAD; n < STAGES; n++) { spin_until(c_start, ST_T0 + n * ST_DELAY); g1(n, n + 1, 8 * j); }
          g1(STAGES, 16, 8 * j);
          g1(0, XPOS - 16, 8 * j + 64);
          step([&](uint32_t dst, uint32_t fb) { mbar_expect(fb, STAGE_BYTES); tma4d(dst, &mXs, 128 * j, 0, 0, 16 * tc, fb); mbar_arrive(bars + B_XI * 8); });
          g1(XPOS - 16, 16, 8 * j + 64);
#pragma unroll 1
          for (int n = 0; n < 32; n += 2) {
            const int col = kblock(n) * 32;
#pragma unroll
            for (int part = 0; part < 2; part++)
              step([&](uint32_t dst, uint32_t fb) { shake(fb); tma5d_mc(dst + rank * 8192, part ? &mCim : &mCre, col, 0, 0, 0, 8 * j + 4 * rank, fb); });
          }
        } else {
          auto g1 = [&](int n0, int n1, int nb) {
#pragma unroll 1
            for (int n = n0; n < n1; n++) step([&](uint32_t dst, uint32_t fb) { tma4d(dst + 16384, &mX, n * 64, 0, 4 * tc, 0, fb); TSTAMP(1, n + nb); });
          };
          auto g2 = [&](int n0, int n1) {
#pragma unroll 1
            for (int n = n0; n < n1; n++) step([&](uint32_t dst, uint32_t fb) { bulk_load(dst + 16384, g_h + (32 * tc + kblock(n)) * 1024, 16384, fb); TSTAMP(1, n + 32); });
          };
#pragma unroll 1
          for (int n = HEAD; n < STAGES; n++) { spin_until(c_start, ST_T0 + n * ST_DELAY); g1(n, n + 1, 0); }
          g1(STAGES, 16, 0);
          g1(0, XPOS - 16, 16);
          step([&](uint32_t dst, uint32_t fb) { tma4d(dst + 16384, &mXs, 128 * j + 64, 0, 0, 16 * tc, fb); });
          g1(XPOS - 16, 16, 16);
#pragma unroll 1
          for (int v = 0; v < 2; v++) {
            STAMP(4 + v);
            mbar_wait(bars + B_HP * 8, v);
            fence_proxy_async_global();
            STAMP(6 + v);
            g2(16 * v, 16 * v + 2);
            mbar_wait(bars + B_HR * 8, v);
            fence_proxy_async_global();
            g2(16 * v + 2, 16 * v + 16);
          }
        }
      }
    } else if (warp == 15) {
      mbar_wait(bars + B_COEF * 8, 0);
      const unsigned epoch = lds32(bars + B_EPOCH * 8);
#pragma unroll 1
      for (int v = 0; v < 2; v++) {
        unsigned* fp = &g_flagH[(16 * v + tc) * 32];
        bar_sync(4 + v, 160);
        if (elect_one()) {
          red_release(fp, 1);
          mbar_arrive(bars + B_HP * 8);
          STAMP(16 + 10 * v);
          int it = 0;
          while (ld_acquire(fp) != 8 * epoch && ++it < (SPIN_LIMIT << 4)) __nanosleep(POLL_NS);
          STAMP(2 + v);
          mbar_arrive(bars + B_HR * 8);
        }
        __syncwarp();
      }
    } else if (elect_one()) {
      const int ch0 = 16 * slot;
      auto load_k = [&](int s, uint32_t dst) { const uint32_t fb = bars + (B_KF + (s & 1)) * 8; mbar_expect(fb, 4096); tma2d(dst, &mS, 0, 64 * (8 * b + s), fb); };
      auto load_q = [&](int i) { mbar_expect(bars + q_bar(i), 4096); tma3d(sb + q_slot(i), &mQ, ch0, 32 * rank, 4 * i, bars + q_bar(i)); };
      prefetch_map(&mS); prefetch_map(&mK); prefetch_map(&mV);
      wait_until(c_start, K_T0);
      load_k(0, sb + OFF_U + (4 * rank + 3) * U_N8); load_k(1, sb + OFF_U + (4 * rank + 3) * U_N8 - 4096);
      {
        uint32_t so = 16, ph = 1;
#pragma unroll 1
        for (int e = 0; e < 9; e++) {
          const uint32_t fb = bars + B_KVF * 8 + so, dst = sb + OFF_KV + (so << 10);
          wait_until(c_start, KV_T0 + (e ? 2 * e - 1 : 0) * KV_DT);
          mbar_wait(bars + B_KVE * 8 + so, ph);
          const uint32_t c1 = clk32();
          mbar_expect(fb, e ? 8192 : 4096);
          if (e > 0) KSTAMP(1, e - 1);
          tma3d(dst, &mK, ch0, 32 * rank - (e == 0), (4 * e - 4) & 31, fb);
          if (e > 0) { wait_until(c1, KV_DV); tma3d(dst + 4096, &mV, ch0, 32 * rank, 4 * e - 4, fb); }
          so += 8;
          if (so == 24) so = 0;
          if (so == 16) ph ^= 1;
        }
      }
      prefetch_map(&mCre); prefetch_map(&mCim); prefetch_map(&mXs); prefetch_map(&mQ);
      mbar_wait(bars + B_KVE * 8, 0);
      load_k(2, sb + OFF_K); load_k(3, sb + OFF_K + 4096);
      mbar_wait(bars + (B_UF + 3) * 8, 0);
#pragma unroll 1
      for (int ch = 0; ch < 8; ch++) {
        if (ch > 0) {
          mbar_wait(bars + (B_Y + (ch & 3)) * 8, ch >> 2);
          if (ch > 2) mbar_wait(bars + (B_IN + ch - 3) * 8, 0);
          send_y(ch - 1);
        }
        if (ch < 6) {
          mbar_wait(bars + (B_KE + (ch & 1)) * 8, (ch >> 1) & 1);
          if (ch < 4) load_k(ch + 4, sb + OFF_K + (ch & 1) * 4096);
          if (ch >= 2) load_q(ch - 2);
        }
      }
#pragma unroll 1
      for (int i = 4; i < 8; i++) { mbar_wait(bars + (i < 6 ? B_CD : B_QE + i - 6) * 8, 0); load_q(i); }
    }
  } else if (wg == 2) {
    asm volatile("setmaxnreg.inc.sync.aligned.u32 %0;" ::"n"(488 - 2 * GREG));
    const int t = tid & 127, w = warp & 3, lane = t & 31, g = lane >> 2, c = lane & 3;
    const uint4 s2[2] = {ldg128_nc(P.shift_k + (8 * b + 2 * c) * 4), ldg128_nc(P.shift_k + (8 * (b ^ 1) + 2 * c) * 4)};
    const uint32_t dskip = __bfloat16_as_ushort(P.ssm_D[8 * b + (t & 7)]);
    uint32_t tp[4] = {}, ts[4] = {};
    float d0r, d0i;
    fft_tables(sb + OFF_F1, sb + OFF_F2, w, lane, tp, ts, d0r, d0i);
    if (t == 0) STAMP(19);
    CLUSTER_WAIT();
    if (t < 12) mbar_expect(bars + (B_IN + t) * 8, t < 8 ? 2048 : U_N8);
    if (t < 8) sts32(sb + OFF_D + 4 * t, dskip << 16);
    const uint64_t dF1a = make_desc(sb + OFF_F1, 128, 512, 0), dF1b = make_desc(sb + OFF_F1, 512, 128, 0);
    const uint64_t dF2f = make_desc(sb + OFF_F2, 512, 128, 0), dF2i = make_desc(sb + OFF_F2, 128, 512, 0);
    auto T1k = [&](float* z, uint64_t dk) { wg_fence(); ss_n64<0, 1>(z, dF1a, dk); ss_n64<1, 1>(z, dF1a + 16, dk + 64); wg_commit(); };
    auto T1u = [&](float* z, uint64_t du) { wg_fence(); ss_n64<0, 0>(z, dF1a, du); ss_n64<1, 0>(z, dF1a + 16, du + 16); wg_commit(); };
    auto T2 = [&](float* s, const uint32_t* f) {
      wg_fence();
      rs_n32<0, 1>(s, f, dF2f); rs_n32<0, 1>(s + 16, f + 8, dF2f); rs_n32<1, 1>(s, f + 4, dF2f + 64); rs_n32<1, 1>(s + 16, f + 12, dF2f + 64);
      wg_commit();
    };
    auto product = [&](uint32_t* pr, const uint32_t* kh, const uint32_t* uh) {
      bimac<1>(pr, kh, uh, pr);
#pragma unroll
      for (int i = 0; i < 4; i++) { pr[8 + 2 * i] = pr[2 * i + 1]; pr[9 + 2 * i] = NEGOP(pr[2 * i]); }
      bimac<0>(pr + 8, kh + 8, uh, pr + 8); bimac<0>(pr + 8, kh, uh + 8, pr + 8);
      fence_u32<16>(pr);
    };
    float zk[32] = {};
    uint32_t pr[16];
    {
      uint32_t kh0[16];
      {
        float z0[32], sk[32];
        uint32_t fk[16];
        const uint64_t dk = make_desc(sb + OFF_U + (4 * rank + 3) * U_N8, 2048, 512, 2);
        fence_proxy_async_smem();
        bar_sync(7, 128);
        mbar_wait(bars + B_KF * 8, 0);
        T1k(z0, dk);
        mbar_wait(bars + (B_KF + 1) * 8, 0);
        T1k(zk, dk - 256);
        wg_wait<0>(); fence_regs<32>(z0); fence_regs<32>(zk);
        const float dd = __uint_as_float(lds32(sb + OFF_D));
        z0[0] = fmaf(d0r, dd, z0[0]); z0[2] = fmaf(d0i, dd, z0[2]);
        pack32(fk, z0); twiddle<0>(fk, tp, ts); fence_u32<16>(fk);
        T2(sk, fk);
        wg_wait<0>(); fence_regs<32>(sk); fence_u32<16>(fk);
        pack32(kh0, sk); fence_u32<16>(kh0);
      }
      {
        uint32_t sk[2][4], kx[2][8];
#pragma unroll
        for (int o = 0; o < 2; o++) {
          sk[o][0] = __byte_perm(s2[o].x, s2[o].z, 0x5410); sk[o][1] = __byte_perm(s2[o].x, s2[o].z, 0x7632);
          sk[o][2] = __byte_perm(s2[o].y, s2[o].w, 0x5410); sk[o][3] = __byte_perm(s2[o].y, s2[o].w, 0x7632);
        }
        const uint32_t la = sb + OFF_KV + (lane >> 3) * 1024 + (8 * w + (lane & 7)) * 32 + ((rank ^ ((lane >> 2) & 1)) << 4);
        const uint32_t uo = (lane & 7) * U_CH + w * 128 + (lane >> 3) * 16;
        mbar_wait(bars + (B_KVF + 2) * 8, 0);
        if (t == 0) STAMP(27);
        ldsm4(kx[0], la + 16384); ldsm4(kx[1], (la ^ 16) + 16384);
        if (lane == 0) mbar_arrive(bars + (B_KVE + 2) * 8 + (kx[0][1] & kx[1][1] & P.zero));
        uint32_t so = 0, ph = 0;
#pragma unroll 1
        for (int n = 0; n < 4; n++) {
          const uint32_t own = sb + OFF_U + (4 * rank + n) * U_N8, box = n < 3 ? sb + OFF_U + (4 * (rank ^ 1) + n + 1) * U_N8 : sb + OFF_IN;
#pragma unroll
          for (int e = 0; e < 2; e++) {
            uint32_t vx[2][4];
            mbar_wait(bars + B_KVF * 8 + so, ph);
            if (t == 0) KSTAMP(2, 2 * n + e);
#pragma unroll
            for (int o = 0; o < 2; o++) { ldsm4(kx[o] + 4, (la ^ (16 * o)) + (so << 10)); ldsm4(vx[o], (la ^ (16 * o)) + (so << 10) + 4096); }
            if (lane == 0) mbar_arrive(bars + B_KVE * 8 + so + (kx[0][4] & kx[1][4] & vx[0][0] & vx[1][0] & P.zero));
#pragma unroll
            for (int o = 0; o < 2; o++) {
#pragma unroll
              for (int i = 0; i < 4; i++) vx[o][i] = bmul2(bfma2(kx[o][i + 4], sk[o][0], bfma2(kx[o][i + 3], sk[o][1], bfma2(kx[o][i + 2], sk[o][2], bmul2(kx[o][i + 1], sk[o][3])))), vx[o][i]);
              stsm4t((o ? box : own) + uo + e * 64, vx[o][0], vx[o][1], vx[o][2], vx[o][3]);
              kx[o][1] = kx[o][5]; kx[o][2] = kx[o][6]; kx[o][3] = kx[o][7];
            }
            if (t == 0) KSTAMP(3, 2 * n + e);
            so += 8;
            if (so == 24) so = 0;
            if (so == 16) ph ^= 1;
          }
          fence_proxy_async_smem();
          bar_sync(7, 128);
          if (w == 0 && elect_one()) {
            if (n > 0) mbar_wait(bars + B_UF * 8 + 8 * (n - 1), 0);
            bulk_send(own, box, U_N8, bars + B_UF * 8 + 8 * n, rank ^ 1);
          }
          __syncwarp();
        }
        if (t == 0) STAMP(28);
      }
      float zu[32], su[32];
      uint32_t fu[16], uh[16];
#pragma unroll
      for (int n = 0; n < 4; n++) mbar_wait(bars + (B_UF + n) * 8, 0);
      T1u(zu, make_desc(sb + OFF_U, 128, U_N8, 0));
      wg_wait<0>(); fence_regs<32>(zu);
      pack32(fu, zu); twiddle<0>(fu, tp, ts); fence_u32<16>(fu);
      T2(su, fu);
      wg_wait<0>(); fence_regs<32>(su); fence_u32<16>(fu);
      pack32(uh, su);
      product(pr, kh0, uh);
      if (t == 0) STAMP(54);
    }
    {
#define CF(i) do { if ((CFM >> (i)) & 1) PMFENCE(); } while (0)
#define CP(i)
      const uint32_t vs = w < 2 ? 512 : U_N8;
      uint32_t va = (w < 2 ? sb + OFF_VP : sb + OFF_U) + ((lane >> 4) & 1) * vs + (w & 1) * 256 + (lane & 15) * 16;
      uint32_t ya = sb + OFF_U + (2 * w + ((lane >> 3) & 1)) * U_N8 + (lane >> 4) * 128 + (lane & 7) * 16;
      uint64_t du = make_desc(sb + OFF_U, 128, U_N8, 0), dk = make_desc(sb + OFF_K, 2048, 512, 2);
      const uint64_t dv = make_desc(sb + OFF_VP, 128, 512, 0);
      uint32_t yp[8] = {};
      uint32_t yq = sb + OFF_Q + lane * 16;
      auto store_y = [&]() { stsm4(yq, yp[0], yp[1], yp[2], yp[3]); stsm4(yq + 256, yp[4], yp[5], yp[6], yp[7]); };
      auto step = [&](int ch, auto fwd) {
        constexpr bool FWD = decltype(fwd)::value;
        float zu[32], sk[32], su[32], v[32], y[16];
        uint32_t kh[16], uh[16], fk[16], fu[16], fv[16];
        CP(16);
        wg_fence();
        rs_n32<0, 0>(v, pr, dF2i); rs_n32<0, 0>(v + 16, pr + 8, dF2i); rs_n32<1, 0>(v, pr + 4, dF2i + 16); rs_n32<1, 0>(v + 16, pr + 12, dF2i + 16);
        wg_commit();
        CF(0);
        store_y();
        if (FWD) {
          const float dd = __uint_as_float(lds32(sb + OFF_D + 4 * (ch + 1)));
          zk[0] = fmaf(d0r, dd, zk[0]); zk[2] = fmaf(d0i, dd, zk[2]);
          pack32(fk, zk); twiddle<0>(fk, tp, ts); fence_u32<16>(fk);
          CP(1);
          T2(sk, fk);
          CF(2);
          mbar_wait(bars + (B_KF + (ch & 1)) * 8, ((ch >> 1) & 1) ^ 1);
          wg_wait<1>();
        } else {
#pragma unroll 1
          for (int r = 0; r < 6; r++) mbar_wait(bars + (B_IN + r) * 8, 0);
          wg_wait<0>();
        }
        fence_regs<32>(v); fence_u32<16>(pr); CP(3);
        pack32(fv, v); fence_u32<16>(fv);
        CF(4);
        if (FWD) T1u(zu, du + U_CH / 16);
        CF(5);
        twiddle<1>(fv, tp, ts);
#pragma unroll
        for (int i = 0; i < 4; i++) stsm4(va + 2 * i * vs, fv[4 * i], fv[4 * i + 1], fv[4 * i + 2], fv[4 * i + 3]);
        if (FWD) {
          CF(6);
          wg_wait<1>(); fence_regs<32>(sk); fence_u32<16>(fk);
          pack32(kh, sk); fence_u32<16>(kh);
          CF(7);
          T1k(zk, dk);
          CF(8);
          wg_wait<1>(); fence_regs<32>(zu);
          pack32(fu, zu); twiddle<0>(fu, tp, ts); fence_u32<16>(fu);
          CP(9);
          T2(su, fu);
          CF(10);
        }
        fence_proxy_async_smem();
        bar_sync(7, 128);
        wg_fence(); CP(11);
        ss_n32_tt<0>(y, dv, dF1b); ss_n32_tt<1>(y, dv + 16, dF1b + 64); ss_n32_tt<1>(y, du, dF1b + 128); ss_n32_tt<1>(y, du + 16, dF1b + 192);
        wg_commit();
        if (t == 0) mbar_arrive(bars + (B_Y + (ch & 3)) * 8);
        CF(12);
        if (FWD) {
          wg_wait<1>(); fence_regs<32>(su); fence_u32<16>(fu); fence_regs<32>(zk); CP(13);
          if (t == 0) mbar_arrive(bars + (B_KE + (ch & 1)) * 8);
          pack32(uh, su);
          product(pr, kh, uh);
          du += U_CH / 16; dk += (ch & 1) ? -256 : 256;
          if (w >= 2) va += U_CH;
        }
        CF(14);
        wg_wait<0>(); fence_regs<16>(y); CP(15);
#pragma unroll
        for (int i = 0; i < 8; i++) yp[i] = pack_bf16(y[2 * i], y[2 * i + 1]);
        fence_u32<8>(yp);
        yq = ya;
        ya += U_CH; CP(17);
        if (t == 0) STAMP(55 + ch);
      };
#pragma unroll 1
      for (int ch = 0; ch < 7; ch++) step(ch, std::true_type());
      step(7, std::false_type());
      store_y();
    }
    {
      fence_proxy_async_smem();
      bar_sync(7, 128);
      if (t == 0) STAMP(29);
      if (elect_one()) { send_y(7, w, w + 1); if (w == 3) mbar_arrive(bars + B_CD * 8); }
      __syncwarp();
      const int lc = 2 * (lane & 2) + (lane & 1) + ((lane >> 2) & 2);
      const bool own = ((lane >> 2) & 1) == rank, spare = !own && lc < 2;
      const uint32_t ya = (spare ? sb + OFF_IN + 96 + lc * 2064 : sb + OFF_U + (own ? 4 * rank * U_N8 : 4 * (rank ^ 1) * U_N8 - 2 * U_CH) + lc * U_CH) + w * 128 + (lane >> 4) * 16;
      const uint32_t ys = spare ? 512 : U_N8;
      const uint32_t qa = sb + (8 * w + g) * 32 + 8 * c;
      float* op = P.out + (size_t)(1024 * rank + 32 * (8 * w + g)) * 2048 + 16 * slot + 4 * c;
      uint32_t y[2][8];
      uint2 q[2][4];
      auto load = [&](int i, int h, bool first) {
        mbar_wait(bars + q_bar(i), i >= 6);
        const uint32_t qs = qa + q_slot(i), a = ya + (i >> 1) * ys + h * 64;
#pragma unroll
        for (int r = 0; r < 4; r++) q[h][r] = lds64(qs + r * 1024);
        if (first) { mbar_wait(bars + (B_IN + 6) * 8, 0); mbar_wait(bars + (B_IN + 7) * 8, 0); }
        ldsm4t(y[h], a); ldsm4t(y[h] + 4, a + 32);
      };
      load(0, 0, true);
      if (t == 0) mbar_arrive_cta(bars + B_ACK * 8, rank ^ 1);
      if (O_WAIT) mbar_wait(bars + (O_WAIT == 1 ? B_HP : B_HR) * 8, 1);
      uint32_t oc = clk32() + w * (O_EVERY * O_PACE / 4);
      if (t == 0) STAMP(30);
#pragma unroll O_UNROLL
      for (int n = 0; n < 4; n++) {
#pragma unroll
        for (int h = 0; h < 2; h++) {
          const int i = 2 * n + h;
          uint32_t* o = y[h];
#pragma unroll
          for (int r = 0; r < 4; r++) { o[2 * r] = bmul2(o[2 * r], q[h][r].x); o[2 * r + 1] = bmul2(o[2 * r + 1], q[h][r].y); }
          if (n == 0 && lane == 0) mbar_arrive(bars + (B_QE + h) * 8 + (o[0] & o[2] & o[4] & o[6] & P.zero));
#pragma unroll
          for (int r = 0; r < 4; r++) {
            if (O_PACE && r % O_EVERY == 0) { while ((int)(clk32() - oc) < 0) {} }
            oc += O_PACE;
            stg128(op + (size_t)(4 * h + r) * 2048, make_uint4(o[2 * r] << 16, o[2 * r] & 0xffff0000u, o[2 * r + 1] << 16, o[2 * r + 1] & 0xffff0000u));
            if (r == 0) load(i < 7 ? i + 1 : 7, h ^ 1, false);
          }
        }
        op += 8 * 2048;
      }
      if (t == 0) STAMP(31);
      mbar_wait(bars + B_ACK * 8, 0);
    }
  } else {
    asm volatile("setmaxnreg.inc.sync.aligned.u32 %0;" ::"n"(GREG));
    const int t = tid & 127, w = warp & 3, lane = t & 31, g = lane >> 2, c = lane & 3;
    if (wg == 1) {
      wait_until(c_start, COEF_T0);
      const int p = 64 * j + (t & 63) + 8 * (t & 64);
      const float Lr = bf2f(P.lam_re[p]), Li = bf2f(P.lam_im[p]);
      const uint32_t ds = __bfloat16_as_ushort(P.Dskip[128 * j + t]);
      const unsigned epoch = ld_relaxed(&g_epoch[b * 32]) + 1;
      const float dt = bf2f(__float2bfloat16_rn(expf(bf2f(P.log_dt[p]))));
      const float e = expf(dt * Lr);
      float sn, cs;
      {
        const double z = (double)(dt * Li) * 0.15915494309189535;
        sincospif(2.f * (float)(z - rint(z)), &sn, &cs);
      }
      const float lr = e * cs, li = e * sn;
      const float nr = lr - 1.0f, ni = li;
      const bool big = fabsf(Lr) >= fabsf(Li);
      const float la = big ? Lr : Li, lb = big ? Li : Lr, r = __fdiv_rn(lb, la), inv = __frcp_rn(fmaf(lb, r, la));
      const float br = (big ? fmaf(ni, r, nr) : fmaf(nr, r, ni)) * inv, bi = (big ? fmaf(-nr, r, ni) : fmaf(ni, r, -nr)) * inv;
      sts128(sb + OFF_COEF + t * 16, make_uint4(__float_as_uint(lr), __float_as_uint(li), pack_bf16(2.f * br, 2.f * br), pack_bf16(-2.f * bi, -2.f * bi)));
      sts32(sb + OFF_DS + 4 * t, ds << 16);
      if (t == 0) sts32(bars + B_EPOCH * 8, epoch);
      if (t == 0) STAMP(52);
    }
    CLUSTER_WAIT();
    if (wg == 1) mbar_arrive(bars + B_COEF * 8);
    float d[128];
    uint32_t so = 0, ph = 0, po = 0;
    auto release = [&](bool first) {
      asm volatile("{\n.reg .pred p;\nsetp.eq.u32 p, %1, 0;\n@p mbarrier.arrive.shared::cta.b64 _, [%0];\n}\n" ::"r"(bars + B_EMPTY * 8 + po), "r"((uint32_t)t | (uint32_t)first) : "memory");
    };
    auto block = [&](auto ta, uint64_t da0, uint64_t db0, bool first, bool zero, int nn) {
      constexpr int TA = decltype(ta)::value, KS = TA ? 128 : 2;
      if (t == 0) TSTAMP(2, nn);
      mbar_wait(bars + B_FULL * 8 + so, ph);
      if (t == 0) TSTAMP(3, nn);
      const uint64_t da = da0 + (so << 8), db = db0 + (so << 8);
      wg_fence();
      wgmma_n128<TA>(d, da, db, !zero);
      wgmma_n128<TA>(d + 64, da + 512, db, !zero);
      wg_commit();
      wg_wait<1>();
      if (RELPOS == 0) release(first);
#pragma unroll
      for (int k = 1; k < 4; k++) {
        if (QD == 2 || (QD == 4 && k == 2)) wg_fence();
        wgmma_n128<TA>(d, da + KS * k, db + 2 * k, 1);
        wgmma_n128<TA>(d + 64, da + 512 + KS * k, db + 2 * k, 1);
        if (QD == 2 || (QD == 4 && k == 1)) wg_commit();
        if (RELPOS == 1 && k == 1) release(first);
        if ((QD == 2 && k < 3) || (QD == 4 && k == 1)) wg_wait<1>();
      }
      if (QD != 2) wg_commit();
      if (RELPOS == 2) release(first);
      po = so;
      so += 8;
      if (so == 8 * STAGES) { so = 0; ph ^= 1; }
    };
    {
      so = wg ? 8 * (16 % STAGES) : 0; ph = wg ? (16 / STAGES) & 1 : 0; po = 0;
      const uint64_t da0 = make_desc(sb + OFF_RING, 16, 1024, 1), db0 = make_desc(sb + OFF_RING + 16384, 16, 1024, 1);
      if (wg == 1) bar_sync(1, 256);
#pragma unroll 1
      for (int kb = 0; kb < 16; kb++) {
        if (16 * wg + kb == XPOS) { so += 8; if (so == 8 * STAGES) { so = 0; ph ^= 1; } }
        block(std::false_type(), da0, db0, kb == 0, kb == 0, 16 * wg + kb);
      }
      asm volatile("bar.arrive %0, 256;" ::"r"(1 + wg) : "memory");
    }
    mbar_wait(bars + B_COEF * 8, 0);
    const unsigned epoch = lds32(bars + B_EPOCH * 8);
    const uint32_t ca = sb + OFF_COEF + (64 * wg + 8 * w + g) * 16;
    const uint32_t tag = epoch & 3;
    constexpr int RE = SWAPB ? 2 : 0, IM = 2 - RE;
    uint2* cp = &g_carry[((16 * wg + 2 * j) * 16 + tc) * 32 + 8 * w];
    const int ct = lane >> 3;
    uint2 cv[4];
    auto load_carry = [&](int i) {
#pragma unroll
      for (int m = 0; m < 4; m++)
        asm volatile("{\n.reg .pred p;\n.reg .b64 v;\nsetp.lt.s32 p, %3, %4;\nmov.b64 v, {%0,%1};\n@p ld.relaxed.gpu.global.b64 v, [%2];\nmov.b64 {%0,%1}, v;\n}\n"
                     : "+r"(cv[m].x), "+r"(cv[m].y) : "l"(cp + 512 * i + (lane & 7) - 32 * (1 + ct) - 128 * m), "r"(ct), "r"(tc - 4 * m) : "memory");
    };
    auto first_load = [&](int i) {
#pragma unroll
      for (int m = 0; m < 4; m++) cv[m] = make_uint2(tag, 0);
      load_carry(i);
    };
    float wr[2], wi[2], vr[2], vi[2], qr[2], qi[2], er[2], ei[2];
#pragma unroll
    for (int i = 0; i < 2; i++) {
      const float* e = d + 64 * i;
      const uint2 cf = lds64(ca + 512 * i);
      const float lr = __uint_as_float(cf.x), li = __uint_as_float(cf.y);
      float pr = lr, pi = li;
#pragma unroll
      for (int s = 0; s < 5; s++) csq(pr, pi);
      qr[i] = pr; qi[i] = pi;
      csq(qr[i], qi[i]);
      asm volatile("pmevent 0;" : "+f"(pr), "+f"(pi), "+f"(qr[i]), "+f"(qi[i])::"memory");
      if (i == 0) {
        wg_wait<0>();
        fence_regs<128>(d);
        release_stage(bars + B_EMPTY * 8 + po, t);
        if (t == 0) STAMP(10 + 10 * wg);
      }
      float sr = e[RE], si = e[IM];
#pragma unroll
      for (int s = 1; s < X_P1; s++) {
        const int ia = 4 * (s >> 1) + (s & 1);
        const float nr = fmaf(-li, si, fmaf(lr, sr, e[ia + RE])), ni = fmaf(li, sr, fmaf(lr, si, e[ia + IM]));
        sr = nr; si = ni;
        if (i == 1 && s == C_AT) { asm volatile("pmevent 0;" : "+f"(sr), "+f"(si)::"memory"); first_load(0); }
      }
      float ur = __shfl_up_sync(0xffffffffu, sr, 1, 4), ui = __shfl_up_sync(0xffffffffu, si, 1, 4);
      if (c >= 1) { sr = fmaf(pr, ur, fmaf(-pi, ui, sr)); si = fmaf(pr, ui, fmaf(pi, ur, si)); }
      ur = __shfl_up_sync(0xffffffffu, sr, 2, 4); ui = __shfl_up_sync(0xffffffffu, si, 2, 4);
      if (c >= 2) { sr = fmaf(qr[i], ur, fmaf(-qi[i], ui, sr)); si = fmaf(qr[i], ui, fmaf(qi[i], ur, si)); }
      if (c == 3 && tc < 15)
        asm volatile("{\n.reg .b64 v;\nmov.b64 v, {%1,%2};\nst.relaxed.gpu.global.b64 [%0], v;\n}\n" ::"l"(cp + 512 * i + g), "r"((__float_as_uint(sr) & ~3u) | tag), "r"(__float_as_uint(si)) : "memory");
      PMFENCE();
      if (t == 0) STAMP(11 + i + 10 * wg);
      er[i] = __shfl_up_sync(0xffffffffu, sr, 1, 4); ei[i] = __shfl_up_sync(0xffffffffu, si, 1, 4);
      if (c == 0) er[i] = ei[i] = 0.f;
      wr[i] = (c & 1) ? pr : 1.f; wi[i] = (c & 1) ? pi : 0.f;
      if (c & 2) { float x, y; cmul(wr[i], wi[i], qr[i], qi[i], x, y); wr[i] = x; wi[i] = y; }
      vr[i] = wr[i]; vi[i] = wi[i];
      csq(vr[i], vi[i]); csq(vr[i], vi[i]);
      csq(qr[i], qi[i]); csq(qr[i], qi[i]); csq(qr[i], qi[i]);
      const int src = 4 * (lane & 7) + ct;
      vr[i] = __shfl_sync(0xffffffffu, vr[i], src); vi[i] = __shfl_sync(0xffffffffu, vi[i], src);
      qr[i] = __shfl_sync(0xffffffffu, qr[i], src); qi[i] = __shfl_sync(0xffffffffu, qi[i], src);
      asm volatile("" : "+f"(wr[i]), "+f"(wi[i]), "+f"(vr[i]), "+f"(vi[i]), "+f"(qr[i]), "+f"(qi[i]), "+f"(er[i]), "+f"(ei[i]));
    }
    uint4* hp = g_h + (32 * tc + 16 * wg + 2 * j) * 1024 + 64 * w + 4 * g + (c ^ (g >> 1));
#pragma unroll
    for (int i = 0; i < 2; i++) {
      float* e = d + 64 * i;
      const uint4 cf = lds128(ca + 512 * i);
      const float lr = __uint_as_float(cf.x), li = __uint_as_float(cf.y);
      const uint32_t gp = cf.z, gn = cf.z ^ 0x80008000u, gms = cf.w;
      PMFENCE();
      int n = 0;
#pragma unroll 1
      while (!__all_sync(0xffffffffu, (((cv[0].x ^ tag) | (cv[1].x ^ tag) | (cv[2].x ^ tag) | (cv[3].x ^ tag)) & 3) == 0) && ++n <= (SPIN_LIMIT << 4)) load_carry(i);
      if (t == 0 && i == 0) STAMP(13 + 10 * wg);
      float hr = __uint_as_float(cv[3].x), hi = __uint_as_float(cv[3].y);
#pragma unroll
      for (int m = 2; m >= 0; m--) {
        const float nr = fmaf(qr[i], hr, fmaf(-qi[i], hi, __uint_as_float(cv[m].x))), ni = fmaf(qr[i], hi, fmaf(qi[i], hr, __uint_as_float(cv[m].y)));
        hr = nr; hi = ni;
      }
      { float x, y; cmul(hr, hi, vr[i], vi[i], x, y); hr = x; hi = y; }
      hr += __shfl_xor_sync(0xffffffffu, hr, 8); hi += __shfl_xor_sync(0xffffffffu, hi, 8);
      hr = __shfl_sync(0xffffffffu, hr, g) + __shfl_sync(0xffffffffu, hr, g + 16); hi = __shfl_sync(0xffffffffu, hi, g) + __shfl_sync(0xffffffffu, hi, g + 16);
      float sr = fmaf(wr[i], hr, fmaf(-wi[i], hi, er[i])), si = fmaf(wr[i], hi, fmaf(wi[i], hr, ei[i]));
      if (t == 0 && i == 0) STAMP(14 + 10 * wg);
#pragma unroll
      for (int i8 = 0; i8 < 4; i8++) {
        asm volatile("pmevent 0;" : "+f"(sr), "+f"(si)::"memory");
        if (i == 0 && i8 == C_AT2) first_load(1);
#pragma unroll
        for (int s = 8 * i8; s < 8 * i8 + X_P2; s++) {
          const int ia = 4 * (s >> 1) + (s & 1);
          const float nr = fmaf(-li, si, fmaf(lr, sr, e[ia + RE])), ni = fmaf(li, sr, fmaf(lr, si, e[ia + IM]));
          sr = nr; si = ni;
          e[ia + RE] = nr; e[ia + IM] = ni;
        }
        if (P2_SPLIT) PMFENCE();
        uint32_t hp0[4], hp1[4];
#pragma unroll
        for (int m = 0; m < 4; m++) {
          const float* f = e + 16 * i8 + 4 * m;
          const uint32_t x = pack_bf16(f[RE], f[RE + 1]), y = pack_bf16(f[IM], f[IM + 1]);
          hp0[m] = bfma2(gp, x, bmul2(gms, y)); hp1[m] = bfma2(gn, y, bmul2(gms, x));
        }
        uint4* o = hp + 512 * (i8 >> 1) + 256 * i + 32 * (i8 & 1);
        stg128(o, make_uint4(hp0[0], hp0[1], hp0[2], hp0[3]));
        stg128(o + 1024, make_uint4(hp1[0], hp1[1], hp1[2], hp1[3]));
      }
    }
    if (t == 0) STAMP(15 + 10 * wg);
    const int trow = 128 * tc + 64 * (w & 1) + 8 * (w >> 1) + g;
    const int dcol = 128 * j + 4 * c;
    asm volatile("bar.arrive %0, 160;" ::"r"(4 + wg) : "memory");
    if (wg == 0) {
      uint2 xv[32];
      {
        const int gp = 2 * (g & 3) + (g >> 2);
        const uint32_t xa = sb + OFF_RING + (XPOS % STAGES) * STAGE_BYTES + (64 * (w & 1) + 8 * (w >> 1) + gp) * 128 + (c & 1) * 8;
        mbar_wait(bars + B_XI * 8, 0);
        mbar_wait(bars + (B_FULL + XPOS % STAGES) * 8, (XPOS / STAGES) & 1);
        if (t == 0) STAMP(18);
#pragma unroll
        for (int u = 0; u < 32; u++) {
          const int J = (u >> 1) & 7;
          if (X_NOXI) xv[u] = make_uint2(0, 0); else
          asm volatile("ld.shared.v2.u32 {%0,%1}, [%2];" : "=r"(xv[u].x), "=r"(xv[u].y) : "r"(xa + (J >> 2) * 16384 + (u >> 4) * 2048 + (u & 1) * 4096 + (((2 * (J & 3) + (c >> 1)) ^ gp) << 4)) : "memory");
        }
        uint32_t dep = P.zero;
#pragma unroll
        for (int u = 0; u < 32; u++) dep &= xv[u].x;
        bar_sync(3 + dep, 128);
        release_stage(bars + (B_EMPTY + XPOS % STAGES) * 8, t);
      }
#pragma unroll
      for (int J = 0; J < (X_NOXI ? 0 : 8); J++) {
        const uint4 ds = lds128(sb + OFF_DS + 16 * c + 64 * J);
#pragma unroll
        for (int r = 0; r < 4; r++) {
          const int u = 16 * (r >> 1) + 2 * J + (r & 1);
          float* e = d + 8 * (u >> 1) + 2 * (u & 1);
          e[0] = __uint_as_float(bfma2(blo2(xv[u].x), ds.x, 0)); e[1] = __uint_as_float(bfma2(xv[u].x, ds.y, 0));
          e[4] = __uint_as_float(bfma2(blo2(xv[u].y), ds.z, 0)); e[5] = __uint_as_float(bfma2(xv[u].y, ds.w, 0));
        }
      }
      fence_regs<128>(d);
      if (t == 0) STAMP(17);
      so = 8 * (33 % STAGES); ph = (33 / STAGES) & 1;
      const uint64_t da0 = make_desc(sb + OFF_RING + 16384, 512, 1024, 2), db0 = make_desc(sb + OFF_RING, 16, 1024, 1);
      bar_sync(2, 256);
#pragma unroll 1
      for (int kb = 0; kb < 32 - TAILB; kb++) {
        block(std::true_type(), da0, db0, kb == 0, false, 32 + kb);
      }
      float* op = P.out + (size_t)trow * 2048 + 1024 + dcol;
      auto mma = [&](int i, int kb, int k0, int k1) {
        const int s = (33 + kb) % STAGES;
        wg_fence();
#pragma unroll
        for (int k = k0; k < k1; k++) wgmma_n128<1>(d + 64 * i, da0 + s * 2048 + 512 * i + 128 * k, db0 + s * 2048 + 2 * k, 1);
        wg_commit();
      };
      auto store = [&](int i, int J0, int J1) {
#pragma unroll
        for (int J = J0; J < J1; J++) {
#pragma unroll
          for (int h = 0; h < 2; h++) {
            const float* e = d + 64 * i + 8 * J + 2 * h;
            stg128(op + (size_t)(16 * i + 32 * h) * 2048 + 16 * J, make_uint4(__float_as_uint(e[0]), __float_as_uint(e[1]), __float_as_uint(e[4]), __float_as_uint(e[5])));
          }
        }
        PMFENCE();
      };
      constexpr int K0 = 32 - TAILB;
#pragma unroll
      for (int kb = K0; kb < 32; kb++) {
        mbar_wait(bars + (B_FULL + (33 + kb) % STAGES) * 8, ((33 + kb) / STAGES) & 1);
        if (TAILB == 5 && kb == K0) { mma(0, kb, 0, 2); wg_wait<1>(); release(false); mma(0, kb, 2, 4); }
        else mma(0, kb, 0, 4);
      }
      mma(1, K0, 0, 4);
      wg_wait<1>();
      fence_regs<64>(d);
      if (t == 0) STAMP(48);
#pragma unroll
      for (int kb = K0 + 1; kb < 32; kb++) {
        mma(1, kb, 0, 4);
        if (T_FENCE) PMFENCE();
        store(0, T_ST * (kb - K0 - 1), kb == 31 ? 8 : T_ST * (kb - K0));
      }
      if (t == 0) STAMP(49);
      wg_wait<0>();
      fence_regs<64>(d + 64);
      if (t == 0) STAMP(50);
      store(1, 0, 8);
      if (t == 0) { STAMP(51); GSTAMP(51); }
      if (t == 0) g_epoch[b * 32] = epoch;
    }
  }
}

typedef CUresult (*EncodeFn)(CUtensorMap*, CUtensorMapDataType, cuuint32_t, void*, const cuuint64_t*, const cuuint64_t*, const cuuint32_t*,
                             const cuuint32_t*, CUtensorMapInterleave, CUtensorMapSwizzle, CUtensorMapL2promotion, CUtensorMapFloatOOBfill);

bool encode(EncodeFn fn, CUtensorMap* m, int rank, const void* base, const cuuint64_t* dims, const cuuint64_t* strides, const cuuint32_t* box, CUtensorMapSwizzle swz,
            CUtensorMapL2promotion promo = CU_TENSOR_MAP_L2_PROMOTION_L2_128B) {
  const cuuint32_t es[5] = {1, 1, 1, 1, 1};
  return fn(m, CU_TENSOR_MAP_DATA_TYPE_BFLOAT16, rank, const_cast<void*>(base), dims, strides, box, es, CU_TENSOR_MAP_INTERLEAVE_NONE, swz,
            promo, CU_TENSOR_MAP_FLOAT_OOB_FILL_NONE) == CUDA_SUCCESS;
}

}

extern "C" void kernel_launch(void* const* d_in, const int* in_sizes, int n_in, void* d_out, int out_size) {
  (void)in_sizes; (void)n_in; (void)out_size;
  typedef const __nv_bfloat16* In;
  const In q = (In)d_in[0], k = (In)d_in[1], v = (In)d_in[2], ssm_k = (In)d_in[4], x = (In)d_in[6], B_re = (In)d_in[9], B_im = (In)d_in[10], C_re = (In)d_in[11], C_im = (In)d_in[12];
  Params P = {};
  P.shift_k = (In)d_in[3]; P.ssm_D = (In)d_in[5]; P.lam_re = (In)d_in[7]; P.lam_im = (In)d_in[8]; P.log_dt = (In)d_in[13]; P.Dskip = (In)d_in[14];
  P.out = (float*)d_out;
  for (int cl = 0; cl < 64; cl++) P.slot[cl >> 2] |= (cl < 4 ? 4 + cl : cl < 36 ? 8 * ((cl - 4) & 7) + ((cl - 4) >> 3) : 8 * (1 + (cl - 36) % 7) + 4 + (cl - 36) / 7) << (8 * (cl & 3));
  const bool swapB = (uintptr_t)B_im < (uintptr_t)B_re;

  EncodeFn fn = nullptr;
  cudaDriverEntryPointQueryResult qr;
  cudaGetDriverEntryPoint("cuTensorMapEncodeTiled", (void**)&fn, cudaEnableDefault, &qr);
  if (!fn) return;

  CUtensorMap mX, mB, mCre, mCim, mXs, mK, mV, mQ, mS;
  bool ok = true;
  {
    const cuuint64_t dims[4] = {1024, 2, 64, 16}, str[3] = {2048, 32 * 2048, 2 * 2048};
    const cuuint32_t box[4] = {64, 2, 4, 16};
    ok &= encode(fn, &mX, 4, x, dims, str, box, CU_TENSOR_MAP_SWIZZLE_128B);
  }
  {
    const uintptr_t lo = swapB ? (uintptr_t)B_im : (uintptr_t)B_re, hi = swapB ? (uintptr_t)B_re : (uintptr_t)B_im;
    const cuuint64_t dims[4] = {1024, 8, 2, 128}, str[3] = {2048, (cuuint64_t)(hi - lo), 8 * 2048};
    const cuuint32_t box[4] = {64, 8, 2, 4};
    ok &= encode(fn, &mB, 4, (const void*)lo, dims, str, box, CU_TENSOR_MAP_SWIZZLE_128B);
  }
  {
    const cuuint64_t dims[5] = {1024, 2, 4, 2, 64}, str[4] = {2048, 4 * 2048, 2 * 2048, 16 * 2048};
    const cuuint32_t box[5] = {64, 2, 4, 2, 4};
    ok &= encode(fn, &mCre, 5, C_re, dims, str, box, CU_TENSOR_MAP_SWIZZLE_128B);
    ok &= encode(fn, &mCim, 5, C_im, dims, str, box, CU_TENSOR_MAP_SWIZZLE_128B);
  }
  {
    const cuuint64_t dims[4] = {1024, 2, 4, 256}, str[3] = {4 * 2048, 2048, 8 * 2048};
    const cuuint32_t box[4] = {64, 2, 4, 16};
    ok &= encode(fn, &mXs, 4, x, dims, str, box, CU_TENSOR_MAP_SWIZZLE_128B);
  }
  {
    const cuuint64_t dims[3] = {1024, 64, 32}, str[2] = {32 * 2048, 2048};
    const cuuint32_t box[3] = {16, 32, 4};
    ok &= encode(fn, &mQ, 3, q, dims, str, box, CU_TENSOR_MAP_SWIZZLE_NONE);
    ok &= encode(fn, &mK, 3, k, dims, str, box, CU_TENSOR_MAP_SWIZZLE_32B);
    ok &= encode(fn, &mV, 3, v, dims, str, box, CU_TENSOR_MAP_SWIZZLE_32B);
  }
  {
    const cuuint64_t dims[2] = {32, 65536}, str[1] = {64};
    const cuuint32_t box[2] = {32, 64};
    ok &= encode(fn, &mS, 2, ssm_k, dims, str, box, CU_TENSOR_MAP_SWIZZLE_64B);
  }
  if (!ok) return;
  auto kern = swapB ? fused_kernel<1> : fused_kernel<0>;
  cudaFuncSetAttribute(kern, cudaFuncAttributeMaxDynamicSharedMemorySize, SMEM_BYTES);
  kern<<<NCTA, 512, SMEM_BYTES, cudaStreamPerThread>>>(P, mX, mB, mCre, mCim, mXs, mK, mV, mQ, mS);
}
```

```cpp
#include <cuda_runtime.h>
#include <cuda_bf16.h>
#include <cuda.h>
#include <stdint.h>
#include <type_traits>

#define PROFILE 0

namespace {

constexpr int D_DIM = 1024;
constexpr int NCTA = 128;

constexpr int STAGES = 5, STAGE_BYTES = 32768;
constexpr int OFF_RING = 0;
constexpr int OFF_F1 = STAGES * STAGE_BYTES, OFF_F2 = OFF_F1 + 4096, OFF_K = OFF_F2 + 2048, OFF_VP = OFF_K + 8192, OFF_Q = OFF_VP + 4096, OFF_IN = OFF_Q + 8192;
constexpr int OFF_KV = OFF_K;
constexpr int U_CH = 528, U_N8 = 8 * U_CH, OFF_U = OFF_IN + U_N8;
constexpr int OFF_COEF = OFF_U + 8 * U_N8;
constexpr int OFF_DS = OFF_COEF + 2048, OFF_D = OFF_DS + 512;
constexpr int OFF_BAR = OFF_D + 64;
constexpr int OFF_PROF = OFF_BAR + 448;
constexpr int SMEM_BYTES = OFF_PROF + 512;
static_assert(SMEM_BYTES <= 232448 && OFF_K % 1024 == 0 && (OFF_U + 3 * U_N8) % 512 == 0 && (4 * U_N8) % 512 == 0, "smem map");
constexpr int B_FULL = 0, B_XI = 5, B_HR = 6, B_HP = 7, B_KVF = 8, B_KF = 11, B_KE = 13, B_QF = 15, B_IN = 19, B_UF = 27, B_Y = 31, B_CD = 35, B_ACK = 36,
              B_EMPTY = 38, B_PEER = 43, B_COEF = 48, B_KVE = 49, B_QE = 52, B_EPOCH = 55;
__host__ __device__ constexpr int q_slot(int i) { return i < 2 ? OFF_Q + 4096 * i : i < 5 ? OFF_K + 4096 * (i - 2) : i == 5 ? OFF_F1 : OFF_Q + 4096 * (i - 6); }
__host__ __device__ constexpr int q_bar(int i) { return 8 * (i < 2 ? B_QF + i : i < 4 ? B_KF + i - 2 : i < 6 ? B_QF + i - 2 : B_QF + i - 6); }

#define QD1 8
#define QD2 2
#define QD3 8
#define QSW 16
#define HEAD 3
#define ST_T0 200
#define ST_DELAY 300
#define XPOS 28
#define K_T0 800
#define KV_T0 1500
#define KV_DT 500
#define KV_DV 100
#define O_PACE 170
#define H_PACE 0
#define CARRY_WAIT 600
#define POLL_NS 30
#define GREEDY 0
#define P2_SPLIT 0
#define TAILB 5
#define GREG 176
#define O_WAIT 2
#define COEF_T0 2500
#define O_EVERY 1
#define X_P1 32
#define X_P2 8
#define X_NOXI 0
#define RELPOS 0
#define O_UNR 4
constexpr int O_UNROLL = O_UNR;
#define C_AT 0
#define C_AT2 1
#define T_FENCE 0
#define T_ST 2
#define X_PROMO 2
#define B_PROMO 2
#define C_PROMO 2
#define KV_PROMO 2
#define Q_PROMO 2
#define S_PROMO 2
#define SHAKE 0
#define PRE_S 0
#define PRE_G 2
#define POW2 0
#define O_SLEEP 20
#define CFM 0x40f1
constexpr int SPIN_LIMIT = 1 << 14;

struct Params {
  unsigned slot[16];
  unsigned zero;
  const __nv_bfloat16 *shift_k, *ssm_D, *lam_re, *lam_im, *log_dt, *Dskip;
  float* out;
};

__device__ __align__(1024) uint4 g_h[16 * 32 * 1024];
__device__ __align__(128) uint2 g_carry[32 * 16 * 32];
__device__ unsigned g_flagH[2 * 16 * 32];
__device__ unsigned g_epoch[NCTA * 32];
#define STAMP(i)
#define GSTAMP(i)
#define TSTAMP(k, n)
#define KSTAMP(k, n)

__device__ __forceinline__ uint64_t make_desc(uint32_t addr, uint32_t lbo, uint32_t sbo, uint32_t swz) {
  return (uint64_t)((addr & 0x3FFFF) >> 4) | ((uint64_t)(lbo >> 4) << 16) | ((uint64_t)(sbo >> 4) << 32) | ((uint64_t)swz << 62);
}
__device__ __forceinline__ void wg_fence() { asm volatile("wgmma.fence.sync.aligned;" ::: "memory"); }
__device__ __forceinline__ void wg_commit() { asm volatile("wgmma.commit_group.sync.aligned;" ::: "memory"); }
template <int N> __device__ __forceinline__ void wg_wait() { asm volatile("wgmma.wait_group.sync.aligned %0;" ::"n"(N) : "memory"); }
__device__ __forceinline__ void mbar_init(uint32_t bar, int cnt) { asm volatile("mbarrier.init.shared::cta.b64 [%0], %1;" ::"r"(bar), "r"(cnt) : "memory"); }
__device__ __forceinline__ void mbar_expect(uint32_t bar, uint32_t bytes) { asm volatile("mbarrier.arrive.expect_tx.shared::cta.b64 _, [%0], %1;" ::"r"(bar), "r"(bytes) : "memory"); }
__device__ __forceinline__ void mbar_wait(uint32_t bar, uint32_t parity) {
  uint32_t ok; int n = 0;
  do {
    asm volatile("{\n.reg .pred p;\nmbarrier.try_wait.parity.shared::cta.b64 p, [%1], %2;\nselp.u32 %0, 1, 0, p;\n}\n" : "=r"(ok) : "r"(bar), "r"(parity) : "memory");
    if (++n > SPIN_LIMIT) break;
  } while (!ok);
}
__device__ __forceinline__ void mbar_arrive(uint32_t bar) { asm volatile("mbarrier.arrive.shared::cta.b64 _, [%0];" ::"r"(bar) : "memory"); }
__device__ __forceinline__ void mbar_arrive_cta(uint32_t bar, uint32_t cta) {
  asm volatile("{\n.reg .b32 ra;\nmapa.shared::cluster.u32 ra, %0, %1;\nmbarrier.arrive.shared::cluster.b64 _, [ra];\n}\n" ::"r"(bar), "r"(cta) : "memory");
}
__device__ __forceinline__ bool elect_one() {
  uint32_t p;
  asm volatile("{\n.reg .pred P;\nelect.sync _|P, 0xffffffff;\nselp.u32 %0, 1, 0, P;\n}\n" : "=r"(p));
  return p != 0;
}
__device__ __forceinline__ void bar_sync(int id, int n) { asm volatile("bar.sync %0, %1;" ::"r"(id), "r"(n) : "memory"); }
#define TMA_LD(dim) "cp.async.bulk.tensor." dim ".shared::cluster.global.mbarrier::complete_tx::bytes"
__device__ __forceinline__ void tma2d(uint32_t dst, const CUtensorMap* m, int c0, int c1, uint32_t bar) {
  asm volatile(TMA_LD("2d") " [%0], [%1, {%3, %4}], [%2];" ::"r"(dst), "l"(m), "r"(bar), "r"(c0), "r"(c1) : "memory");
}
__device__ __forceinline__ void tma3d(uint32_t dst, const CUtensorMap* m, int c0, int c1, int c2, uint32_t bar) {
  asm volatile(TMA_LD("3d") " [%0], [%1, {%3, %4, %5}], [%2];" ::"r"(dst), "l"(m), "r"(bar), "r"(c0), "r"(c1), "r"(c2) : "memory");
}
__device__ __forceinline__ void tma4d(uint32_t dst, const CUtensorMap* m, int c0, int c1, int c2, int c3, uint32_t bar) {
  asm volatile(TMA_LD("4d") " [%0], [%1, {%3, %4, %5, %6}], [%2];" ::"r"(dst), "l"(m), "r"(bar), "r"(c0), "r"(c1), "r"(c2), "r"(c3) : "memory");
}
__device__ __forceinline__ void tma4d_mc(uint32_t dst, const CUtensorMap* m, int c0, int c1, int c2, int c3, uint32_t bar) {
  asm volatile(TMA_LD("4d") ".multicast::cluster [%0], [%1, {%3, %4, %5, %6}], [%2], %7;" ::"r"(dst), "l"(m), "r"(bar), "r"(c0), "r"(c1), "r"(c2), "r"(c3), "h"((uint16_t)3) : "memory");
}
__device__ __forceinline__ void tma5d_mc(uint32_t dst, const CUtensorMap* m, int c0, int c1, int c2, int c3, int c4, uint32_t bar) {
  asm volatile(TMA_LD("5d") ".multicast::cluster [%0], [%1, {%3, %4, %5, %6, %7}], [%2], %8;" ::"r"(dst), "l"(m), "r"(bar), "r"(c0), "r"(c1), "r"(c2), "r"(c3), "r"(c4), "h"((uint16_t)3) : "memory");
}
__device__ __forceinline__ void bulk_load(uint32_t dst, const void* src, uint32_t bytes, uint32_t bar) {
  asm volatile("cp.async.bulk.shared::cluster.global.mbarrier::complete_tx::bytes [%0], [%1], %2, [%3];" ::"r"(dst), "l"(src), "r"(bytes), "r"(bar) : "memory");
}
__device__ __forceinline__ void bulk_send(uint32_t dst, uint32_t src, uint32_t bytes, uint32_t bar, uint32_t cta) {
  asm volatile("{\n.reg .b32 rd, rb;\nmapa.shared::cluster.u32 rd, %0, %3;\nmapa.shared::cluster.u32 rb, %2, %3;\n"
               "cp.async.bulk.shared::cluster.shared::cta.mbarrier::complete_tx::bytes [rd], [%1], %4, [rb];\n}\n"
               ::"r"(dst), "r"(src), "r"(bar), "r"(cta), "r"(bytes) : "memory");
}
__device__ __forceinline__ void fence_proxy_async_smem() { asm volatile("fence.proxy.async.shared::cta;" ::: "memory"); }
__device__ __forceinline__ void fence_proxy_async_global() { asm volatile("fence.proxy.async.global;" ::: "memory"); }
__device__ __forceinline__ void red_release(unsigned* p, unsigned v) { asm volatile("red.release.gpu.global.add.u32 [%0], %1;" ::"l"(p), "r"(v) : "memory"); }
__device__ __forceinline__ uint32_t clk32() { uint32_t c; asm volatile("mov.u32 %0, %%clock;" : "=r"(c)::"memory"); return c; }
__device__ __forceinline__ void wait_until(uint32_t t0, uint32_t dt) { while (clk32() - t0 < dt) __nanosleep(32); }
__device__ __forceinline__ void spin_until(uint32_t t0, uint32_t dt) { while (clk32() - t0 < dt) {} }
__device__ __forceinline__ void prefetch_map(const CUtensorMap* m) { asm volatile("prefetch.tensormap [%0];" ::"l"(m) : "memory"); }
__device__ __forceinline__ void prefetch_line(const void* p) { asm volatile("prefetch.global.L2 [%0];" ::"l"(p) : "memory"); }
__device__ __forceinline__ unsigned ld_acquire(const unsigned* p) { unsigned v; asm volatile("ld.acquire.gpu.global.u32 %0, [%1];" : "=r"(v) : "l"(p) : "memory"); return v; }
__device__ __forceinline__ unsigned ld_relaxed(const unsigned* p) { unsigned v; asm volatile("ld.relaxed.gpu.global.u32 %0, [%1];" : "=r"(v) : "l"(p) : "memory"); return v; }
__device__ __forceinline__ uint32_t lds32(uint32_t a) { uint32_t v; asm volatile("ld.shared.u32 %0, [%1];" : "=r"(v) : "r"(a)); return v; }
__device__ __forceinline__ uint2 lds64(uint32_t a) { uint2 v; asm volatile("ld.shared.v2.u32 {%0,%1}, [%2];" : "=r"(v.x), "=r"(v.y) : "r"(a) : "memory"); return v; }
__device__ __forceinline__ uint4 lds128(uint32_t a) { uint4 v; asm volatile("ld.shared.v4.u32 {%0,%1,%2,%3}, [%4];" : "=r"(v.x), "=r"(v.y), "=r"(v.z), "=r"(v.w) : "r"(a) : "memory"); return v; }
__device__ __forceinline__ void sts32(uint32_t a, uint32_t v) { asm volatile("st.shared.u32 [%0], %1;" ::"r"(a), "r"(v) : "memory"); }
__device__ __forceinline__ void sts128(uint32_t a, uint4 v) { asm volatile("st.shared.v4.u32 [%0], {%1,%2,%3,%4};" ::"r"(a), "r"(v.x), "r"(v.y), "r"(v.z), "r"(v.w) : "memory"); }
__device__ __forceinline__ void ldsm4(uint32_t* r, uint32_t a) { asm volatile("ldmatrix.sync.aligned.m8n8.x4.shared.b16 {%0,%1,%2,%3}, [%4];" : "=r"(r[0]), "=r"(r[1]), "=r"(r[2]), "=r"(r[3]) : "r"(a) : "memory"); }
__device__ __forceinline__ void ldsm4t(uint32_t* r, uint32_t a) { asm volatile("ldmatrix.sync.aligned.m8n8.x4.trans.shared.b16 {%0,%1,%2,%3}, [%4];" : "=r"(r[0]), "=r"(r[1]), "=r"(r[2]), "=r"(r[3]) : "r"(a) : "memory"); }
__device__ __forceinline__ void stsm4t(uint32_t a, uint32_t r0, uint32_t r1, uint32_t r2, uint32_t r3) {
  asm volatile("stmatrix.sync.aligned.m8n8.x4.trans.shared.b16 [%0], {%1,%2,%3,%4};" ::"r"(a), "r"(r0), "r"(r1), "r"(r2), "r"(r3) : "memory");
}
__device__ __forceinline__ uint4 ldg128_nc(const void* p) { uint4 v; asm volatile("ld.global.nc.L1::no_allocate.v4.u32 {%0,%1,%2,%3}, [%4];" : "=r"(v.x), "=r"(v.y), "=r"(v.z), "=r"(v.w) : "l"(p)); return v; }
__device__ __forceinline__ void stg128(void* p, uint4 v) { asm volatile("st.global.L1::no_allocate.v4.u32 [%0], {%1,%2,%3,%4};" ::"l"(p), "r"(v.x), "r"(v.y), "r"(v.z), "r"(v.w) : "memory"); }
__device__ __forceinline__ uint32_t pack_bf16(float lo, float hi) { uint32_t r; asm("cvt.rn.bf16x2.f32 %0, %1, %2;" : "=r"(r) : "f"(hi), "f"(lo)); return r; }
__device__ __forceinline__ uint32_t bmul2(uint32_t a, uint32_t b) { uint32_t r; asm("mul.rn.bf16x2 %0, %1, %2;" : "=r"(r) : "r"(a), "r"(b)); return r; }
__device__ __forceinline__ uint32_t bfma2(uint32_t a, uint32_t b, uint32_t c) { uint32_t r; asm("fma.rn.bf16x2 %0, %1, %2, %3;" : "=r"(r) : "r"(a), "r"(b), "r"(c)); return r; }
__device__ __forceinline__ uint32_t blo2(uint32_t a) { uint32_t r; asm("{\n.reg .b16 l, h;\nmov.b32 {l, h}, %1;\nmov.b32 %0, {l, l};\n}" : "=r"(r) : "r"(a)); return r; }
__device__ __forceinline__ float bf2f(__nv_bfloat16 v) { return __bfloat162float(v); }

#define R8(d, o) "+f"(d[o]), "+f"(d[o + 1]), "+f"(d[o + 2]), "+f"(d[o + 3]), "+f"(d[o + 4]), "+f"(d[o + 5]), "+f"(d[o + 6]), "+f"(d[o + 7])
#define R16(d, o) R8(d, o), R8(d, o + 8)
#define R64(d, o) R16(d, o), R16(d, o + 16), R16(d, o + 32), R16(d, o + 48)
template <int TA> __device__ __forceinline__ void wgmma_n128(float* d, uint64_t da, uint64_t db, int scale_d) {
  asm volatile("{\n.reg .pred p;\nsetp.ne.b32 p, %66, 0;\n"
    "wgmma.mma_async.sync.aligned.m64n128k16.f32.bf16.bf16 {"
    "%0,%1,%2,%3,%4,%5,%6,%7,%8,%9,%10,%11,%12,%13,%14,%15,%16,%17,%18,%19,%20,%21,%22,%23,%24,%25,%26,%27,%28,%29,%30,%31,"
    "%32,%33,%34,%35,%36,%37,%38,%39,%40,%41,%42,%43,%44,%45,%46,%47,%48,%49,%50,%51,%52,%53,%54,%55,%56,%57,%58,%59,%60,%61,%62,%63"
    "}, %64, %65, p, 1, 1, %67, 0;\n}\n"
    : R64(d, 0)
    : "l"(da), "l"(db), "r"(scale_d), "n"(TA));
}
template <int N> __device__ __forceinline__ void fence_regs(float* d) {
#pragma unroll
  for (int i = 0; i < N; i++) asm volatile("" : "+f"(d[i])::"memory");
}
#define PMFENCE() asm volatile("pmevent 0;" ::: "memory")
__device__ __forceinline__ void cmul(float ar, float ai, float br, float bi, float& cr, float& ci) {
  cr = ar * br - ai * bi; ci = ar * bi + ai * br;
}
__device__ __forceinline__ void csq(float& r, float& i) { const float x = fmaf(r, r, -i * i), y = (r + r) * i; r = x; i = y; }

#define W8(d, o) "=f"(d[o]), "=f"(d[o + 1]), "=f"(d[o + 2]), "=f"(d[o + 3]), "=f"(d[o + 4]), "=f"(d[o + 5]), "=f"(d[o + 6]), "=f"(d[o + 7])
#define L16 "{%0,%1,%2,%3,%4,%5,%6,%7,%8,%9,%10,%11,%12,%13,%14,%15}"
#define L32 "{%0,%1,%2,%3,%4,%5,%6,%7,%8,%9,%10,%11,%12,%13,%14,%15,%16,%17,%18,%19,%20,%21,%22,%23,%24,%25,%26,%27,%28,%29,%30,%31}"
template <int ACC, int TB> __device__ __forceinline__ void rs_n32(float* d, const uint32_t* a, uint64_t db) {
  if constexpr (ACC) asm volatile("wgmma.mma_async.sync.aligned.m64n32k16.f32.bf16.bf16 " L16 ", {%16,%17,%18,%19}, %20, 1, 1, 1, %21;" : R16(d, 0) : "r"(a[0]), "r"(a[1]), "r"(a[2]), "r"(a[3]), "l"(db), "n"(TB));
  else asm volatile("wgmma.mma_async.sync.aligned.m64n32k16.f32.bf16.bf16 " L16 ", {%16,%17,%18,%19}, %20, 0, 1, 1, %21;" : W8(d, 0), W8(d, 8) : "r"(a[0]), "r"(a[1]), "r"(a[2]), "r"(a[3]), "l"(db), "n"(TB));
}
template <int ACC, int TB> __device__ __forceinline__ void ss_n64(float* d, uint64_t da, uint64_t db) {
  if constexpr (ACC) asm volatile("wgmma.mma_async.sync.aligned.m64n64k16.f32.bf16.bf16 " L32 ", %32, %33, 1, 1, 1, 0, %34;" : R16(d, 0), R16(d, 16) : "l"(da), "l"(db), "n"(TB));
  else asm volatile("wgmma.mma_async.sync.aligned.m64n64k16.f32.bf16.bf16 " L32 ", %32, %33, 0, 1, 1, 0, %34;" : W8(d, 0), W8(d, 8), W8(d, 16), W8(d, 24) : "l"(da), "l"(db), "n"(TB));
}
template <int ACC> __device__ __forceinline__ void ss_n32_tt(float* d, uint64_t da, uint64_t db) {
  if constexpr (ACC) asm volatile("wgmma.mma_async.sync.aligned.m64n32k16.f32.bf16.bf16 " L16 ", %16, %17, 1, 1, 1, 1, 1;" : R16(d, 0) : "l"(da), "l"(db));
  else asm volatile("wgmma.mma_async.sync.aligned.m64n32k16.f32.bf16.bf16 " L16 ", %16, %17, 0, 1, 1, 1, 1;" : W8(d, 0), W8(d, 8) : "l"(da), "l"(db));
}
__device__ __forceinline__ void stsm4(uint32_t a, uint32_t r0, uint32_t r1, uint32_t r2, uint32_t r3) {
  asm volatile("stmatrix.sync.aligned.m8n8.x4.shared.b16 [%0], {%1,%2,%3,%4};" ::"r"(a), "r"(r0), "r"(r1), "r"(r2), "r"(r3) : "memory");
}
template <int N> __device__ __forceinline__ void fence_u32(uint32_t* d) {
#pragma unroll
  for (int i = 0; i < N; i++) asm volatile("" : "+r"(d[i])::"memory");
}
__device__ __forceinline__ void pack32(uint32_t* f, const float* z) {
#pragma unroll
  for (int i = 0; i < 16; i++) f[i] = pack_bf16(z[2 * i], z[2 * i + 1]);
}
template <int INV> __device__ __forceinline__ void twiddle(uint32_t* f, const uint32_t* tp, const uint32_t* ts) {
#pragma unroll
  for (int i = 0; i < 8; i++) {
    uint32_t x = f[2 * i + INV], y = f[2 * i + 1 - INV];
    x = bfma2(tp[i & 3], y, x); y = bfma2(ts[i & 3], x, y); x = bfma2(tp[i & 3], y, x);
    f[2 * i + INV] = x; f[2 * i + 1 - INV] = y;
  }
}
__device__ __forceinline__ uint32_t bfnma2(uint32_t a, uint32_t b, uint32_t c) { uint32_t r; asm("{\n.reg .b32 t;\nmul.bf16x2 t, %1, %2;\nsub.bf16x2 %0, %3, t;\n}" : "=r"(r) : "r"(a), "r"(b), "r"(c)); return r; }
__device__ __forceinline__ uint32_t bfms2(uint32_t a, uint32_t b, uint32_t c) { uint32_t r; asm("{\n.reg .b32 t;\nmul.bf16x2 t, %1, %2;\nsub.bf16x2 %0, t, %3;\n}" : "=r"(r) : "r"(a), "r"(b), "r"(c)); return r; }
template <int ADD> __device__ __forceinline__ void bimac(uint32_t* o, const uint32_t* a, const uint32_t* b, const uint32_t* c) {
#pragma unroll
  for (int J = 0; J < 2; J++) {
    const uint32_t Pr = a[2 * J], Pi = a[2 * J + 1], Qr = a[2 * J + 4], Qi = a[2 * J + 5], pr = b[2 * J], pi = b[2 * J + 1], qr = b[2 * J + 4], qi = b[2 * J + 5];
    uint32_t x0, x1, x2, x3;
    if (ADD == 0) { x0 = bmul2(Pr, pr); x1 = bmul2(Pr, pi); x2 = bmul2(Pr, qr); x3 = bmul2(Pr, qi); }
    if (ADD == 1) { x0 = bfma2(Pr, pr, c[2 * J]); x1 = bfma2(Pr, pi, c[2 * J + 1]); x2 = bfma2(Pr, qr, c[2 * J + 4]); x3 = bfma2(Pr, qi, c[2 * J + 5]); }
    if (ADD == 2) { x0 = bfma2(Pr, pr, c[2 * J + 1]); x1 = bfms2(Pr, pi, c[2 * J]); x2 = bfma2(Pr, qr, c[2 * J + 5]); x3 = bfms2(Pr, qi, c[2 * J + 4]); }
    x0 = bfnma2(Pi, pi, x0); x1 = bfma2(Pi, pr, x1); x2 = bfnma2(Pi, qi, x2); x3 = bfma2(Pi, qr, x3);
    x0 = bfnma2(Qr, qr, x0); x1 = bfnma2(Qr, qi, x1); x2 = bfma2(Qr, pr, x2); x3 = bfma2(Qr, pi, x3);
    x0 = bfma2(Qi, qi, x0); x1 = bfnma2(Qi, qr, x1); x2 = bfnma2(Qi, pi, x2); x3 = bfma2(Qi, pr, x3);
    o[2 * J] = x0; o[2 * J + 1] = x1; o[2 * J + 4] = x2; o[2 * J + 5] = x3;
  }
}
__device__ __forceinline__ void sincos8k(int n, float& s, float& c) {
  const float x = (float)((n << 19) >> 19) * (6.283185307179586f / 8192.f);
  s = __sinf(x); c = __cosf(x);
}
__device__ __forceinline__ void fft_tables(uint32_t f1a, uint32_t f2a, int w, int lane, uint32_t* tp, uint32_t* ts, float& d0r, float& d0i) {
  const int c = lane & 3, f1 = 8 * w + (lane >> 2);
#pragma unroll 1
  for (int J = 3; J >= 0; J--) {
    const int a = 8 * J + 2 * c;
    float s0, c0, s1, c1;
    sincos8k(64 * (4 * f1 + 1) * a + 31 * (4 * f1 - 63), d0i, d0r); sincos8k(64 * (4 * f1 + 1) * (a + 1) + 31 * (4 * f1 - 63), s1, c1);
    d0r *= 0.125f; d0i *= 0.125f;
    sts32(f1a + w * 1024 + J * 128 + lane * 4, pack_bf16(d0r, 0.125f * c1)); sts32(f1a + w * 1024 + 512 + J * 128 + lane * 4, pack_bf16(d0i, 0.125f * s1));
    sincos8k(128 * (2 * (a & 15) + 1) * f1 - 128 * (a & 16), s0, c0); sincos8k(128 * (2 * (a & 15) + 3) * f1 - 128 * (a & 16), s1, c1);
    sts32(f2a + w * 512 + J * 128 + lane * 4, pack_bf16(c0, c1));
    sincos8k((4 * f1 - 63) * (2 * a - 31), s0, c0); sincos8k((4 * f1 - 63) * (2 * a - 29), s1, c1);
#pragma unroll
    for (int i = 3; i > 0; i--) { ts[i] = ts[i - 1]; tp[i] = tp[i - 1]; }
    ts[0] = pack_bf16(s0, s1); tp[0] = pack_bf16(-__fdividef(s0, 1.f + c0), -__fdividef(s1, 1.f + c1));
  }
  if (c != 0) d0r = d0i = 0.f;
}

template <int SWAPB>
__global__ void __cluster_dims__(2, 1, 1) __launch_bounds__(512, 1)
fused_kernel(const __grid_constant__ Params P, const __grid_constant__ CUtensorMap mX, const __grid_constant__ CUtensorMap mB,
             const __grid_constant__ CUtensorMap mCre, const __grid_constant__ CUtensorMap mCim, const __grid_constant__ CUtensorMap mXs,
             const __grid_constant__ CUtensorMap mK, const __grid_constant__ CUtensorMap mV, const __grid_constant__ CUtensorMap mQ, const __grid_constant__ CUtensorMap mS) {
  extern __shared__ __align__(1024) uint8_t smem_raw[];
  const uint32_t sb = (uint32_t)__cvta_generic_to_shared(smem_raw);
  const uint32_t bars = sb + OFF_BAR;
  const int slot = (P.slot[blockIdx.x >> 3] >> (4 * (blockIdx.x & 6))) & 63, rank = blockIdx.x & 1;
  const int j = slot & 7, tc = 2 * (slot >> 3) + rank, b = 2 * slot + rank;
  const int tid = threadIdx.x;
  const int warp = __shfl_sync(0xffffffffu, tid >> 5, 0);
  const int wg = warp >> 2;
  const uint32_t c_start = clk32();
  auto kblock = [&](int n) { return ((n & 14) == 0 || (n & 14) == 2 * j ? n ^ (2 * j) : n) & 31; };
  auto send_y = [&](int r, int n0 = 0, int n1 = 4) {
    const uint32_t src = sb + OFF_U + 4 * (rank ^ 1) * U_N8 + r * U_CH, dst = r >= 2 ? sb + OFF_U + 4 * rank * U_N8 + (r - 2) * U_CH : sb + OFF_IN + 96 + r * 2064;
#pragma unroll 1
    for (int n = n0; n < n1; n++) bulk_send(dst + n * (r >= 2 ? U_N8 : 512), src + n * U_N8, 512, bars + (B_IN + r) * 8, rank ^ 1);
  };
  auto head = [&](int n) {
    const uint32_t fb = bars + (B_FULL + n) * 8, dst = sb + OFF_RING + n * STAGE_BYTES;
    mbar_expect(fb, STAGE_BYTES);
    tma4d(dst + 16384, &mX, 64 * n, 0, 4 * tc, 0, fb);
    tma4d(dst, &mB, 64 * n, 0, 0, 8 * j, fb);
    tma4d(dst + 8192, &mB, 64 * n, 0, 0, 8 * j + 4, fb);
  };
  if (warp == 0 && elect_one()) {
    STAMP(0); GSTAMP(0);
#pragma unroll
    for (int s = 0; s < STAGES; s++) mbar_init(bars + (B_FULL + s) * 8, 1);
    head(0);
    STAMP(1);
    asm volatile("fence.mbarrier_init.release.cluster;" ::: "memory");
  }
  if (wg == 3 && elect_one()) {
    if (warp < 15) {
#pragma unroll
      for (int s = 0; s < 11; s++) mbar_init(bars + 8 * B_XI + (warp & 3) * 88 + 8 * s, 1);
    } else {
#pragma unroll
      for (int s = B_EMPTY; s < B_QE + 2; s++) mbar_init(bars + 8 * s, s < B_PEER ? (SHAKE ? 1 : 2) : s < B_COEF ? (SHAKE == 2 ? 2 : 1) : s == B_COEF ? 128 : 4);
    }
    asm volatile("fence.mbarrier_init.release.cluster;" ::: "memory");
  }
  __syncwarp();
  asm volatile("barrier.cluster.arrive.relaxed.aligned;" ::: "memory");
  if (warp == 0 && elect_one()) {
#pragma unroll 1
    for (int n = 1; n < HEAD; n++) { spin_until(c_start, ST_T0 + n * ST_DELAY); head(n); }
  }
  __syncwarp();
#define CLUSTER_WAIT() asm volatile("barrier.cluster.wait.aligned;" ::: "memory")

  if (wg == 3) {
    asm volatile("setmaxnreg.dec.sync.aligned.u32 24;");
    CLUSTER_WAIT();
    if (warp < 14) {
      if (elect_one()) {
        uint32_t so = 8 * (HEAD % STAGES), ph = HEAD < STAGES;
        auto step = [&](auto issue) {
          mbar_wait(bars + (SHAKE == 2 && warp == 12 ? B_PEER : B_EMPTY) * 8 + so, ph);
          issue(sb + OFF_RING + (so << 12), bars + B_FULL * 8 + so);
          so += 8;
          if (so == 8 * STAGES) { so = 0; ph ^= 1; }
        };
        if (warp == 12) {
          uint64_t pp = 0;
          auto shake = [&](uint32_t fb) {
            if (SHAKE == 1) mbar_arrive_cta(bars + B_PEER * 8 + so, rank ^ 1);
            mbar_expect(fb, STAGE_BYTES);
            if (SHAKE == 1) {
              mbar_wait(bars + B_PEER * 8 + so, (uint32_t)(pp >> so) & 1);
              pp ^= 1ull << so;
            }
          };
          auto g1 = [&](int n0, int n1, int grp) {
#pragma unroll 1
            for (int n = n0; n < n1; n++) step([&](uint32_t dst, uint32_t fb) { shake(fb); tma4d_mc(dst + rank * 8192, &mB, n * 64, 0, 0, grp + 4 * rank, fb); });
          };
#pragma unroll 1
          for (int n = HEAD; n < STAGES; n++) { spin_until(c_start, ST_T0 + n * ST_DELAY); g1(n, n + 1, 8 * j); }
          g1(STAGES, 16, 8 * j);
          g1(0, XPOS - 16, 8 * j + 64);
          step([&](uint32_t dst, uint32_t fb) { mbar_expect(fb, STAGE_BYTES); tma4d(dst, &mXs, 128 * j, 0, 0, 16 * tc, fb); mbar_arrive(bars + B_XI * 8); });
          g1(XPOS - 16, 16, 8 * j + 64);
#pragma unroll 1
          for (int n = 0; n < 32; n += 2) {
            const int col = kblock(n) * 32;
#pragma unroll
            for (int part = 0; part < 2; part++)
              step([&](uint32_t dst, uint32_t fb) { shake(fb); tma5d_mc(dst + rank * 8192, part ? &mCim : &mCre, col, 0, 0, 0, 8 * j + 4 * rank, fb); });
          }
        } else {
          auto g1 = [&](int n0, int n1, int nb) {
#pragma unroll 1
            for (int n = n0; n < n1; n++) step([&](uint32_t dst, uint32_t fb) { tma4d(dst + 16384, &mX, n * 64, 0, 4 * tc, 0, fb); TSTAMP(1, n + nb); });
          };
          auto g2 = [&](int n0, int n1) {
#pragma unroll 1
            for (int n = n0; n < n1; n++) step([&](uint32_t dst, uint32_t fb) { bulk_load(dst + 16384, g_h + (32 * tc + kblock(n)) * 1024, 16384, fb); TSTAMP(1, n + 32); });
          };
#pragma unroll 1
          for (int n = HEAD; n < STAGES; n++) { spin_until(c_start, ST_T0 + n * ST_DELAY); g1(n, n + 1, 0); }
          g1(STAGES, 16, 0);
          g1(0, XPOS - 16, 16);
          step([&](uint32_t dst, uint32_t fb) { tma4d(dst + 16384, &mXs, 128 * j + 64, 0, 0, 16 * tc, fb); });
          g1(XPOS - 16, 16, 16);
#pragma unroll 1
          for (int v = 0; v < 2; v++) {
            STAMP(4 + v);
            mbar_wait(bars + B_HP * 8, v);
            fence_proxy_async_global();
            STAMP(6 + v);
            g2(16 * v, 16 * v + 2);
            mbar_wait(bars + B_HR * 8, v);
            fence_proxy_async_global();
            g2(16 * v + 2, 16 * v + 16);
          }
        }
      }
    } else if (warp == 15) {
      mbar_wait(bars + B_COEF * 8, 0);
      const unsigned epoch = lds32(bars + B_EPOCH * 8);
#pragma unroll 1
      for (int v = 0; v < 2; v++) {
        unsigned* fp = &g_flagH[(16 * v + tc) * 32];
        bar_sync(4 + v, 160);
        if (elect_one()) {
          red_release(fp, 1);
          mbar_arrive(bars + B_HP * 8);
          STAMP(16 + 10 * v);
          int it = 0;
          while (ld_acquire(fp) != 8 * epoch && ++it < (SPIN_LIMIT << 4)) __nanosleep(POLL_NS);
          STAMP(2 + v);
          mbar_arrive(bars + B_HR * 8);
        }
        __syncwarp();
      }
    } else if (elect_one()) {
      const int ch0 = 16 * slot;
      auto load_k = [&](int s, uint32_t dst) { const uint32_t fb = bars + (B_KF + (s & 1)) * 8; mbar_expect(fb, 4096); tma2d(dst, &mS, 0, 64 * (8 * b + s), fb); };
      auto load_q = [&](int i) { mbar_expect(bars + q_bar(i), 4096); tma3d(sb + q_slot(i), &mQ, ch0, 32 * rank, 4 * i, bars + q_bar(i)); };
      prefetch_map(&mS); prefetch_map(&mK); prefetch_map(&mV);
      wait_until(c_start, K_T0);
      load_k(0, sb + OFF_U + (4 * rank + 3) * U_N8); load_k(1, sb + OFF_U + (4 * rank + 3) * U_N8 - 4096);
      {
        uint32_t so = 16, ph = 1;
#pragma unroll 1
        for (int e = 0; e < 9; e++) {
          const uint32_t fb = bars + B_KVF * 8 + so, dst = sb + OFF_KV + (so << 10);
          wait_until(c_start, KV_T0 + (e ? 2 * e - 1 : 0) * KV_DT);
          mbar_wait(bars + B_KVE * 8 + so, ph);
          const uint32_t c1 = clk32();
          mbar_expect(fb, e ? 8192 : 4096);
          if (e > 0) KSTAMP(1, e - 1);
          tma3d(dst, &mK, ch0, 32 * rank - (e == 0), (4 * e - 4) & 31, fb);
          if (e > 0) { wait_until(c1, KV_DV); tma3d(dst + 4096, &mV, ch0, 32 * rank, 4 * e - 4, fb); }
          so += 8;
          if (so == 24) so = 0;
          if (so == 16) ph ^= 1;
        }
      }
      prefetch_map(&mCre); prefetch_map(&mCim); prefetch_map(&mXs); prefetch_map(&mQ);
      mbar_wait(bars + B_KVE * 8, 0);
      load_k(2, sb + OFF_K); load_k(3, sb + OFF_K + 4096);
      mbar_wait(bars + (B_UF + 3) * 8, 0);
#pragma unroll 1
      for (int ch = 0; ch < 8; ch++) {
        if (ch > 0) {
          mbar_wait(bars + (B_Y + (ch & 3)) * 8, ch >> 2);
          if (ch > 2) mbar_wait(bars + (B_IN + ch - 3) * 8, 0);
          send_y(ch - 1);
        }
        if (ch < 6) {
          mbar_wait(bars + (B_KE + (ch & 1)) * 8, (ch >> 1) & 1);
          if (ch < 4) load_k(ch + 4, sb + OFF_K + (ch & 1) * 4096);
          if (ch >= 2) load_q(ch - 2);
        }
      }
#pragma unroll 1
      for (int i = 4; i < 8; i++) { mbar_wait(bars + (i < 6 ? B_CD : B_QE + i - 6) * 8, 0); load_q(i); }
    }
    return;
  } else if (wg == 2) {
    asm volatile("setmaxnreg.inc.sync.aligned.u32 %0;" ::"n"(488 - 2 * GREG));
    const int t = tid & 127, w = warp & 3, lane = t & 31, g = lane >> 2, c = lane & 3;
    const uint4 s2[2] = {ldg128_nc(P.shift_k + (8 * b + 2 * c) * 4), ldg128_nc(P.shift_k + (8 * (b ^ 1) + 2 * c) * 4)};
    const uint32_t dskip = __bfloat16_as_ushort(P.ssm_D[8 * b + (t & 7)]);
    uint32_t tp[4] = {}, ts[4] = {};
    float d0r, d0i;
    fft_tables(sb + OFF_F1, sb + OFF_F2, w, lane, tp, ts, d0r, d0i);
    if (t == 0) STAMP(19);
    CLUSTER_WAIT();
    if (t < 12) mbar_expect(bars + (B_IN + t) * 8, t < 8 ? 2048 : U_N8);
    if (t < 8) sts32(sb + OFF_D + 4 * t, dskip << 16);
    const uint64_t dF1a = make_desc(sb + OFF_F1, 128, 512, 0), dF1b = make_desc(sb + OFF_F1, 512, 128, 0);
    const uint64_t dF2f = make_desc(sb + OFF_F2, 512, 128, 0), dF2i = make_desc(sb + OFF_F2, 128, 512, 0);
    auto T1k = [&](float* z, uint64_t dk) { wg_fence(); ss_n64<0, 1>(z, dF1a, dk); ss_n64<1, 1>(z, dF1a + 16, dk + 64); wg_commit(); };
    auto T1u = [&](float* z, uint64_t du) { wg_fence(); ss_n64<0, 0>(z, dF1a, du); ss_n64<1, 0>(z, dF1a + 16, du + 16); wg_commit(); };
    auto T2 = [&](float* s, const uint32_t* f) {
      wg_fence();
      rs_n32<0, 1>(s, f, dF2f); rs_n32<0, 1>(s + 16, f + 8, dF2f); rs_n32<1, 1>(s, f + 4, dF2f + 64); rs_n32<1, 1>(s + 16, f + 12, dF2f + 64);
      wg_commit();
    };
    auto product = [&](uint32_t* pr, const uint32_t* kh, const uint32_t* uh) {
      bimac<0>(pr, kh, uh, pr); bimac<2>(pr + 8, kh + 8, uh, pr); bimac<1>(pr + 8, kh, uh + 8, pr + 8);
      fence_u32<16>(pr);
    };
    float zk[32] = {};
    uint32_t pr[16];
    {
      uint32_t kh0[16];
      {
        float z0[32], sk[32];
        uint32_t fk[16];
        const uint64_t dk = make_desc(sb + OFF_U + (4 * rank + 3) * U_N8, 2048, 512, 2);
        fence_proxy_async_smem();
        bar_sync(7, 128);
        mbar_wait(bars + B_KF * 8, 0);
        T1k(z0, dk);
        mbar_wait(bars + (B_KF + 1) * 8, 0);
        T1k(zk, dk - 256);
        wg_wait<0>(); fence_regs<32>(z0); fence_regs<32>(zk);
        const float dd = __uint_as_float(lds32(sb + OFF_D));
        z0[0] = fmaf(d0r, dd, z0[0]); z0[2] = fmaf(d0i, dd, z0[2]);
        pack32(fk, z0); twiddle<0>(fk, tp, ts); fence_u32<16>(fk);
        T2(sk, fk);
        wg_wait<0>(); fence_regs<32>(sk); fence_u32<16>(fk);
        pack32(kh0, sk); fence_u32<16>(kh0);
      }
      {
        uint32_t sk[2][4], kx[2][8];
#pragma unroll
        for (int o = 0; o < 2; o++) {
          sk[o][0] = __byte_perm(s2[o].x, s2[o].z, 0x5410); sk[o][1] = __byte_perm(s2[o].x, s2[o].z, 0x7632);
          sk[o][2] = __byte_perm(s2[o].y, s2[o].w, 0x5410); sk[o][3] = __byte_perm(s2[o].y, s2[o].w, 0x7632);
        }
        const uint32_t la = sb + OFF_KV + (lane >> 3) * 1024 + (8 * w + (lane & 7)) * 32 + ((rank ^ ((lane >> 2) & 1)) << 4);
        const uint32_t uo = (lane & 7) * U_CH + w * 128 + (lane >> 3) * 16;
        mbar_wait(bars + (B_KVF + 2) * 8, 0);
        if (t == 0) STAMP(27);
        ldsm4(kx[0], la + 16384); ldsm4(kx[1], (la ^ 16) + 16384);
        if (lane == 0) mbar_arrive(bars + (B_KVE + 2) * 8 + (kx[0][1] & kx[1][1] & P.zero));
        uint32_t so = 0, ph = 0;
#pragma unroll 1
        for (int n = 0; n < 4; n++) {
          const uint32_t own = sb + OFF_U + (4 * rank + n) * U_N8, box = n < 3 ? sb + OFF_U + (4 * (rank ^ 1) + n + 1) * U_N8 : sb + OFF_IN;
#pragma unroll
          for (int e = 0; e < 2; e++) {
            uint32_t vx[2][4];
            mbar_wait(bars + B_KVF * 8 + so, ph);
            if (t == 0) KSTAMP(2, 2 * n + e);
#pragma unroll
            for (int o = 0; o < 2; o++) { ldsm4(kx[o] + 4, (la ^ (16 * o)) + (so << 10)); ldsm4(vx[o], (la ^ (16 * o)) + (so << 10) + 4096); }
            if (lane == 0) mbar_arrive(bars + B_KVE * 8 + so + (kx[0][4] & kx[1][4] & vx[0][0] & vx[1][0] & P.zero));
#pragma unroll
            for (int o = 0; o < 2; o++) {
#pragma unroll
              for (int i = 0; i < 4; i++) vx[o][i] = bmul2(bfma2(kx[o][i + 4], sk[o][0], bfma2(kx[o][i + 3], sk[o][1], bfma2(kx[o][i + 2], sk[o][2], bmul2(kx[o][i + 1], sk[o][3])))), vx[o][i]);
              stsm4t((o ? box : own) + uo + e * 64, vx[o][0], vx[o][1], vx[o][2], vx[o][3]);
              kx[o][1] = kx[o][5]; kx[o][2] = kx[o][6]; kx[o][3] = kx[o][7];
            }
            if (t == 0) KSTAMP(3, 2 * n + e);
            so += 8;
            if (so == 24) so = 0;
            if (so == 16) ph ^= 1;
          }
          fence_proxy_async_smem();
          bar_sync(7, 128);
          if (w == 0 && elect_one()) {
            if (n > 0) mbar_wait(bars + B_UF * 8 + 8 * (n - 1), 0);
            bulk_send(own, box, U_N8, bars + B_UF * 8 + 8 * n, rank ^ 1);
          }
          __syncwarp();
        }
        if (t == 0) STAMP(28);
      }
      float zu[32], su[32];
      uint32_t fu[16], uh[16];
#pragma unroll
      for (int n = 0; n < 4; n++) mbar_wait(bars + (B_UF + n) * 8, 0);
      T1u(zu, make_desc(sb + OFF_U, 128, U_N8, 0));
      wg_wait<0>(); fence_regs<32>(zu);
      pack32(fu, zu); twiddle<0>(fu, tp, ts); fence_u32<16>(fu);
      T2(su, fu);
      wg_wait<0>(); fence_regs<32>(su); fence_u32<16>(fu);
      pack32(uh, su);
      product(pr, kh0, uh);
      if (t == 0) STAMP(54);
    }
    {
#define CF(i) do { if ((CFM >> (i)) & 1) PMFENCE(); } while (0)
#define CP(i)
      const uint32_t vs = w < 2 ? 512 : U_N8;
      uint32_t va = (w < 2 ? sb + OFF_VP : sb + OFF_U) + ((lane >> 4) & 1) * vs + (w & 1) * 256 + (lane & 15) * 16;
      uint32_t ya = sb + OFF_U + (2 * w + ((lane >> 3) & 1)) * U_N8 + (lane >> 4) * 128 + (lane & 7) * 16;
      uint64_t du = make_desc(sb + OFF_U, 128, U_N8, 0), dk = make_desc(sb + OFF_K, 2048, 512, 2);
      const uint64_t dv = make_desc(sb + OFF_VP, 128, 512, 0);
      uint32_t yp[8] = {};
      uint32_t yq = sb + OFF_Q + lane * 16;
      auto store_y = [&]() { stsm4(yq, yp[0], yp[1], yp[2], yp[3]); stsm4(yq + 256, yp[4], yp[5], yp[6], yp[7]); };
      auto step = [&](int ch, auto fwd) {
        constexpr bool FWD = decltype(fwd)::value;
        float zu[32], sk[32], su[32], v[32], y[16];
        uint32_t kh[16], uh[16], fk[16], fu[16], fv[16];
        CP(16);
        wg_fence();
        rs_n32<0, 0>(v, pr, dF2i); rs_n32<0, 0>(v + 16, pr + 8, dF2i); rs_n32<1, 0>(v, pr + 4, dF2i + 16); rs_n32<1, 0>(v + 16, pr + 12, dF2i + 16);
        wg_commit();
        CF(0);
        store_y();
        if (FWD) {
          const float dd = __uint_as_float(lds32(sb + OFF_D + 4 * (ch + 1)));
          zk[0] = fmaf(d0r, dd, zk[0]); zk[2] = fmaf(d0i, dd, zk[2]);
          pack32(fk, zk); twiddle<0>(fk, tp, ts); fence_u32<16>(fk);
          CP(1);
          T2(sk, fk);
          CF(2);
          mbar_wait(bars + (B_KF + (ch & 1)) * 8, ((ch >> 1) & 1) ^ 1);
          wg_wait<1>();
        } else wg_wait<0>();
        fence_regs<32>(v); fence_u32<16>(pr); CP(3);
        pack32(fv, v); fence_u32<16>(fv);
        CF(4);
        if (FWD) T1u(zu, du + U_CH / 16);
        CF(5);
        twiddle<1>(fv, tp, ts);
#pragma unroll
        for (int i = 0; i < 4; i++) stsm4(va + 2 * i * vs, fv[4 * i], fv[4 * i + 1], fv[4 * i + 2], fv[4 * i + 3]);
        if (FWD) {
          CF(6);
          wg_wait<1>(); fence_regs<32>(sk); fence_u32<16>(fk);
          pack32(kh, sk); fence_u32<16>(kh);
          CF(7);
          T1k(zk, dk);
          CF(8);
          wg_wait<1>(); fence_regs<32>(zu);
          pack32(fu, zu); twiddle<0>(fu, tp, ts); fence_u32<16>(fu);
          CP(9);
          T2(su, fu);
          CF(10);
        }
        fence_proxy_async_smem();
        bar_sync(7, 128);
        wg_fence(); CP(11);
        ss_n32_tt<0>(y, dv, dF1b); ss_n32_tt<1>(y, dv + 16, dF1b + 64); ss_n32_tt<1>(y, du, dF1b + 128); ss_n32_tt<1>(y, du + 16, dF1b + 192);
        wg_commit();
        if (t == 0) mbar_arrive(bars + (B_Y + (ch & 3)) * 8);
        CF(12);
        if (FWD) {
          wg_wait<1>(); fence_regs<32>(su); fence_u32<16>(fu); fence_regs<32>(zk); CP(13);
          if (t == 0) mbar_arrive(bars + (B_KE + (ch & 1)) * 8);
          pack32(uh, su);
          product(pr, kh, uh);
          du += U_CH / 16; dk += (ch & 1) ? -256 : 256;
          if (w >= 2) va += U_CH;
        }
        CF(14);
        wg_wait<0>(); fence_regs<16>(y); CP(15);
#pragma unroll
        for (int i = 0; i < 8; i++) yp[i] = pack_bf16(y[2 * i], y[2 * i + 1]);
        fence_u32<8>(yp);
        yq = ya;
        ya += U_CH; CP(17);
        if (t == 0) STAMP(55 + ch);
      };
#pragma unroll 1
      for (int ch = 0; ch < 7; ch++) step(ch, std::true_type());
      step(7, std::false_type());
      store_y();
    }
    fence_proxy_async_smem();
    bar_sync(9, 256);
    if (t == 0) STAMP(29);
  } else {
    asm volatile("setmaxnreg.inc.sync.aligned.u32 %0;" ::"n"(GREG));
    const int t = tid & 127, w = warp & 3, lane = t & 31, g = lane >> 2, c = lane & 3;
    if (wg == 1) {
      wait_until(c_start, COEF_T0);
      const int p = 64 * j + (t & 63) + 8 * (t & 64);
      const float Lr = bf2f(P.lam_re[p]), Li = bf2f(P.lam_im[p]);
      const uint32_t ds = __bfloat16_as_ushort(P.Dskip[128 * j + t]);
      const unsigned epoch = ld_relaxed(&g_epoch[b * 32]) + 1;
      const float dt = bf2f(__float2bfloat16_rn(expf(bf2f(P.log_dt[p]))));
      const float e = expf(dt * Lr);
      float sn, cs;
      {
        const double z = (double)(dt * Li) * 0.15915494309189535;
        sincospif(2.f * (float)(z - rint(z)), &sn, &cs);
      }
      const float lr = e * cs, li = e * sn;
      const float nr = lr - 1.0f, ni = li;
      const bool big = fabsf(Lr) >= fabsf(Li);
      const float la = big ? Lr : Li, lb = big ? Li : Lr, r = __fdiv_rn(lb, la), inv = __frcp_rn(fmaf(lb, r, la));
      const float br = (big ? fmaf(ni, r, nr) : fmaf(nr, r, ni)) * inv, bi = (big ? fmaf(-nr, r, ni) : fmaf(ni, r, -nr)) * inv;
      sts128(sb + OFF_COEF + t * 16, make_uint4(__float_as_uint(lr), __float_as_uint(li), __float_as_uint(2.f * br), __float_as_uint(-2.f * bi)));
      sts32(sb + OFF_DS + 4 * t, ds << 16);
      if (t == 0) sts32(bars + B_EPOCH * 8, epoch);
      if (t == 0) STAMP(52);
    }
    CLUSTER_WAIT();
    if (wg == 1) mbar_arrive(bars + B_COEF * 8);
    float d[128];
    uint32_t so = 0, ph = 0, po = 0;
    uint32_t ra;
    auto set_ra = [&]() { asm volatile("mapa.shared::cluster.u32 %0, %1, %2;" : "=r"(ra) : "r"(bars + (SHAKE == 2 && (t & 3) != 2 ? B_PEER : B_EMPTY) * 8), "r"((t & 1) ? rank ^ 1 : rank)); };
    set_ra();
    auto release_at = [&](uint32_t off, bool skip) {
      asm volatile("{\n.reg .pred p;\nsetp.lt.u32 p, %1, %2;\n@p mbarrier.arrive.shared::cluster.b64 _, [%0];\n}\n" ::"r"(ra + off), "r"(t), "r"(skip ? 0 : SHAKE == 2 ? 3 : SHAKE == 1 ? 1 : 2) : "memory");
    };
    auto release = [&](bool first) { release_at(po, first); };
    auto block = [&](auto ta, uint64_t da0, uint64_t db0, bool first, bool zero, int nn) {
      constexpr int PH = decltype(ta)::value, TA = PH > 0, KS = TA ? 128 : 2, QD = PH == 0 ? QD1 : PH == 1 ? QD2 : QD3;
      if (t == 0) TSTAMP(2, nn);
      mbar_wait(bars + B_FULL * 8 + so, ph);
      if (t == 0) TSTAMP(3, nn);
      const uint64_t da = da0 + (so << 8), db = db0 + (so << 8);
      wg_fence();
      wgmma_n128<TA>(d, da, db, !zero);
      wgmma_n128<TA>(d + 64, da + 512, db, !zero);
      wg_commit();
      wg_wait<1>();
      if (RELPOS == 0) release(first);
#pragma unroll
      for (int k = 1; k < 4; k++) {
        if (QD == 2 || (QD == 4 && k == 2)) wg_fence();
        wgmma_n128<TA>(d, da + KS * k, db + 2 * k, 1);
        wgmma_n128<TA>(d + 64, da + 512 + KS * k, db + 2 * k, 1);
        if (QD == 2 || (QD == 4 && k == 1)) wg_commit();
        if (RELPOS == 1 && k == 1) release(first);
        if ((QD == 2 && k < 3) || (QD == 4 && k == 1)) wg_wait<1>();
      }
      if (QD != 2) wg_commit();
      if (RELPOS == 2) release(first);
      po = so;
      so += 8;
      if (so == 8 * STAGES) { so = 0; ph ^= 1; }
    };
    {
      so = wg ? 8 * (16 % STAGES) : 0; ph = wg ? (16 / STAGES) & 1 : 0; po = 0;
      const uint64_t da0 = make_desc(sb + OFF_RING, 16, 1024, 1), db0 = make_desc(sb + OFF_RING + 16384, 16, 1024, 1);
      if (wg == 1) bar_sync(1, 256);
#pragma unroll 1
      for (int kb = 0; kb < 16; kb++) {
        if (16 * wg + kb == XPOS) { so += 8; if (so == 8 * STAGES) { so = 0; ph ^= 1; } }
        block(std::integral_constant<int, 0>(), da0, db0, kb == 0, kb == 0, 16 * wg + kb);
      }
      asm volatile("bar.arrive %0, 256;" ::"r"(1 + wg) : "memory");
    }
    mbar_wait(bars + B_COEF * 8, 0);
    const uint32_t ca = sb + OFF_COEF + (64 * wg + 8 * w + g) * 16;
    const uint32_t tag = __shfl_sync(0xffffffffu, lds32(bars + B_EPOCH * 8) & 3, 0);
    constexpr int RE = SWAPB ? 2 : 0, IM = 2 - RE;
    uint2* cp = &g_carry[((16 * wg + 2 * j) * 16 + tc) * 32 + 8 * w];
    const int ct = lane >> 3;
    uint2 cv[4];
    auto load_carry = [&](int i) {
#pragma unroll
      for (int m = 0; m < 4; m++)
        asm volatile("{\n.reg .pred p;\n.reg .b64 v;\nsetp.lt.s32 p, %3, %4;\nmov.b64 v, {%0,%1};\n@p ld.relaxed.gpu.global.b64 v, [%2];\nmov.b64 {%0,%1}, v;\n}\n"
                     : "+r"(cv[m].x), "+r"(cv[m].y) : "l"(cp + 512 * i + (lane & 7) - 32 * (1 + ct) - 128 * m), "r"(ct), "r"(tc - 4 * m) : "memory");
    };
    auto first_load = [&](int i) {
#pragma unroll
      for (int m = 0; m < 4; m++) cv[m] = make_uint2(tag, 0);
      load_carry(i);
    };
    float lr[2], li[2], pr[2], pi[2], wr[2], wi[2], vr[2], vi[2], qr[2], qi[2], er[2], ei[2], gr[2], gi[2];
    auto powers = [&](int i) {
      const uint2 cf = lds64(ca + 512 * i);
      pr[i] = lr[i] = __uint_as_float(cf.x); pi[i] = li[i] = __uint_as_float(cf.y);
#pragma unroll
      for (int s = 0; s < 4; s++) csq(pr[i], pi[i]);
      gr[i] = pr[i]; gi[i] = pi[i];
      csq(pr[i], pi[i]);
      qr[i] = pr[i]; qi[i] = pi[i];
      csq(qr[i], qi[i]);
      er[i] = qr[i]; ei[i] = qi[i];
      wr[i] = (c & 1) ? pr[i] : 1.f; wi[i] = (c & 1) ? pi[i] : 0.f;
      if (c & 2) { float x, y; cmul(wr[i], wi[i], qr[i], qi[i], x, y); wr[i] = x; wi[i] = y; }
      vr[i] = wr[i]; vi[i] = wi[i];
      csq(vr[i], vi[i]); csq(vr[i], vi[i]);
      csq(qr[i], qi[i]); csq(qr[i], qi[i]); csq(qr[i], qi[i]);
      const int src = 4 * (lane & 7) + ct;
      vr[i] = __shfl_sync(0xffffffffu, vr[i], src); vi[i] = __shfl_sync(0xffffffffu, vi[i], src);
      qr[i] = __shfl_sync(0xffffffffu, qr[i], src); qi[i] = __shfl_sync(0xffffffffu, qi[i], src);
      asm volatile("" : "+f"(wr[i]), "+f"(wi[i]), "+f"(pr[i]), "+f"(pi[i]), "+f"(er[i]), "+f"(ei[i]));
    };
    powers(0);
    if (POW2 == 0) powers(1);
    PMFENCE();
    wg_wait<0>();
    fence_regs<128>(d);
    release(false);
    if (t == 0) STAMP(10 + 10 * wg);
#pragma unroll
    for (int i = 0; i < 2; i++) {
      const float* e = d + 64 * i;
      auto chain = [&](int s0, int s1, float& sr, float& si) {
        sr = e[2 * s0 + RE]; si = e[2 * s0 + IM];
#pragma unroll
        for (int s = s0 + 1; s < s1; s++) {
          const int ia = 4 * (s >> 1) + (s & 1);
          const float nr = fmaf(-li[i], si, fmaf(lr[i], sr, e[ia + RE])), ni = fmaf(li[i], sr, fmaf(lr[i], si, e[ia + IM]));
          sr = nr; si = ni;
        }
      };
      float sr, si;
      if (POW2 == 1 && i == 1) powers(1);
      if ((GREEDY >> i) & 1) {
        float ar, ai;
        chain(0, 16, ar, ai); chain(16, 32, sr, si);
        sr = fmaf(gr[i], ar, fmaf(-gi[i], ai, sr)); si = fmaf(gr[i], ai, fmaf(gi[i], ar, si));
      } else chain(0, 32, sr, si);
      if (i == 1 && C_AT == 0) { asm volatile("pmevent 0;" : "+f"(sr), "+f"(si)::"memory"); first_load(0); }
      float ur = __shfl_up_sync(0xffffffffu, sr, 1, 4), ui = __shfl_up_sync(0xffffffffu, si, 1, 4);
      if (c >= 1) { sr = fmaf(pr[i], ur, fmaf(-pi[i], ui, sr)); si = fmaf(pr[i], ui, fmaf(pi[i], ur, si)); }
      ur = __shfl_up_sync(0xffffffffu, sr, 2, 4); ui = __shfl_up_sync(0xffffffffu, si, 2, 4);
      if (c >= 2) { sr = fmaf(er[i], ur, fmaf(-ei[i], ui, sr)); si = fmaf(er[i], ui, fmaf(ei[i], ur, si)); }
      if (c == 3 && tc < 15)
        asm volatile("{\n.reg .b64 v;\nmov.b64 v, {%1,%2};\nst.relaxed.gpu.global.b64 [%0], v;\n}\n" ::"l"(cp + 512 * i + g), "r"((__float_as_uint(sr) & ~3u) | tag), "r"(__float_as_uint(si)) : "memory");
      if (i == 1 && C_AT == 1) first_load(0);
      PMFENCE();
      if (t == 0) STAMP(11 + i + 10 * wg);
      er[i] = __shfl_up_sync(0xffffffffu, sr, 1, 4); ei[i] = __shfl_up_sync(0xffffffffu, si, 1, 4);
      if (c == 0) er[i] = ei[i] = 0.f;
    }
    uint4* hp = g_h + (32 * tc + 16 * wg + 2 * j) * 1024 + 64 * w + 4 * g + (c ^ (g >> 1));
#pragma unroll
    for (int i = 0; i < 2; i++) {
      float* e = d + 64 * i;
      const uint2 cf = lds64(ca + 512 * i + 8);
      const float mr = __uint_as_float(cf.x), mi = __uint_as_float(cf.y);
      const uint32_t gp = pack_bf16(mr, mr), gms = pack_bf16(mi, mi);
      const int NS = i == 0 ? PRE_S : 0;
#pragma unroll
      for (int s = 32 - 8 * NS; s < 32; s++) {
        const int ia = 4 * (s >> 1) + (s & 1);
        asm volatile("{\n.reg .f32 u, v, n;\nmul.f32 u, %3, %1;\nmul.f32 v, %3, %0;\nneg.f32 n, %2;\nfma.rn.f32 %0, %2, %0, u;\nfma.rn.f32 %1, n, %1, v;\n}\n"
                     : "+f"(e[ia + RE]), "+f"(e[ia + IM]) : "f"(mr), "f"(mi));
        if (s % PRE_G == PRE_G - 1) PMFENCE();
      }
      PMFENCE();
      int n = 0;
#pragma unroll 1
      while (!__all_sync(0xffffffffu, (((cv[0].x ^ tag) | (cv[1].x ^ tag) | (cv[2].x ^ tag) | (cv[3].x ^ tag)) & 3) == 0) && ++n <= (SPIN_LIMIT << 4)) load_carry(i);
      if (t == 0 && i == 0) STAMP(13 + 10 * wg);
      float hr = __uint_as_float(cv[3].x), hi = __uint_as_float(cv[3].y);
#pragma unroll
      for (int m = 2; m >= 0; m--) {
        const float nr = fmaf(qr[i], hr, fmaf(-qi[i], hi, __uint_as_float(cv[m].x))), ni = fmaf(qr[i], hi, fmaf(qi[i], hr, __uint_as_float(cv[m].y)));
        hr = nr; hi = ni;
      }
      { float x, y; cmul(hr, hi, vr[i], vi[i], x, y); hr = x; hi = y; }
      hr += __shfl_xor_sync(0xffffffffu, hr, 8); hi += __shfl_xor_sync(0xffffffffu, hi, 8);
      hr = __shfl_sync(0xffffffffu, hr, g) + __shfl_sync(0xffffffffu, hr, g + 16); hi = __shfl_sync(0xffffffffu, hi, g) + __shfl_sync(0xffffffffu, hi, g + 16);
      float sr = fmaf(wr[i], hr, fmaf(-wi[i], hi, er[i])), si = fmaf(wr[i], hi, fmaf(wi[i], hr, ei[i]));
      if (t == 0 && i == 0) STAMP(14 + 10 * wg);
#pragma unroll
      for (int i8 = 0; i8 < 4; i8++) {
        const bool pre = i8 >= 4 - NS;
        if (i8 == 4 - NS) { const float x = sr; sr = fmaf(mr, x, mi * si); si = fmaf(-mr, si, mi * x); }
        asm volatile("pmevent 0;" : "+f"(sr), "+f"(si)::"memory");
        if (i == 0 && i8 == C_AT2) first_load(1);
        const float ls = pre ? -li[i] : li[i];
#pragma unroll
        for (int s = 8 * i8; s < 8 * i8 + 8; s++) {
          const int ia = 4 * (s >> 1) + (s & 1);
          const float nr = fmaf(-ls, si, fmaf(lr[i], sr, e[ia + RE])), ni = fmaf(ls, sr, fmaf(lr[i], si, e[ia + IM]));
          sr = nr; si = ni;
          e[ia + RE] = nr; e[ia + IM] = ni;
        }
        if (P2_SPLIT) PMFENCE();
        uint32_t hp0[4], hp1[4];
#pragma unroll
        for (int m = 0; m < 4; m++) {
          const float* f = e + 16 * i8 + 4 * m;
          const uint32_t x = pack_bf16(f[RE], f[RE + 1]), y = pack_bf16(f[IM], f[IM + 1]);
          hp0[m] = pre ? x : bfma2(gp, x, bmul2(gms, y)); hp1[m] = pre ? y : bfnma2(gp, y, bmul2(gms, x));
        }
        uint4* o = hp + 512 * (i8 >> 1) + 256 * i + 32 * (i8 & 1);
        stg128(o, make_uint4(hp0[0], hp0[1], hp0[2], hp0[3]));
        stg128(o + 1024, make_uint4(hp1[0], hp1[1], hp1[2], hp1[3]));
      }
    }
    if (t == 0) STAMP(15 + 10 * wg);
    const int trow = 128 * tc + 64 * (w & 1) + 8 * (w >> 1) + g;
    const int dcol = 128 * j + 4 * c;
    asm volatile("bar.arrive %0, 160;" ::"r"(4 + wg) : "memory");
    if (wg == 0) {
      set_ra();
      uint2 xv[32];
      {
        const int gp = 2 * (g & 3) + (g >> 2);
        const uint32_t xa = sb + OFF_RING + (XPOS % STAGES) * STAGE_BYTES + (64 * (w & 1) + 8 * (w >> 1) + gp) * 128 + (c & 1) * 8;
        mbar_wait(bars + B_XI * 8, 0);
        mbar_wait(bars + (B_FULL + XPOS % STAGES) * 8, (XPOS / STAGES) & 1);
        if (t == 0) STAMP(18);
#pragma unroll
        for (int u = 0; u < 32; u++) {
          const int J = (u >> 1) & 7;
          if (X_NOXI) xv[u] = make_uint2(0, 0); else
          asm volatile("ld.shared.v2.u32 {%0,%1}, [%2];" : "=r"(xv[u].x), "=r"(xv[u].y) : "r"(xa + (J >> 2) * 16384 + (u >> 4) * 2048 + (u & 1) * 4096 + (((2 * (J & 3) + (c >> 1)) ^ gp) << 4)) : "memory");
        }
        uint32_t dep = P.zero;
#pragma unroll
        for (int u = 0; u < 32; u++) dep &= xv[u].x;
        bar_sync(3 + dep, 128);
        release_at(8 * (XPOS % STAGES), false);
      }
#pragma unroll
      for (int J = 0; J < (X_NOXI ? 0 : 8); J++) {
        const uint4 ds = lds128(sb + OFF_DS + 16 * c + 64 * J);
#pragma unroll
        for (int r = 0; r < 4; r++) {
          const int u = 16 * (r >> 1) + 2 * J + (r & 1);
          float* e = d + 8 * (u >> 1) + 2 * (u & 1);
          e[0] = __uint_as_float(bfma2(blo2(xv[u].x), ds.x, 0)); e[1] = __uint_as_float(bfma2(xv[u].x, ds.y, 0));
          e[4] = __uint_as_float(bfma2(blo2(xv[u].y), ds.z, 0)); e[5] = __uint_as_float(bfma2(xv[u].y, ds.w, 0));
        }
      }
      fence_regs<128>(d);
      if (t == 0) STAMP(17);
      so = 8 * (33 % STAGES); ph = (33 / STAGES) & 1;
      const uint64_t da0 = make_desc(sb + OFF_RING + 16384, 512, 1024, 2), db0 = make_desc(sb + OFF_RING, 16, 1024, 1);
      bar_sync(2, 256);
#pragma unroll 1
      for (int kb = 0; kb < QSW; kb++) block(std::integral_constant<int, 1>(), da0, db0, kb == 0, false, 32 + kb);
#pragma unroll 1
      for (int kb = QSW; kb < 32 - TAILB; kb++) block(std::integral_constant<int, 2>(), da0, db0, false, false, 32 + kb);
      float* op = P.out + (size_t)trow * 2048 + 1024 + dcol;
      auto mma = [&](int i, int kb, int k0, int k1) {
        const int s = (33 + kb) % STAGES;
        wg_fence();
#pragma unroll
        for (int k = k0; k < k1; k++) wgmma_n128<1>(d + 64 * i, da0 + s * 2048 + 512 * i + 128 * k, db0 + s * 2048 + 2 * k, 1);
        wg_commit();
      };
      auto store = [&](int i, int J0, int J1) {
#pragma unroll
        for (int J = J0; J < J1; J++) {
#pragma unroll
          for (int h = 0; h < 2; h++) {
            const float* e = d + 64 * i + 8 * J + 2 * h;
            stg128(op + (size_t)(16 * i + 32 * h) * 2048 + 16 * J, make_uint4(__float_as_uint(e[0]), __float_as_uint(e[1]), __float_as_uint(e[4]), __float_as_uint(e[5])));
          }
        }
        PMFENCE();
      };
      constexpr int K0 = 32 - TAILB;
#pragma unroll
      for (int kb = K0; kb < 32; kb++) {
        mbar_wait(bars + (B_FULL + (33 + kb) % STAGES) * 8, ((33 + kb) / STAGES) & 1);
        if (TAILB == 5 && kb == K0) { mma(0, kb, 0, 2); wg_wait<1>(); release(false); mma(0, kb, 2, 4); }
        else mma(0, kb, 0, 4);
      }
      mma(1, K0, 0, 4);
      wg_wait<1>();
      fence_regs<64>(d);
      if (t == 0) STAMP(48);
#pragma unroll
      for (int kb = K0 + 1; kb < 32; kb++) {
        mma(1, kb, 0, 4);
        if (T_FENCE) PMFENCE();
        store(0, T_ST * (kb - K0 - 1), kb == 31 ? 8 : T_ST * (kb - K0));
      }
      if (t == 0) STAMP(49);
      wg_wait<0>();
      fence_regs<64>(d + 64);
      if (t == 0) STAMP(50);
      store(1, 0, 8);
      if (t == 0) { STAMP(51); GSTAMP(51); }
      if (t == 0) g_epoch[b * 32] = lds32(bars + B_EPOCH * 8);
      return;
    }
    asm volatile("setmaxnreg.dec.sync.aligned.u32 %0;" ::"n"(488 - 2 * GREG));
  }
  {
    int lane;
    asm volatile("mov.u32 %0, %%laneid;" : "=r"(lane));
    const int w = warp & 3, g = lane >> 2, c = lane & 3, h = wg & 1;
    const int lc = 2 * (lane & 2) + (lane & 1) + ((lane >> 2) & 2);
    const bool own = ((lane >> 2) & 1) == rank, spare = !own && lc < 2;
    const uint32_t ya = (spare ? sb + OFF_IN + 96 + lc * 2064 : sb + OFF_U + (own ? 4 * rank * U_N8 : 4 * (rank ^ 1) * U_N8 - 2 * U_CH) + lc * U_CH) + w * 128 + (lane >> 4) * 16 + h * 64;
    const uint32_t ys = spare ? 512 : U_N8;
    const uint32_t qa = sb + (8 * w + g) * 32 + 8 * c;
    float* op = P.out + (size_t)(1024 * rank + 32 * (8 * w + g) + 4 * h) * 2048 + 16 * slot + 4 * c;
    uint32_t y[2][8];
    uint2 q[2][4];
    auto load = [&](int n) {
      mbar_wait(bars + q_bar(2 * n) + 8 * h, n == 3);
      const uint32_t qs = qa + (h ? q_slot(2 * n + 1) : q_slot(2 * n));
#pragma unroll
      for (int r = 0; r < 4; r++) q[n & 1][r] = lds64(qs + r * 1024);
      if (n == 0) {
        if (h) {
#pragma unroll 1
          for (int r = 0; r < 6; r++) mbar_wait(bars + (B_IN + r) * 8, 0);
          uint32_t src = sb + OFF_U + (4 * (rank ^ 1) + w) * U_N8 + 7 * U_CH, dst = sb + OFF_U + (4 * rank + w) * U_N8 + 5 * U_CH;
          bar_sync(9, 256);
          if (elect_one()) { bulk_send(dst, src, 512, bars + (B_IN + 7) * 8, rank ^ 1); if (w == 3) mbar_arrive(bars + B_CD * 8); }
          __syncwarp();
        }
        mbar_wait(bars + (B_IN + 6) * 8, 0); mbar_wait(bars + (B_IN + 7) * 8, 0);
      }
      ldsm4t(y[n & 1], ya + n * ys); ldsm4t(y[n & 1] + 4, ya + n * ys + 32);
    };
    load(0);
    if (warp == 8 && lane == 0) mbar_arrive_cta(bars + B_ACK * 8, rank ^ 1);
    if (O_WAIT) mbar_wait(bars + (O_WAIT == 1 ? B_HP : B_HR) * 8, 1);
    uint32_t oc = clk32() + (2 * w + h) * (O_PACE / 4);
    if (warp == 8 && lane == 0) STAMP(30);
#pragma unroll
    for (int n = 0; n < 4; n++) {
      uint32_t* o = y[n & 1];
#pragma unroll
      for (int r = 0; r < 4; r++) { o[2 * r] = bmul2(o[2 * r], q[n & 1][r].x); o[2 * r + 1] = bmul2(o[2 * r + 1], q[n & 1][r].y); }
      if (n == 0 && lane == 0) mbar_arrive(bars + (B_QE + h) * 8 + (o[0] & o[2] & o[4] & o[6] & P.zero));
#pragma unroll
      for (int r = 0; r < 4; r++) {
        if (O_PACE) { while ((int)(clk32() - oc) < 0) { if (O_SLEEP) __nanosleep(O_SLEEP); } }
        oc += 2 * O_PACE;
        stg128(op + (size_t)(8 * n + r) * 2048, make_uint4(o[2 * r] << 16, o[2 * r] & 0xffff0000u, o[2 * r + 1] << 16, o[2 * r + 1] & 0xffff0000u));
        if (r == 1 && n < 3) load(n + 1);
      }
    }
    if (warp == 8 && lane == 0) STAMP(31);
    mbar_wait(bars + B_ACK * 8, 0);
  }
}

typedef CUresult (*EncodeFn)(CUtensorMap*, CUtensorMapDataType, cuuint32_t, void*, const cuuint64_t*, const cuuint64_t*, const cuuint32_t*,
                             const cuuint32_t*, CUtensorMapInterleave, CUtensorMapSwizzle, CUtensorMapL2promotion, CUtensorMapFloatOOBfill);

bool encode(EncodeFn fn, CUtensorMap* m, int rank, const void* base, const cuuint64_t* dims, const cuuint64_t* strides, const cuuint32_t* box, CUtensorMapSwizzle swz,
            CUtensorMapL2promotion promo = CU_TENSOR_MAP_L2_PROMOTION_L2_128B) {
  const cuuint32_t es[5] = {1, 1, 1, 1, 1};
  return fn(m, CU_TENSOR_MAP_DATA_TYPE_BFLOAT16, rank, const_cast<void*>(base), dims, strides, box, es, CU_TENSOR_MAP_INTERLEAVE_NONE, swz,
            promo, CU_TENSOR_MAP_FLOAT_OOB_FILL_NONE) == CUDA_SUCCESS;
}

}

extern "C" void kernel_launch(void* const* d_in, const int* in_sizes, int n_in, void* d_out, int out_size) {
  (void)in_sizes; (void)n_in; (void)out_size;
  typedef const __nv_bfloat16* In;
  const In q = (In)d_in[0], k = (In)d_in[1], v = (In)d_in[2], ssm_k = (In)d_in[4], x = (In)d_in[6], B_re = (In)d_in[9], B_im = (In)d_in[10], C_re = (In)d_in[11], C_im = (In)d_in[12];
  Params P = {};
  P.shift_k = (In)d_in[3]; P.ssm_D = (In)d_in[5]; P.lam_re = (In)d_in[7]; P.lam_im = (In)d_in[8]; P.log_dt = (In)d_in[13]; P.Dskip = (In)d_in[14];
  P.out = (float*)d_out;
  for (int cl = 0; cl < 64; cl++) P.slot[cl >> 2] |= (cl < 4 ? 4 + cl : cl < 36 ? 8 * ((cl - 4) & 7) + ((cl - 4) >> 3) : 8 * (1 + (cl - 36) % 7) + 4 + (cl - 36) / 7) << (8 * (cl & 3));
  const bool swapB = (uintptr_t)B_im < (uintptr_t)B_re;

  EncodeFn fn = nullptr;
  cudaDriverEntryPointQueryResult qr;
  cudaGetDriverEntryPoint("cuTensorMapEncodeTiled", (void**)&fn, cudaEnableDefault, &qr);
  if (!fn) return;

  CUtensorMap mX, mB, mCre, mCim, mXs, mK, mV, mQ, mS;
  bool ok = true;
  {
    const cuuint64_t dims[4] = {1024, 2, 64, 16}, str[3] = {2048, 32 * 2048, 2 * 2048};
    const cuuint32_t box[4] = {64, 2, 4, 16};
    ok &= encode(fn, &mX, 4, x, dims, str, box, CU_TENSOR_MAP_SWIZZLE_128B, (CUtensorMapL2promotion)X_PROMO);
  }
  {
    const uintptr_t lo = swapB ? (uintptr_t)B_im : (uintptr_t)B_re, hi = swapB ? (uintptr_t)B_re : (uintptr_t)B_im;
    const cuuint64_t dims[4] = {1024, 8, 2, 128}, str[3] = {2048, (cuuint64_t)(hi - lo), 8 * 2048};
    const cuuint32_t box[4] = {64, 8, 2, 4};
    ok &= encode(fn, &mB, 4, (const void*)lo, dims, str, box, CU_TENSOR_MAP_SWIZZLE_128B, (CUtensorMapL2promotion)B_PROMO);
  }
  {
    const cuuint64_t dims[5] = {1024, 2, 4, 2, 64}, str[4] = {2048, 4 * 2048, 2 * 2048, 16 * 2048};
    const cuuint32_t box[5] = {64, 2, 4, 2, 4};
    ok &= encode(fn, &mCre, 5, C_re, dims, str, box, CU_TENSOR_MAP_SWIZZLE_128B, (CUtensorMapL2promotion)C_PROMO);
    ok &= encode(fn, &mCim, 5, C_im, dims, str, box, CU_TENSOR_MAP_SWIZZLE_128B, (CUtensorMapL2promotion)C_PROMO);
  }
  {
    const cuuint64_t dims[4] = {1024, 2, 4, 256}, str[3] = {4 * 2048, 2048, 8 * 2048};
    const cuuint32_t box[4] = {64, 2, 4, 16};
    ok &= encode(fn, &mXs, 4, x, dims, str, box, CU_TENSOR_MAP_SWIZZLE_128B);
  }
  {
    const cuuint64_t dims[3] = {1024, 64, 32}, str[2] = {32 * 2048, 2048};
    const cuuint32_t box[3] = {16, 32, 4};
    ok &= encode(fn, &mQ, 3, q, dims, str, box, CU_TENSOR_MAP_SWIZZLE_NONE, (CUtensorMapL2promotion)Q_PROMO);
    ok &= encode(fn, &mK, 3, k, dims, str, box, CU_TENSOR_MAP_SWIZZLE_32B, (CUtensorMapL2promotion)KV_PROMO);
    ok &= encode(fn, &mV, 3, v, dims, str, box, CU_TENSOR_MAP_SWIZZLE_32B, (CUtensorMapL2promotion)KV_PROMO);
  }
  {
    const cuuint64_t dims[2] = {32, 65536}, str[1] = {64};
    const cuuint32_t box[2] = {32, 64};
    ok &= encode(fn, &mS, 2, ssm_k, dims, str, box, CU_TENSOR_MAP_SWIZZLE_64B, (CUtensorMapL2promotion)S_PROMO);
  }
  if (!ok) return;
  auto kern = swapB ? fused_kernel<1> : fused_kernel<0>;
  cudaFuncSetAttribute(kern, cudaFuncAttributeMaxDynamicSharedMemorySize, SMEM_BYTES);
  kern<<<NCTA, 512, SMEM_BYTES, cudaStreamPerThread>>>(P, mX, mB, mCre, mCim, mXs, mK, mV, mQ, mS);
}
```

```cpp
#include <cuda_runtime.h>
#include <cuda_bf16.h>
#include <cuda.h>
#include <stdint.h>
#include <type_traits>

#define PROFILE 0

namespace {

constexpr int D_DIM = 1024;
constexpr int NCTA = 128;

constexpr int STAGES = 5, STAGE_BYTES = 32768;
constexpr int OFF_RING = 0;
constexpr int OFF_F1 = STAGES * STAGE_BYTES, OFF_F2 = OFF_F1 + 4096, OFF_K = OFF_F2 + 2048, OFF_VP = OFF_K + 8192, OFF_Q = OFF_VP + 4096, OFF_IN = OFF_Q + 8192;
constexpr int OFF_KV = OFF_K;
constexpr int U_CH = 528, U_N8 = 8 * U_CH, OFF_U = OFF_IN + U_N8;
constexpr int OFF_COEF = OFF_U + 8 * U_N8;
constexpr int OFF_DS = OFF_COEF + 2048, OFF_D = OFF_DS + 512;
constexpr int OFF_BAR = OFF_D + 64;
constexpr int OFF_PROF = OFF_BAR + 512;
constexpr int SMEM_BYTES = OFF_PROF + 512;
static_assert(SMEM_BYTES <= 232448 && OFF_K % 1024 == 0 && (OFF_U + 3 * U_N8) % 512 == 0 && (4 * U_N8) % 512 == 0, "smem map");
constexpr int B_FULL = 0, B_XI = 5, B_HR = 6, B_HP = 7, B_KVF = 8, B_KF = 11, B_KE = 13, B_QF = 15, B_IN = 19, B_UF = 27, B_Y = 31, B_CD = 35, B_ACK = 36,
              B_EMPTY = 38, B_PEER = 43, B_COEF = 48, B_KVE = 49, B_QE = 52, B_EPOCH = 56;
__host__ __device__ constexpr int q_slot(int i) { return ((i & 2) ? OFF_K : OFF_Q) + 4096 * (i & 1); }
__host__ __device__ constexpr int q_bar(int i) { return 8 * (((i & 2) ? B_KF : B_QF) + (i & 1)); }

#define QD1 8
#define QD2 2
#define QD3 8
#define QSW 16
#define HEAD 3
#define ST_T0 200
#define ST_DELAY 300
#define XPOS 28
#define K_T0 800
#define KV_T0 1500
#define KV_DT 500
#define KV_DV 100
#define O_PACE 170
#define H_PACE 0
#define CARRY_WAIT 600
#define POLL_NS 30
#define GREEDY 0
#define P2_SPLIT 0
#define TAILB 5
#define GREG 176
#define O_WAIT 2
#define COEF_T0 2500
#define O_EVERY 1
#define X_P1 32
#define X_P2 8
#define X_NOXI 0
#define RELPOS 0
#define O_UNR 4
constexpr int O_UNROLL = O_UNR;
#define C_AT 0
#define C_AT2 1
#define T_FENCE 0
#define T_ST 2
#define X_PROMO 2
#define B_PROMO 2
#define C_PROMO 2
#define KV_PROMO 2
#define Q_PROMO 2
#define S_PROMO 2
#define SHAKE 0
#define PRE_S 0
#define PRE_G 2
#define POW2 0
#define O_SLEEP 20
#define CFM 0x40f1
constexpr int SPIN_LIMIT = 1 << 14;

struct Params {
  unsigned slot[16];
  unsigned zero;
  const __nv_bfloat16 *shift_k, *ssm_D, *lam_re, *lam_im, *log_dt, *Dskip;
  float* out;
};

__device__ __align__(1024) uint4 g_h[16 * 32 * 1024];
__device__ __align__(128) uint2 g_carry[32 * 16 * 32];
__device__ unsigned g_flagH[2 * 16 * 32];
__device__ unsigned g_epoch[NCTA * 32];
#define STAMP(i)
#define GSTAMP(i)
#define TSTAMP(k, n)
#define KSTAMP(k, n)

__device__ __forceinline__ uint64_t make_desc(uint32_t addr, uint32_t lbo, uint32_t sbo, uint32_t swz) {
  return (uint64_t)((addr & 0x3FFFF) >> 4) | ((uint64_t)(lbo >> 4) << 16) | ((uint64_t)(sbo >> 4) << 32) | ((uint64_t)swz << 62);
}
__device__ __forceinline__ void wg_fence() { asm volatile("wgmma.fence.sync.aligned;" ::: "memory"); }
__device__ __forceinline__ void wg_commit() { asm volatile("wgmma.commit_group.sync.aligned;" ::: "memory"); }
template <int N> __device__ __forceinline__ void wg_wait() { asm volatile("wgmma.wait_group.sync.aligned %0;" ::"n"(N) : "memory"); }
__device__ __forceinline__ void mbar_init(uint32_t bar, int cnt) { asm volatile("mbarrier.init.shared::cta.b64 [%0], %1;" ::"r"(bar), "r"(cnt) : "memory"); }
__device__ __forceinline__ void mbar_expect(uint32_t bar, uint32_t bytes) { asm volatile("mbarrier.arrive.expect_tx.shared::cta.b64 _, [%0], %1;" ::"r"(bar), "r"(bytes) : "memory"); }
__device__ __forceinline__ void mbar_wait(uint32_t bar, uint32_t parity) {
  uint32_t ok; int n = 0;
  do {
    asm volatile("{\n.reg .pred p;\nmbarrier.try_wait.parity.shared::cta.b64 p, [%1], %2;\nselp.u32 %0, 1, 0, p;\n}\n" : "=r"(ok) : "r"(bar), "r"(parity) : "memory");
    if (++n > SPIN_LIMIT) break;
  } while (!ok);
}
__device__ __forceinline__ void mbar_arrive(uint32_t bar) { asm volatile("mbarrier.arrive.shared::cta.b64 _, [%0];" ::"r"(bar) : "memory"); }
__device__ __forceinline__ void mbar_arrive_cta(uint32_t bar, uint32_t cta) {
  asm volatile("{\n.reg .b32 ra;\nmapa.shared::cluster.u32 ra, %0, %1;\nmbarrier.arrive.shared::cluster.b64 _, [ra];\n}\n" ::"r"(bar), "r"(cta) : "memory");
}
__device__ __forceinline__ bool elect_one() {
  uint32_t p;
  asm volatile("{\n.reg .pred P;\nelect.sync _|P, 0xffffffff;\nselp.u32 %0, 1, 0, P;\n}\n" : "=r"(p));
  return p != 0;
}
__device__ __forceinline__ void bar_sync(int id, int n) { asm volatile("bar.sync %0, %1;" ::"r"(id), "r"(n) : "memory"); }
#define TMA_LD(dim) "cp.async.bulk.tensor." dim ".shared::cluster.global.mbarrier::complete_tx::bytes"
__device__ __forceinline__ void tma2d(uint32_t dst, const CUtensorMap* m, int c0, int c1, uint32_t bar) {
  asm volatile(TMA_LD("2d") " [%0], [%1, {%3, %4}], [%2];" ::"r"(dst), "l"(m), "r"(bar), "r"(c0), "r"(c1) : "memory");
}
__device__ __forceinline__ void tma3d(uint32_t dst, const CUtensorMap* m, int c0, int c1, int c2, uint32_t bar) {
  asm volatile(TMA_LD("3d") " [%0], [%1, {%3, %4, %5}], [%2];" ::"r"(dst), "l"(m), "r"(bar), "r"(c0), "r"(c1), "r"(c2) : "memory");
}
__device__ __forceinline__ void tma4d(uint32_t dst, const CUtensorMap* m, int c0, int c1, int c2, int c3, uint32_t bar) {
  asm volatile(TMA_LD("4d") " [%0], [%1, {%3, %4, %5, %6}], [%2];" ::"r"(dst), "l"(m), "r"(bar), "r"(c0), "r"(c1), "r"(c2), "r"(c3) : "memory");
}
__device__ __forceinline__ void tma4d_mc(uint32_t dst, const CUtensorMap* m, int c0, int c1, int c2, int c3, uint32_t bar) {
  asm volatile(TMA_LD("4d") ".multicast::cluster [%0], [%1, {%3, %4, %5, %6}], [%2], %7;" ::"r"(dst), "l"(m), "r"(bar), "r"(c0), "r"(c1), "r"(c2), "r"(c3), "h"((uint16_t)3) : "memory");
}
__device__ __forceinline__ void tma5d_mc(uint32_t dst, const CUtensorMap* m, int c0, int c1, int c2, int c3, int c4, uint32_t bar) {
  asm volatile(TMA_LD("5d") ".multicast::cluster [%0], [%1, {%3, %4, %5, %6, %7}], [%2], %8;" ::"r"(dst), "l"(m), "r"(bar), "r"(c0), "r"(c1), "r"(c2), "r"(c3), "r"(c4), "h"((uint16_t)3) : "memory");
}
__device__ __forceinline__ void bulk_load(uint32_t dst, const void* src, uint32_t bytes, uint32_t bar) {
  asm volatile("cp.async.bulk.shared::cluster.global.mbarrier::complete_tx::bytes [%0], [%1], %2, [%3];" ::"r"(dst), "l"(src), "r"(bytes), "r"(bar) : "memory");
}
__device__ __forceinline__ void bulk_send(uint32_t dst, uint32_t src, uint32_t bytes, uint32_t bar, uint32_t cta) {
  asm volatile("{\n.reg .b32 rd, rb;\nmapa.shared::cluster.u32 rd, %0, %3;\nmapa.shared::cluster.u32 rb, %2, %3;\n"
               "cp.async.bulk.shared::cluster.shared::cta.mbarrier::complete_tx::bytes [rd], [%1], %4, [rb];\n}\n"
               ::"r"(dst), "r"(src), "r"(bar), "r"(cta), "r"(bytes) : "memory");
}
__device__ __forceinline__ void fence_proxy_async_smem() { asm volatile("fence.proxy.async.shared::cta;" ::: "memory"); }
__device__ __forceinline__ void fence_proxy_async_global() { asm volatile("fence.proxy.async.global;" ::: "memory"); }
__device__ __forceinline__ void red_release(unsigned* p, unsigned v) { asm volatile("red.release.gpu.global.add.u32 [%0], %1;" ::"l"(p), "r"(v) : "memory"); }
__device__ __forceinline__ uint32_t clk32() { uint32_t c; asm volatile("mov.u32 %0, %%clock;" : "=r"(c)::"memory"); return c; }
__device__ __forceinline__ void wait_until(uint32_t t0, uint32_t dt) { while (clk32() - t0 < dt) __nanosleep(32); }
__device__ __forceinline__ void spin_until(uint32_t t0, uint32_t dt) { while (clk32() - t0 < dt) {} }
__device__ __forceinline__ void prefetch_map(const CUtensorMap* m) { asm volatile("prefetch.tensormap [%0];" ::"l"(m) : "memory"); }
__device__ __forceinline__ void prefetch_line(const void* p) { asm volatile("prefetch.global.L2 [%0];" ::"l"(p) : "memory"); }
__device__ __forceinline__ unsigned ld_acquire(const unsigned* p) { unsigned v; asm volatile("ld.acquire.gpu.global.u32 %0, [%1];" : "=r"(v) : "l"(p) : "memory"); return v; }
__device__ __forceinline__ unsigned ld_relaxed(const unsigned* p) { unsigned v; asm volatile("ld.relaxed.gpu.global.u32 %0, [%1];" : "=r"(v) : "l"(p) : "memory"); return v; }
__device__ __forceinline__ uint32_t lds32(uint32_t a) { uint32_t v; asm volatile("ld.shared.u32 %0, [%1];" : "=r"(v) : "r"(a)); return v; }
__device__ __forceinline__ uint2 lds64(uint32_t a) { uint2 v; asm volatile("ld.shared.v2.u32 {%0,%1}, [%2];" : "=r"(v.x), "=r"(v.y) : "r"(a) : "memory"); return v; }
__device__ __forceinline__ uint4 lds128(uint32_t a) { uint4 v; asm volatile("ld.shared.v4.u32 {%0,%1,%2,%3}, [%4];" : "=r"(v.x), "=r"(v.y), "=r"(v.z), "=r"(v.w) : "r"(a) : "memory"); return v; }
__device__ __forceinline__ void sts32(uint32_t a, uint32_t v) { asm volatile("st.shared.u32 [%0], %1;" ::"r"(a), "r"(v) : "memory"); }
__device__ __forceinline__ void sts128(uint32_t a, uint4 v) { asm volatile("st.shared.v4.u32 [%0], {%1,%2,%3,%4};" ::"r"(a), "r"(v.x), "r"(v.y), "r"(v.z), "r"(v.w) : "memory"); }
__device__ __forceinline__ void ldsm4(uint32_t* r, uint32_t a) { asm volatile("ldmatrix.sync.aligned.m8n8.x4.shared.b16 {%0,%1,%2,%3}, [%4];" : "=r"(r[0]), "=r"(r[1]), "=r"(r[2]), "=r"(r[3]) : "r"(a) : "memory"); }
__device__ __forceinline__ void ldsm4t(uint32_t* r, uint32_t a) { asm volatile("ldmatrix.sync.aligned.m8n8.x4.trans.shared.b16 {%0,%1,%2,%3}, [%4];" : "=r"(r[0]), "=r"(r[1]), "=r"(r[2]), "=r"(r[3]) : "r"(a) : "memory"); }
__device__ __forceinline__ void stsm4t(uint32_t a, uint32_t r0, uint32_t r1, uint32_t r2, uint32_t r3) {
  asm volatile("stmatrix.sync.aligned.m8n8.x4.trans.shared.b16 [%0], {%1,%2,%3,%4};" ::"r"(a), "r"(r0), "r"(r1), "r"(r2), "r"(r3) : "memory");
}
__device__ __forceinline__ uint4 ldg128_nc(const void* p) { uint4 v; asm volatile("ld.global.nc.L1::no_allocate.v4.u32 {%0,%1,%2,%3}, [%4];" : "=r"(v.x), "=r"(v.y), "=r"(v.z), "=r"(v.w) : "l"(p)); return v; }
__device__ __forceinline__ void stg128(void* p, uint4 v) { asm volatile("st.global.L1::no_allocate.v4.u32 [%0], {%1,%2,%3,%4};" ::"l"(p), "r"(v.x), "r"(v.y), "r"(v.z), "r"(v.w) : "memory"); }
__device__ __forceinline__ uint32_t pack_bf16(float lo, float hi) { uint32_t r; asm("cvt.rn.bf16x2.f32 %0, %1, %2;" : "=r"(r) : "f"(hi), "f"(lo)); return r; }
__device__ __forceinline__ uint32_t bmul2(uint32_t a, uint32_t b) { uint32_t r; asm("mul.rn.bf16x2 %0, %1, %2;" : "=r"(r) : "r"(a), "r"(b)); return r; }
__device__ __forceinline__ uint32_t bfma2(uint32_t a, uint32_t b, uint32_t c) { uint32_t r; asm("fma.rn.bf16x2 %0, %1, %2, %3;" : "=r"(r) : "r"(a), "r"(b), "r"(c)); return r; }
__device__ __forceinline__ uint32_t blo2(uint32_t a) { uint32_t r; asm("{\n.reg .b16 l, h;\nmov.b32 {l, h}, %1;\nmov.b32 %0, {l, l};\n}" : "=r"(r) : "r"(a)); return r; }
__device__ __forceinline__ float bf2f(__nv_bfloat16 v) { return __bfloat162float(v); }

#define R8(d, o) "+f"(d[o]), "+f"(d[o + 1]), "+f"(d[o + 2]), "+f"(d[o + 3]), "+f"(d[o + 4]), "+f"(d[o + 5]), "+f"(d[o + 6]), "+f"(d[o + 7])
#define R16(d, o) R8(d, o), R8(d, o + 8)
#define R64(d, o) R16(d, o), R16(d, o + 16), R16(d, o + 32), R16(d, o + 48)
template <int TA> __device__ __forceinline__ void wgmma_n128(float* d, uint64_t da, uint64_t db, int scale_d) {
  asm volatile("{\n.reg .pred p;\nsetp.ne.b32 p, %66, 0;\n"
    "wgmma.mma_async.sync.aligned.m64n128k16.f32.bf16.bf16 {"
    "%0,%1,%2,%3,%4,%5,%6,%7,%8,%9,%10,%11,%12,%13,%14,%15,%16,%17,%18,%19,%20,%21,%22,%23,%24,%25,%26,%27,%28,%29,%30,%31,"
    "%32,%33,%34,%35,%36,%37,%38,%39,%40,%41,%42,%43,%44,%45,%46,%47,%48,%49,%50,%51,%52,%53,%54,%55,%56,%57,%58,%59,%60,%61,%62,%63"
    "}, %64, %65, p, 1, 1, %67, 0;\n}\n"
    : R64(d, 0)
    : "l"(da), "l"(db), "r"(scale_d), "n"(TA));
}
template <int N> __device__ __forceinline__ void fence_regs(float* d) {
#pragma unroll
  for (int i = 0; i < N; i++) asm volatile("" : "+f"(d[i])::"memory");
}
#define PMFENCE() asm volatile("pmevent 0;" ::: "memory")
__device__ __forceinline__ void cmul(float ar, float ai, float br, float bi, float& cr, float& ci) {
  cr = ar * br - ai * bi; ci = ar * bi + ai * br;
}
__device__ __forceinline__ void csq(float& r, float& i) { const float x = fmaf(r, r, -i * i), y = (r + r) * i; r = x; i = y; }

#define W8(d, o) "=f"(d[o]), "=f"(d[o + 1]), "=f"(d[o + 2]), "=f"(d[o + 3]), "=f"(d[o + 4]), "=f"(d[o + 5]), "=f"(d[o + 6]), "=f"(d[o + 7])
#define L16 "{%0,%1,%2,%3,%4,%5,%6,%7,%8,%9,%10,%11,%12,%13,%14,%15}"
#define L32 "{%0,%1,%2,%3,%4,%5,%6,%7,%8,%9,%10,%11,%12,%13,%14,%15,%16,%17,%18,%19,%20,%21,%22,%23,%24,%25,%26,%27,%28,%29,%30,%31}"
template <int ACC, int TB> __device__ __forceinline__ void rs_n32(float* d, const uint32_t* a, uint64_t db) {
  if constexpr (ACC) asm volatile("wgmma.mma_async.sync.aligned.m64n32k16.f32.bf16.bf16 " L16 ", {%16,%17,%18,%19}, %20, 1, 1, 1, %21;" : R16(d, 0) : "r"(a[0]), "r"(a[1]), "r"(a[2]), "r"(a[3]), "l"(db), "n"(TB));
  else asm volatile("wgmma.mma_async.sync.aligned.m64n32k16.f32.bf16.bf16 " L16 ", {%16,%17,%18,%19}, %20, 0, 1, 1, %21;" : W8(d, 0), W8(d, 8) : "r"(a[0]), "r"(a[1]), "r"(a[2]), "r"(a[3]), "l"(db), "n"(TB));
}
template <int ACC, int TB> __device__ __forceinline__ void ss_n64(float* d, uint64_t da, uint64_t db) {
  if constexpr (ACC) asm volatile("wgmma.mma_async.sync.aligned.m64n64k16.f32.bf16.bf16 " L32 ", %32, %33, 1, 1, 1, 0, %34;" : R16(d, 0), R16(d, 16) : "l"(da), "l"(db), "n"(TB));
  else asm volatile("wgmma.mma_async.sync.aligned.m64n64k16.f32.bf16.bf16 " L32 ", %32, %33, 0, 1, 1, 0, %34;" : W8(d, 0), W8(d, 8), W8(d, 16), W8(d, 24) : "l"(da), "l"(db), "n"(TB));
}
template <int ACC> __device__ __forceinline__ void ss_n32_tt(float* d, uint64_t da, uint64_t db) {
  if constexpr (ACC) asm volatile("wgmma.mma_async.sync.aligned.m64n32k16.f32.bf16.bf16 " L16 ", %16, %17, 1, 1, 1, 1, 1;" : R16(d, 0) : "l"(da), "l"(db));
  else asm volatile("wgmma.mma_async.sync.aligned.m64n32k16.f32.bf16.bf16 " L16 ", %16, %17, 0, 1, 1, 1, 1;" : W8(d, 0), W8(d, 8) : "l"(da), "l"(db));
}
__device__ __forceinline__ void stsm4(uint32_t a, uint32_t r0, uint32_t r1, uint32_t r2, uint32_t r3) {
  asm volatile("stmatrix.sync.aligned.m8n8.x4.shared.b16 [%0], {%1,%2,%3,%4};" ::"r"(a), "r"(r0), "r"(r1), "r"(r2), "r"(r3) : "memory");
}
template <int N> __device__ __forceinline__ void fence_u32(uint32_t* d) {
#pragma unroll
  for (int i = 0; i < N; i++) asm volatile("" : "+r"(d[i])::"memory");
}
__device__ __forceinline__ void pack32(uint32_t* f, const float* z) {
#pragma unroll
  for (int i = 0; i < 16; i++) f[i] = pack_bf16(z[2 * i], z[2 * i + 1]);
}
template <int INV> __device__ __forceinline__ void twiddle(uint32_t* f, const uint32_t* tp, const uint32_t* ts) {
#pragma unroll
  for (int i = 0; i < 8; i++) {
    uint32_t x = f[2 * i + INV], y = f[2 * i + 1 - INV];
    x = bfma2(tp[i & 3], y, x); y = bfma2(ts[i & 3], x, y); x = bfma2(tp[i & 3], y, x);
    f[2 * i + INV] = x; f[2 * i + 1 - INV] = y;
  }
}
__device__ __forceinline__ uint32_t bfnma2(uint32_t a, uint32_t b, uint32_t c) { uint32_t r; asm("{\n.reg .b32 t;\nmul.bf16x2 t, %1, %2;\nsub.bf16x2 %0, %3, t;\n}" : "=r"(r) : "r"(a), "r"(b), "r"(c)); return r; }
__device__ __forceinline__ uint32_t bfms2(uint32_t a, uint32_t b, uint32_t c) { uint32_t r; asm("{\n.reg .b32 t;\nmul.bf16x2 t, %1, %2;\nsub.bf16x2 %0, t, %3;\n}" : "=r"(r) : "r"(a), "r"(b), "r"(c)); return r; }
template <int ADD> __device__ __forceinline__ void bimac(uint32_t* o, const uint32_t* a, const uint32_t* b, const uint32_t* c) {
#pragma unroll
  for (int J = 0; J < 2; J++) {
    const uint32_t Pr = a[2 * J], Pi = a[2 * J + 1], Qr = a[2 * J + 4], Qi = a[2 * J + 5], pr = b[2 * J], pi = b[2 * J + 1], qr = b[2 * J + 4], qi = b[2 * J + 5];
    uint32_t x0, x1, x2, x3;
    if (ADD == 0) { x0 = bmul2(Pr, pr); x1 = bmul2(Pr, pi); x2 = bmul2(Pr, qr); x3 = bmul2(Pr, qi); }
    if (ADD == 1) { x0 = bfma2(Pr, pr, c[2 * J]); x1 = bfma2(Pr, pi, c[2 * J + 1]); x2 = bfma2(Pr, qr, c[2 * J + 4]); x3 = bfma2(Pr, qi, c[2 * J + 5]); }
    if (ADD == 2) { x0 = bfma2(Pr, pr, c[2 * J + 1]); x1 = bfms2(Pr, pi, c[2 * J]); x2 = bfma2(Pr, qr, c[2 * J + 5]); x3 = bfms2(Pr, qi, c[2 * J + 4]); }
    x0 = bfnma2(Pi, pi, x0); x1 = bfma2(Pi, pr, x1); x2 = bfnma2(Pi, qi, x2); x3 = bfma2(Pi, qr, x3);
    x0 = bfnma2(Qr, qr, x0); x1 = bfnma2(Qr, qi, x1); x2 = bfma2(Qr, pr, x2); x3 = bfma2(Qr, pi, x3);
    x0 = bfma2(Qi, qi, x0); x1 = bfnma2(Qi, qr, x1); x2 = bfnma2(Qi, pi, x2); x3 = bfma2(Qi, pr, x3);
    o[2 * J] = x0; o[2 * J + 1] = x1; o[2 * J + 4] = x2; o[2 * J + 5] = x3;
  }
}
__device__ __forceinline__ void sincos8k(int n, float& s, float& c) {
  const float x = (float)((n << 19) >> 19) * (6.283185307179586f / 8192.f);
  s = __sinf(x); c = __cosf(x);
}
__device__ __forceinline__ void fft_tables(uint32_t f1a, uint32_t f2a, int w, int lane, uint32_t* tp, uint32_t* ts, float& d0r, float& d0i) {
  const int c = lane & 3, f1 = 8 * w + (lane >> 2);
#pragma unroll 1
  for (int J = 3; J >= 0; J--) {
    const int a = 8 * J + 2 * c;
    float s0, c0, s1, c1;
    sincos8k(64 * (4 * f1 + 1) * a + 31 * (4 * f1 - 63), d0i, d0r); sincos8k(64 * (4 * f1 + 1) * (a + 1) + 31 * (4 * f1 - 63), s1, c1);
    d0r *= 0.125f; d0i *= 0.125f;
    sts32(f1a + w * 1024 + J * 128 + lane * 4, pack_bf16(d0r, 0.125f * c1)); sts32(f1a + w * 1024 + 512 + J * 128 + lane * 4, pack_bf16(d0i, 0.125f * s1));
    sincos8k(128 * (2 * (a & 15) + 1) * f1 - 128 * (a & 16), s0, c0); sincos8k(128 * (2 * (a & 15) + 3) * f1 - 128 * (a & 16), s1, c1);
    sts32(f2a + w * 512 + J * 128 + lane * 4, pack_bf16(c0, c1));
    sincos8k((4 * f1 - 63) * (2 * a - 31), s0, c0); sincos8k((4 * f1 - 63) * (2 * a - 29), s1, c1);
#pragma unroll
    for (int i = 3; i > 0; i--) { ts[i] = ts[i - 1]; tp[i] = tp[i - 1]; }
    ts[0] = pack_bf16(s0, s1); tp[0] = pack_bf16(-__fdividef(s0, 1.f + c0), -__fdividef(s1, 1.f + c1));
  }
  if (c != 0) d0r = d0i = 0.f;
}

template <int SWAPB>
__global__ void __cluster_dims__(2, 1, 1) __launch_bounds__(512, 1)
fused_kernel(const __grid_constant__ Params P, const __grid_constant__ CUtensorMap mX, const __grid_constant__ CUtensorMap mB,
             const __grid_constant__ CUtensorMap mCre, const __grid_constant__ CUtensorMap mCim, const __grid_constant__ CUtensorMap mXs,
             const __grid_constant__ CUtensorMap mK, const __grid_constant__ CUtensorMap mV, const __grid_constant__ CUtensorMap mQ, const __grid_constant__ CUtensorMap mS,
             const __grid_constant__ CUtensorMap mO) {
  extern __shared__ __align__(1024) uint8_t smem_raw[];
  const uint32_t sb = (uint32_t)__cvta_generic_to_shared(smem_raw);
  const uint32_t bars = sb + OFF_BAR;
  const int slot = (P.slot[blockIdx.x >> 3] >> (4 * (blockIdx.x & 6))) & 63, rank = blockIdx.x & 1;
  const int j = slot & 7, tc = 2 * (slot >> 3) + rank, b = 2 * slot + rank;
  const int tid = threadIdx.x;
  const int warp = __shfl_sync(0xffffffffu, tid >> 5, 0);
  const int wg = warp >> 2;
  const uint32_t c_start = clk32();
  auto kblock = [&](int n) { return ((n & 14) == 0 || (n & 14) == 2 * j ? n ^ (2 * j) : n) & 31; };
  auto send_y = [&](int r, int n0 = 0, int n1 = 4) {
    const uint32_t src = sb + OFF_U + 4 * (rank ^ 1) * U_N8 + r * U_CH, dst = r >= 2 ? sb + OFF_U + 4 * rank * U_N8 + (r - 2) * U_CH : sb + OFF_IN + 96 + r * 2064;
#pragma unroll 1
    for (int n = n0; n < n1; n++) bulk_send(dst + n * (r >= 2 ? U_N8 : 512), src + n * U_N8, 512, bars + (B_IN + r) * 8, rank ^ 1);
  };
  auto head = [&](int n) {
    const uint32_t fb = bars + (B_FULL + n) * 8, dst = sb + OFF_RING + n * STAGE_BYTES;
    mbar_expect(fb, STAGE_BYTES);
    tma4d(dst + 16384, &mX, 64 * n, 0, 4 * tc, 0, fb);
    tma4d(dst, &mB, 64 * n, 0, 0, 8 * j, fb);
    tma4d(dst + 8192, &mB, 64 * n, 0, 0, 8 * j + 4, fb);
  };
  if (warp == 0 && elect_one()) {
    STAMP(0); GSTAMP(0);
#pragma unroll
    for (int s = 0; s < STAGES; s++) mbar_init(bars + (B_FULL + s) * 8, 1);
    head(0);
    STAMP(1);
    asm volatile("fence.mbarrier_init.release.cluster;" ::: "memory");
  }
  if (wg == 3 && elect_one()) {
    if (warp < 15) {
#pragma unroll
      for (int s = 0; s < 11; s++) mbar_init(bars + 8 * B_XI + (warp & 3) * 88 + 8 * s, 1);
    } else {
#pragma unroll
      for (int s = B_EMPTY; s < B_QE + 4; s++) mbar_init(bars + 8 * s, s < B_PEER ? (SHAKE ? 1 : 2) : s < B_COEF ? (SHAKE == 2 ? 2 : 1) : s == B_COEF ? 128 : 4);
    }
    asm volatile("fence.mbarrier_init.release.cluster;" ::: "memory");
  }
  __syncwarp();
  asm volatile("barrier.cluster.arrive.relaxed.aligned;" ::: "memory");
  if (warp == 0 && elect_one()) {
#pragma unroll 1
    for (int n = 1; n < HEAD; n++) { spin_until(c_start, ST_T0 + n * ST_DELAY); head(n); }
  }
  __syncwarp();
#define CLUSTER_WAIT() asm volatile("barrier.cluster.wait.aligned;" ::: "memory")

  if (wg == 3) {
    asm volatile("setmaxnreg.dec.sync.aligned.u32 24;");
    CLUSTER_WAIT();
    if (warp < 14) {
      if (elect_one()) {
        uint32_t so = 8 * (HEAD % STAGES), ph = HEAD < STAGES;
        auto step = [&](auto issue) {
          mbar_wait(bars + (SHAKE == 2 && warp == 12 ? B_PEER : B_EMPTY) * 8 + so, ph);
          issue(sb + OFF_RING + (so << 12), bars + B_FULL * 8 + so);
          so += 8;
          if (so == 8 * STAGES) { so = 0; ph ^= 1; }
        };
        if (warp == 12) {
          uint64_t pp = 0;
          auto shake = [&](uint32_t fb) {
            if (SHAKE == 1) mbar_arrive_cta(bars + B_PEER * 8 + so, rank ^ 1);
            mbar_expect(fb, STAGE_BYTES);
            if (SHAKE == 1) {
              mbar_wait(bars + B_PEER * 8 + so, (uint32_t)(pp >> so) & 1);
              pp ^= 1ull << so;
            }
          };
          auto g1 = [&](int n0, int n1, int grp) {
#pragma unroll 1
            for (int n = n0; n < n1; n++) step([&](uint32_t dst, uint32_t fb) { shake(fb); tma4d_mc(dst + rank * 8192, &mB, n * 64, 0, 0, grp + 4 * rank, fb); });
          };
#pragma unroll 1
          for (int n = HEAD; n < STAGES; n++) { spin_until(c_start, ST_T0 + n * ST_DELAY); g1(n, n + 1, 8 * j); }
          g1(STAGES, 16, 8 * j);
          g1(0, XPOS - 16, 8 * j + 64);
          step([&](uint32_t dst, uint32_t fb) { mbar_expect(fb, STAGE_BYTES); tma4d(dst, &mXs, 128 * j, 0, 0, 16 * tc, fb); mbar_arrive(bars + B_XI * 8); });
          g1(XPOS - 16, 16, 8 * j + 64);
#pragma unroll 1
          for (int n = 0; n < 32; n += 2) {
            const int col = kblock(n) * 32;
#pragma unroll
            for (int part = 0; part < 2; part++)
              step([&](uint32_t dst, uint32_t fb) { shake(fb); tma5d_mc(dst + rank * 8192, part ? &mCim : &mCre, col, 0, 0, 0, 8 * j + 4 * rank, fb); });
          }
        } else {
          auto g1 = [&](int n0, int n1, int nb) {
#pragma unroll 1
            for (int n = n0; n < n1; n++) step([&](uint32_t dst, uint32_t fb) { tma4d(dst + 16384, &mX, n * 64, 0, 4 * tc, 0, fb); TSTAMP(1, n + nb); });
          };
          auto g2 = [&](int n0, int n1) {
#pragma unroll 1
            for (int n = n0; n < n1; n++) step([&](uint32_t dst, uint32_t fb) { bulk_load(dst + 16384, g_h + (32 * tc + kblock(n)) * 1024, 16384, fb); TSTAMP(1, n + 32); });
          };
#pragma unroll 1
          for (int n = HEAD; n < STAGES; n++) { spin_until(c_start, ST_T0 + n * ST_DELAY); g1(n, n + 1, 0); }
          g1(STAGES, 16, 0);
          g1(0, XPOS - 16, 16);
          step([&](uint32_t dst, uint32_t fb) { tma4d(dst + 16384, &mXs, 128 * j + 64, 0, 0, 16 * tc, fb); });
          g1(XPOS - 16, 16, 16);
#pragma unroll 1
          for (int v = 0; v < 2; v++) {
            STAMP(4 + v);
            mbar_wait(bars + B_HP * 8, v);
            fence_proxy_async_global();
            STAMP(6 + v);
            g2(16 * v, 16 * v + 2);
            mbar_wait(bars + B_HR * 8, v);
            fence_proxy_async_global();
            g2(16 * v + 2, 16 * v + 16);
          }
        }
      }
    } else if (warp == 15) {
      mbar_wait(bars + B_COEF * 8, 0);
      const unsigned epoch = lds32(bars + B_EPOCH * 8);
#pragma unroll 1
      for (int v = 0; v < 2; v++) {
        unsigned* fp = &g_flagH[(16 * v + tc) * 32];
        bar_sync(4 + v, 160);
        if (elect_one()) {
          red_release(fp, 1);
          mbar_arrive(bars + B_HP * 8);
          STAMP(16 + 10 * v);
          int it = 0;
          while (ld_acquire(fp) != 8 * epoch && ++it < (SPIN_LIMIT << 4)) __nanosleep(POLL_NS);
          STAMP(2 + v);
          mbar_arrive(bars + B_HR * 8);
        }
        __syncwarp();
      }
    } else if (elect_one()) {
      const int ch0 = 16 * slot;
      auto load_k = [&](int s, uint32_t dst) { const uint32_t fb = bars + (B_KF + (s & 1)) * 8; mbar_expect(fb, 4096); tma2d(dst, &mS, 0, 64 * (8 * b + s), fb); };
      auto load_q = [&](int i) { mbar_expect(bars + q_bar(i), 4096); tma3d(sb + q_slot(i), &mQ, ch0, 32 * rank, 4 * i, bars + q_bar(i)); };
      prefetch_map(&mS); prefetch_map(&mK); prefetch_map(&mV);
      wait_until(c_start, K_T0);
      load_k(0, sb + OFF_U + (4 * rank + 3) * U_N8); load_k(1, sb + OFF_U + (4 * rank + 3) * U_N8 - 4096);
      {
        uint32_t so = 16, ph = 1;
#pragma unroll 1
        for (int e = 0; e < 9; e++) {
          const uint32_t fb = bars + B_KVF * 8 + so, dst = sb + OFF_KV + (so << 10);
          wait_until(c_start, KV_T0 + (e ? 2 * e - 1 : 0) * KV_DT);
          mbar_wait(bars + B_KVE * 8 + so, ph);
          const uint32_t c1 = clk32();
          mbar_expect(fb, e ? 8192 : 4096);
          if (e > 0) KSTAMP(1, e - 1);
          tma3d(dst, &mK, ch0, 32 * rank - (e == 0), (4 * e - 4) & 31, fb);
          if (e > 0) { wait_until(c1, KV_DV); tma3d(dst + 4096, &mV, ch0, 32 * rank, 4 * e - 4, fb); }
          so += 8;
          if (so == 24) so = 0;
          if (so == 16) ph ^= 1;
        }
      }
      prefetch_map(&mCre); prefetch_map(&mCim); prefetch_map(&mXs); prefetch_map(&mQ); prefetch_map(&mO);
      mbar_wait(bars + B_KVE * 8, 0);
      load_k(2, sb + OFF_K); load_k(3, sb + OFF_K + 4096);
      mbar_wait(bars + (B_UF + 3) * 8, 0);
#pragma unroll 1
      for (int ch = 0; ch < 8; ch++) {
        if (ch > 0) {
          mbar_wait(bars + (B_Y + (ch & 3)) * 8, ch >> 2);
          if (ch > 2) mbar_wait(bars + (B_IN + ch - 3) * 8, 0);
          send_y(ch - 1);
        }
        if (ch < 6) {
          mbar_wait(bars + (B_KE + (ch & 1)) * 8, (ch >> 1) & 1);
          if (ch < 4) load_k(ch + 4, sb + OFF_K + (ch & 1) * 4096);
          if (ch >= 2) load_q(ch - 2);
        }
      }
#pragma unroll 1
      for (int i = 4; i < 8; i++) { mbar_wait(bars + (B_QE + i - 4) * 8, 0); load_q(i); }
    }
    return;
  } else if (wg == 2) {
    asm volatile("setmaxnreg.inc.sync.aligned.u32 %0;" ::"n"(488 - 2 * GREG));
    const int t = tid & 127, w = warp & 3, lane = t & 31, g = lane >> 2, c = lane & 3;
    const uint4 s2[2] = {ldg128_nc(P.shift_k + (8 * b + 2 * c) * 4), ldg128_nc(P.shift_k + (8 * (b ^ 1) + 2 * c) * 4)};
    const uint32_t dskip = __bfloat16_as_ushort(P.ssm_D[8 * b + (t & 7)]);
    uint32_t tp[4] = {}, ts[4] = {};
    float d0r, d0i;
    fft_tables(sb + OFF_F1, sb + OFF_F2, w, lane, tp, ts, d0r, d0i);
    if (t == 0) STAMP(19);
    CLUSTER_WAIT();
    if (t < 12) mbar_expect(bars + (B_IN + t) * 8, t < 8 ? 2048 : U_N8);
    if (t < 8) sts32(sb + OFF_D + 4 * t, dskip << 16);
    const uint64_t dF1a = make_desc(sb + OFF_F1, 128, 512, 0), dF1b = make_desc(sb + OFF_F1, 512, 128, 0);
    const uint64_t dF2f = make_desc(sb + OFF_F2, 512, 128, 0), dF2i = make_desc(sb + OFF_F2, 128, 512, 0);
    auto T1k = [&](float* z, uint64_t dk) { wg_fence(); ss_n64<0, 1>(z, dF1a, dk); ss_n64<1, 1>(z, dF1a + 16, dk + 64); wg_commit(); };
    auto T1u = [&](float* z, uint64_t du) { wg_fence(); ss_n64<0, 0>(z, dF1a, du); ss_n64<1, 0>(z, dF1a + 16, du + 16); wg_commit(); };
    auto T2 = [&](float* s, const uint32_t* f) {
      wg_fence();
      rs_n32<0, 1>(s, f, dF2f); rs_n32<0, 1>(s + 16, f + 8, dF2f); rs_n32<1, 1>(s, f + 4, dF2f + 64); rs_n32<1, 1>(s + 16, f + 12, dF2f + 64);
      wg_commit();
    };
    auto product = [&](uint32_t* pr, const uint32_t* kh, const uint32_t* uh) {
      bimac<0>(pr, kh, uh, pr); bimac<2>(pr + 8, kh + 8, uh, pr); bimac<1>(pr + 8, kh, uh + 8, pr + 8);
      fence_u32<16>(pr);
    };
    float zk[32] = {};
    uint32_t pr[16];
    {
      uint32_t kh0[16];
      {
        float z0[32], sk[32];
        uint32_t fk[16];
        const uint64_t dk = make_desc(sb + OFF_U + (4 * rank + 3) * U_N8, 2048, 512, 2);
        fence_proxy_async_smem();
        bar_sync(7, 128);
        mbar_wait(bars + B_KF * 8, 0);
        T1k(z0, dk);
        mbar_wait(bars + (B_KF + 1) * 8, 0);
        T1k(zk, dk - 256);
        wg_wait<0>(); fence_regs<32>(z0); fence_regs<32>(zk);
        const float dd = __uint_as_float(lds32(sb + OFF_D));
        z0[0] = fmaf(d0r, dd, z0[0]); z0[2] = fmaf(d0i, dd, z0[2]);
        pack32(fk, z0); twiddle<0>(fk, tp, ts); fence_u32<16>(fk);
        T2(sk, fk);
        wg_wait<0>(); fence_regs<32>(sk); fence_u32<16>(fk);
        pack32(kh0, sk); fence_u32<16>(kh0);
      }
      {
        uint32_t sk[2][4], kx[2][8];
#pragma unroll
        for (int o = 0; o < 2; o++) {
          sk[o][0] = __byte_perm(s2[o].x, s2[o].z, 0x5410); sk[o][1] = __byte_perm(s2[o].x, s2[o].z, 0x7632);
          sk[o][2] = __byte_perm(s2[o].y, s2[o].w, 0x5410); sk[o][3] = __byte_perm(s2[o].y, s2[o].w, 0x7632);
        }
        const uint32_t la = sb + OFF_KV + (lane >> 3) * 1024 + (8 * w + (lane & 7)) * 32 + ((rank ^ ((lane >> 2) & 1)) << 4);
        const uint32_t uo = (lane & 7) * U_CH + w * 128 + (lane >> 3) * 16;
        mbar_wait(bars + (B_KVF + 2) * 8, 0);
        if (t == 0) STAMP(27);
        ldsm4(kx[0], la + 16384); ldsm4(kx[1], (la ^ 16) + 16384);
        if (lane == 0) mbar_arrive(bars + (B_KVE + 2) * 8 + (kx[0][1] & kx[1][1] & P.zero));
        uint32_t so = 0, ph = 0;
#pragma unroll 1
        for (int n = 0; n < 4; n++) {
          const uint32_t own = sb + OFF_U + (4 * rank + n) * U_N8, box = n < 3 ? sb + OFF_U + (4 * (rank ^ 1) + n + 1) * U_N8 : sb + OFF_IN;
#pragma unroll
          for (int e = 0; e < 2; e++) {
            uint32_t vx[2][4];
            mbar_wait(bars + B_KVF * 8 + so, ph);
            if (t == 0) KSTAMP(2, 2 * n + e);
#pragma unroll
            for (int o = 0; o < 2; o++) { ldsm4(kx[o] + 4, (la ^ (16 * o)) + (so << 10)); ldsm4(vx[o], (la ^ (16 * o)) + (so << 10) + 4096); }
            if (lane == 0) mbar_arrive(bars + B_KVE * 8 + so + (kx[0][4] & kx[1][4] & vx[0][0] & vx[1][0] & P.zero));
#pragma unroll
            for (int o = 0; o < 2; o++) {
#pragma unroll
              for (int i = 0; i < 4; i++) vx[o][i] = bmul2(bfma2(kx[o][i + 4], sk[o][0], bfma2(kx[o][i + 3], sk[o][1], bfma2(kx[o][i + 2], sk[o][2], bmul2(kx[o][i + 1], sk[o][3])))), vx[o][i]);
              stsm4t((o ? box : own) + uo + e * 64, vx[o][0], vx[o][1], vx[o][2], vx[o][3]);
              kx[o][1] = kx[o][5]; kx[o][2] = kx[o][6]; kx[o][3] = kx[o][7];
            }
            if (t == 0) KSTAMP(3, 2 * n + e);
            so += 8;
            if (so == 24) so = 0;
            if (so == 16) ph ^= 1;
          }
          fence_proxy_async_smem();
          bar_sync(7, 128);
          if (w == 0 && elect_one()) {
            if (n > 0) mbar_wait(bars + B_UF * 8 + 8 * (n - 1), 0);
            bulk_send(own, box, U_N8, bars + B_UF * 8 + 8 * n, rank ^ 1);
          }
          __syncwarp();
        }
        if (t == 0) STAMP(28);
      }
      float zu[32], su[32];
      uint32_t fu[16], uh[16];
#pragma unroll
      for (int n = 0; n < 4; n++) mbar_wait(bars + (B_UF + n) * 8, 0);
      T1u(zu, make_desc(sb + OFF_U, 128, U_N8, 0));
      wg_wait<0>(); fence_regs<32>(zu);
      pack32(fu, zu); twiddle<0>(fu, tp, ts); fence_u32<16>(fu);
      T2(su, fu);
      wg_wait<0>(); fence_regs<32>(su); fence_u32<16>(fu);
      pack32(uh, su);
      product(pr, kh0, uh);
      if (t == 0) STAMP(54);
    }
    {
#define CF(i) do { if ((CFM >> (i)) & 1) PMFENCE(); } while (0)
#define CP(i)
      const uint32_t vs = w < 2 ? 512 : U_N8;
      uint32_t va = (w < 2 ? sb + OFF_VP : sb + OFF_U) + ((lane >> 4) & 1) * vs + (w & 1) * 256 + (lane & 15) * 16;
      uint32_t ya = sb + OFF_U + (2 * w + ((lane >> 3) & 1)) * U_N8 + (lane >> 4) * 128 + (lane & 7) * 16;
      uint64_t du = make_desc(sb + OFF_U, 128, U_N8, 0), dk = make_desc(sb + OFF_K, 2048, 512, 2);
      const uint64_t dv = make_desc(sb + OFF_VP, 128, 512, 0);
      uint32_t yp[8] = {};
      uint32_t yq = sb + OFF_Q + lane * 16;
      auto store_y = [&]() { stsm4(yq, yp[0], yp[1], yp[2], yp[3]); stsm4(yq + 256, yp[4], yp[5], yp[6], yp[7]); };
      auto step = [&](int ch, auto fwd) {
        constexpr bool FWD = decltype(fwd)::value;
        float zu[32], sk[32], su[32], v[32], y[16];
        uint32_t kh[16], uh[16], fk[16], fu[16], fv[16];
        CP(16);
        wg_fence();
        rs_n32<0, 0>(v, pr, dF2i); rs_n32<0, 0>(v + 16, pr + 8, dF2i); rs_n32<1, 0>(v, pr + 4, dF2i + 16); rs_n32<1, 0>(v + 16, pr + 12, dF2i + 16);
        wg_commit();
        CF(0);
        store_y();
        if (FWD) {
          const float dd = __uint_as_float(lds32(sb + OFF_D + 4 * (ch + 1)));
          zk[0] = fmaf(d0r, dd, zk[0]); zk[2] = fmaf(d0i, dd, zk[2]);
          pack32(fk, zk); twiddle<0>(fk, tp, ts); fence_u32<16>(fk);
          CP(1);
          T2(sk, fk);
          CF(2);
          mbar_wait(bars + (B_KF + (ch & 1)) * 8, ((ch >> 1) & 1) ^ 1);
          wg_wait<1>();
        } else wg_wait<0>();
        fence_regs<32>(v); fence_u32<16>(pr); CP(3);
        pack32(fv, v); fence_u32<16>(fv);
        CF(4);
        if (FWD) T1u(zu, du + U_CH / 16);
        CF(5);
        twiddle<1>(fv, tp, ts);
#pragma unroll
        for (int i = 0; i < 4; i++) stsm4(va + 2 * i * vs, fv[4 * i], fv[4 * i + 1], fv[4 * i + 2], fv[4 * i + 3]);
        if (FWD) {
          CF(6);
          wg_wait<1>(); fence_regs<32>(sk); fence_u32<16>(fk);
          pack32(kh, sk); fence_u32<16>(kh);
          CF(7);
          T1k(zk, dk);
          CF(8);
          wg_wait<1>(); fence_regs<32>(zu);
          pack32(fu, zu); twiddle<0>(fu, tp, ts); fence_u32<16>(fu);
          CP(9);
          T2(su, fu);
          CF(10);
        }
        fence_proxy_async_smem();
        bar_sync(7, 128);
        wg_fence(); CP(11);
        ss_n32_tt<0>(y, dv, dF1b); ss_n32_tt<1>(y, dv + 16, dF1b + 64); ss_n32_tt<1>(y, du, dF1b + 128); ss_n32_tt<1>(y, du + 16, dF1b + 192);
        wg_commit();
        if (t == 0) mbar_arrive(bars + (B_Y + (ch & 3)) * 8);
        CF(12);
        if (FWD) {
          wg_wait<1>(); fence_regs<32>(su); fence_u32<16>(fu); fence_regs<32>(zk); CP(13);
          if (t == 0) mbar_arrive(bars + (B_KE + (ch & 1)) * 8);
          pack32(uh, su);
          product(pr, kh, uh);
          du += U_CH / 16; dk += (ch & 1) ? -256 : 256;
          if (w >= 2) va += U_CH;
        }
        CF(14);
        wg_wait<0>(); fence_regs<16>(y); CP(15);
#pragma unroll
        for (int i = 0; i < 8; i++) yp[i] = pack_bf16(y[2 * i], y[2 * i + 1]);
        fence_u32<8>(yp);
        yq = ya;
        ya += U_CH; CP(17);
        if (t == 0) STAMP(55 + ch);
      };
#pragma unroll 1
      for (int ch = 0; ch < 7; ch++) step(ch, std::true_type());
      step(7, std::false_type());
      store_y();
    }
    fence_proxy_async_smem();
    bar_sync(9, 256);
    if (t == 0) STAMP(29);
  } else {
    asm volatile("setmaxnreg.inc.sync.aligned.u32 %0;" ::"n"(GREG));
    const int t = tid & 127, w = warp & 3, lane = t & 31, g = lane >> 2, c = lane & 3;
    if (wg == 1) {
      wait_until(c_start, COEF_T0);
      const int p = 64 * j + (t & 63) + 8 * (t & 64);
      const float Lr = bf2f(P.lam_re[p]), Li = bf2f(P.lam_im[p]);
      const uint32_t ds = __bfloat16_as_ushort(P.Dskip[128 * j + t]);
      const unsigned epoch = ld_relaxed(&g_epoch[b * 32]) + 1;
      const float dt = bf2f(__float2bfloat16_rn(expf(bf2f(P.log_dt[p]))));
      const float e = expf(dt * Lr);
      float sn, cs;
      {
        const double z = (double)(dt * Li) * 0.15915494309189535;
        sincospif(2.f * (float)(z - rint(z)), &sn, &cs);
      }
      const float lr = e * cs, li = e * sn;
      const float nr = lr - 1.0f, ni = li;
      const bool big = fabsf(Lr) >= fabsf(Li);
      const float la = big ? Lr : Li, lb = big ? Li : Lr, r = __fdiv_rn(lb, la), inv = __frcp_rn(fmaf(lb, r, la));
      const float br = (big ? fmaf(ni, r, nr) : fmaf(nr, r, ni)) * inv, bi = (big ? fmaf(-nr, r, ni) : fmaf(ni, r, -nr)) * inv;
      sts128(sb + OFF_COEF + t * 16, make_uint4(__float_as_uint(lr), __float_as_uint(li), __float_as_uint(2.f * br), __float_as_uint(-2.f * bi)));
      sts32(sb + OFF_DS + 4 * t, ds << 16);
      if (t == 0) sts32(bars + B_EPOCH * 8, epoch);
      if (t == 0) STAMP(52);
    }
    CLUSTER_WAIT();
    if (wg == 1) mbar_arrive(bars + B_COEF * 8);
    float d[128];
    uint32_t so = 0, ph = 0, po = 0;
    uint32_t ra;
    auto set_ra = [&]() { asm volatile("mapa.shared::cluster.u32 %0, %1, %2;" : "=r"(ra) : "r"(bars + (SHAKE == 2 && (t & 3) != 2 ? B_PEER : B_EMPTY) * 8), "r"((t & 1) ? rank ^ 1 : rank)); };
    set_ra();
    auto release_at = [&](uint32_t off, bool skip) {
      asm volatile("{\n.reg .pred p;\nsetp.lt.u32 p, %1, %2;\n@p mbarrier.arrive.shared::cluster.b64 _, [%0];\n}\n" ::"r"(ra + off), "r"(t), "r"(skip ? 0 : SHAKE == 2 ? 3 : SHAKE == 1 ? 1 : 2) : "memory");
    };
    auto release = [&](bool first) { release_at(po, first); };
    auto block = [&](auto ta, uint64_t da0, uint64_t db0, bool first, bool zero, int nn) {
      constexpr int PH = decltype(ta)::value, TA = PH > 0, KS = TA ? 128 : 2, QD = PH == 0 ? QD1 : PH == 1 ? QD2 : QD3;
      if (t == 0) TSTAMP(2, nn);
      mbar_wait(bars + B_FULL * 8 + so, ph);
      if (t == 0) TSTAMP(3, nn);
      const uint64_t da = da0 + (so << 8), db = db0 + (so << 8);
      wg_fence();
      wgmma_n128<TA>(d, da, db, !zero);
      wgmma_n128<TA>(d + 64, da + 512, db, !zero);
      wg_commit();
      wg_wait<1>();
      if (RELPOS == 0) release(first);
#pragma unroll
      for (int k = 1; k < 4; k++) {
        if (QD == 2 || (QD == 4 && k == 2)) wg_fence();
        wgmma_n128<TA>(d, da + KS * k, db + 2 * k, 1);
        wgmma_n128<TA>(d + 64, da + 512 + KS * k, db + 2 * k, 1);
        if (QD == 2 || (QD == 4 && k == 1)) wg_commit();
        if (RELPOS == 1 && k == 1) release(first);
        if ((QD == 2 && k < 3) || (QD == 4 && k == 1)) wg_wait<1>();
      }
      if (QD != 2) wg_commit();
      if (RELPOS == 2) release(first);
      po = so;
      so += 8;
      if (so == 8 * STAGES) { so = 0; ph ^= 1; }
    };
    {
      so = wg ? 8 * (16 % STAGES) : 0; ph = wg ? (16 / STAGES) & 1 : 0; po = 0;
      const uint64_t da0 = make_desc(sb + OFF_RING, 16, 1024, 1), db0 = make_desc(sb + OFF_RING + 16384, 16, 1024, 1);
      if (wg == 1) bar_sync(1, 256);
#pragma unroll 1
      for (int kb = 0; kb < 16; kb++) {
        if (16 * wg + kb == XPOS) { so += 8; if (so == 8 * STAGES) { so = 0; ph ^= 1; } }
        block(std::integral_constant<int, 0>(), da0, db0, kb == 0, kb == 0, 16 * wg + kb);
      }
      asm volatile("bar.arrive %0, 256;" ::"r"(1 + wg) : "memory");
    }
    mbar_wait(bars + B_COEF * 8, 0);
    const uint32_t ca = sb + OFF_COEF + (64 * wg + 8 * w + g) * 16;
    const uint32_t tag = __shfl_sync(0xffffffffu, lds32(bars + B_EPOCH * 8) & 3, 0);
    constexpr int RE = SWAPB ? 2 : 0, IM = 2 - RE;
    uint2* cp = &g_carry[((16 * wg + 2 * j) * 16 + tc) * 32 + 8 * w];
    const int ct = lane >> 3;
    uint2 cv[4];
    auto load_carry = [&](int i) {
#pragma unroll
      for (int m = 0; m < 4; m++)
        asm volatile("{\n.reg .pred p;\n.reg .b64 v;\nsetp.lt.s32 p, %3, %4;\nmov.b64 v, {%0,%1};\n@p ld.relaxed.gpu.global.b64 v, [%2];\nmov.b64 {%0,%1}, v;\n}\n"
                     : "+r"(cv[m].x), "+r"(cv[m].y) : "l"(cp + 512 * i + (lane & 7) - 32 * (1 + ct) - 128 * m), "r"(ct), "r"(tc - 4 * m) : "memory");
    };
    auto first_load = [&](int i) {
#pragma unroll
      for (int m = 0; m < 4; m++) cv[m] = make_uint2(tag, 0);
      load_carry(i);
    };
    float lr[2], li[2], pr[2], pi[2], wr[2], wi[2], vr[2], vi[2], qr[2], qi[2], er[2], ei[2], gr[2], gi[2];
    auto powers = [&](int i) {
      const uint2 cf = lds64(ca + 512 * i);
      pr[i] = lr[i] = __uint_as_float(cf.x); pi[i] = li[i] = __uint_as_float(cf.y);
#pragma unroll
      for (int s = 0; s < 4; s++) csq(pr[i], pi[i]);
      gr[i] = pr[i]; gi[i] = pi[i];
      csq(pr[i], pi[i]);
      qr[i] = pr[i]; qi[i] = pi[i];
      csq(qr[i], qi[i]);
      er[i] = qr[i]; ei[i] = qi[i];
      wr[i] = (c & 1) ? pr[i] : 1.f; wi[i] = (c & 1) ? pi[i] : 0.f;
      if (c & 2) { float x, y; cmul(wr[i], wi[i], qr[i], qi[i], x, y); wr[i] = x; wi[i] = y; }
      vr[i] = wr[i]; vi[i] = wi[i];
      csq(vr[i], vi[i]); csq(vr[i], vi[i]);
      csq(qr[i], qi[i]); csq(qr[i], qi[i]); csq(qr[i], qi[i]);
      const int src = 4 * (lane & 7) + ct;
      vr[i] = __shfl_sync(0xffffffffu, vr[i], src); vi[i] = __shfl_sync(0xffffffffu, vi[i], src);
      qr[i] = __shfl_sync(0xffffffffu, qr[i], src); qi[i] = __shfl_sync(0xffffffffu, qi[i], src);
      asm volatile("" : "+f"(wr[i]), "+f"(wi[i]), "+f"(pr[i]), "+f"(pi[i]), "+f"(er[i]), "+f"(ei[i]));
    };
    powers(0);
    if (POW2 == 0) powers(1);
    PMFENCE();
    wg_wait<0>();
    fence_regs<128>(d);
    release(false);
    if (t == 0) STAMP(10 + 10 * wg);
#pragma unroll
    for (int i = 0; i < 2; i++) {
      const float* e = d + 64 * i;
      auto chain = [&](int s0, int s1, float& sr, float& si) {
        sr = e[2 * s0 + RE]; si = e[2 * s0 + IM];
#pragma unroll
        for (int s = s0 + 1; s < s1; s++) {
          const int ia = 4 * (s >> 1) + (s & 1);
          const float nr = fmaf(-li[i], si, fmaf(lr[i], sr, e[ia + RE])), ni = fmaf(li[i], sr, fmaf(lr[i], si, e[ia + IM]));
          sr = nr; si = ni;
        }
      };
      float sr, si;
      if (POW2 == 1 && i == 1) powers(1);
      if ((GREEDY >> i) & 1) {
        float ar, ai;
        chain(0, 16, ar, ai); chain(16, 32, sr, si);
        sr = fmaf(gr[i], ar, fmaf(-gi[i], ai, sr)); si = fmaf(gr[i], ai, fmaf(gi[i], ar, si));
      } else chain(0, 32, sr, si);
      if (i == 1 && C_AT == 0) { asm volatile("pmevent 0;" : "+f"(sr), "+f"(si)::"memory"); first_load(0); }
      float ur = __shfl_up_sync(0xffffffffu, sr, 1, 4), ui = __shfl_up_sync(0xffffffffu, si, 1, 4);
      if (c >= 1) { sr = fmaf(pr[i], ur, fmaf(-pi[i], ui, sr)); si = fmaf(pr[i], ui, fmaf(pi[i], ur, si)); }
      ur = __shfl_up_sync(0xffffffffu, sr, 2, 4); ui = __shfl_up_sync(0xffffffffu, si, 2, 4);
      if (c >= 2) { sr = fmaf(er[i], ur, fmaf(-ei[i], ui, sr)); si = fmaf(er[i], ui, fmaf(ei[i], ur, si)); }
      if (c == 3 && tc < 15)
        asm volatile("{\n.reg .b64 v;\nmov.b64 v, {%1,%2};\nst.relaxed.gpu.global.b64 [%0], v;\n}\n" ::"l"(cp + 512 * i + g), "r"((__float_as_uint(sr) & ~3u) | tag), "r"(__float_as_uint(si)) : "memory");
      if (i == 1 && C_AT == 1) first_load(0);
      PMFENCE();
      if (t == 0) STAMP(11 + i + 10 * wg);
      er[i] = __shfl_up_sync(0xffffffffu, sr, 1, 4); ei[i] = __shfl_up_sync(0xffffffffu, si, 1, 4);
      if (c == 0) er[i] = ei[i] = 0.f;
    }
    uint4* hp = g_h + (32 * tc + 16 * wg + 2 * j) * 1024 + 64 * w + 4 * g + (c ^ (g >> 1));
#pragma unroll
    for (int i = 0; i < 2; i++) {
      float* e = d + 64 * i;
      const uint2 cf = lds64(ca + 512 * i + 8);
      const float mr = __uint_as_float(cf.x), mi = __uint_as_float(cf.y);
      const uint32_t gp = pack_bf16(mr, mr), gms = pack_bf16(mi, mi);
      const int NS = i == 0 ? PRE_S : 0;
#pragma unroll
      for (int s = 32 - 8 * NS; s < 32; s++) {
        const int ia = 4 * (s >> 1) + (s & 1);
        asm volatile("{\n.reg .f32 u, v, n;\nmul.f32 u, %3, %1;\nmul.f32 v, %3, %0;\nneg.f32 n, %2;\nfma.rn.f32 %0, %2, %0, u;\nfma.rn.f32 %1, n, %1, v;\n}\n"
                     : "+f"(e[ia + RE]), "+f"(e[ia + IM]) : "f"(mr), "f"(mi));
        if (s % PRE_G == PRE_G - 1) PMFENCE();
      }
      PMFENCE();
      int n = 0;
#pragma unroll 1
      while (!__all_sync(0xffffffffu, (((cv[0].x ^ tag) | (cv[1].x ^ tag) | (cv[2].x ^ tag) | (cv[3].x ^ tag)) & 3) == 0) && ++n <= (SPIN_LIMIT << 4)) load_carry(i);
      if (t == 0 && i == 0) STAMP(13 + 10 * wg);
      float hr = __uint_as_float(cv[3].x), hi = __uint_as_float(cv[3].y);
#pragma unroll
      for (int m = 2; m >= 0; m--) {
        const float nr = fmaf(qr[i], hr, fmaf(-qi[i], hi, __uint_as_float(cv[m].x))), ni = fmaf(qr[i], hi, fmaf(qi[i], hr, __uint_as_float(cv[m].y)));
        hr = nr; hi = ni;
      }
      { float x, y; cmul(hr, hi, vr[i], vi[i], x, y); hr = x; hi = y; }
      hr += __shfl_xor_sync(0xffffffffu, hr, 8); hi += __shfl_xor_sync(0xffffffffu, hi, 8);
      hr = __shfl_sync(0xffffffffu, hr, g) + __shfl_sync(0xffffffffu, hr, g + 16); hi = __shfl_sync(0xffffffffu, hi, g) + __shfl_sync(0xffffffffu, hi, g + 16);
      float sr = fmaf(wr[i], hr, fmaf(-wi[i], hi, er[i])), si = fmaf(wr[i], hi, fmaf(wi[i], hr, ei[i]));
      if (t == 0 && i == 0) STAMP(14 + 10 * wg);
#pragma unroll
      for (int i8 = 0; i8 < 4; i8++) {
        const bool pre = i8 >= 4 - NS;
        if (i8 == 4 - NS) { const float x = sr; sr = fmaf(mr, x, mi * si); si = fmaf(-mr, si, mi * x); }
        asm volatile("pmevent 0;" : "+f"(sr), "+f"(si)::"memory");
        if (i == 0 && i8 == C_AT2) first_load(1);
        const float ls = pre ? -li[i] : li[i];
#pragma unroll
        for (int s = 8 * i8; s < 8 * i8 + 8; s++) {
          const int ia = 4 * (s >> 1) + (s & 1);
          const float nr = fmaf(-ls, si, fmaf(lr[i], sr, e[ia + RE])), ni = fmaf(ls, sr, fmaf(lr[i], si, e[ia + IM]));
          sr = nr; si = ni;
          e[ia + RE] = nr; e[ia + IM] = ni;
        }
        if (P2_SPLIT) PMFENCE();
        uint32_t hp0[4], hp1[4];
#pragma unroll
        for (int m = 0; m < 4; m++) {
          const float* f = e + 16 * i8 + 4 * m;
          const uint32_t x = pack_bf16(f[RE], f[RE + 1]), y = pack_bf16(f[IM], f[IM + 1]);
          hp0[m] = pre ? x : bfma2(gp, x, bmul2(gms, y)); hp1[m] = pre ? y : bfnma2(gp, y, bmul2(gms, x));
        }
        uint4* o = hp + 512 * (i8 >> 1) + 256 * i + 32 * (i8 & 1);
        stg128(o, make_uint4(hp0[0], hp0[1], hp0[2], hp0[3]));
        stg128(o + 1024, make_uint4(hp1[0], hp1[1], hp1[2], hp1[3]));
      }
    }
    if (t == 0) STAMP(15 + 10 * wg);
    const int trow = 128 * tc + 64 * (w & 1) + 8 * (w >> 1) + g;
    const int dcol = 128 * j + 4 * c;
    asm volatile("bar.arrive %0, 160;" ::"r"(4 + wg) : "memory");
    if (wg == 0) {
      set_ra();
      uint2 xv[32];
      {
        const int gp = 2 * (g & 3) + (g >> 2);
        const uint32_t xa = sb + OFF_RING + (XPOS % STAGES) * STAGE_BYTES + (64 * (w & 1) + 8 * (w >> 1) + gp) * 128 + (c & 1) * 8;
        mbar_wait(bars + B_XI * 8, 0);
        mbar_wait(bars + (B_FULL + XPOS % STAGES) * 8, (XPOS / STAGES) & 1);
        if (t == 0) STAMP(18);
#pragma unroll
        for (int u = 0; u < 32; u++) {
          const int J = (u >> 1) & 7;
          if (X_NOXI) xv[u] = make_uint2(0, 0); else
          asm volatile("ld.shared.v2.u32 {%0,%1}, [%2];" : "=r"(xv[u].x), "=r"(xv[u].y) : "r"(xa + (J >> 2) * 16384 + (u >> 4) * 2048 + (u & 1) * 4096 + (((2 * (J & 3) + (c >> 1)) ^ gp) << 4)) : "memory");
        }
        uint32_t dep = P.zero;
#pragma unroll
        for (int u = 0; u < 32; u++) dep &= xv[u].x;
        bar_sync(3 + dep, 128);
        release_at(8 * (XPOS % STAGES), false);
      }
#pragma unroll
      for (int J = 0; J < (X_NOXI ? 0 : 8); J++) {
        const uint4 ds = lds128(sb + OFF_DS + 16 * c + 64 * J);
#pragma unroll
        for (int r = 0; r < 4; r++) {
          const int u = 16 * (r >> 1) + 2 * J + (r & 1);
          float* e = d + 8 * (u >> 1) + 2 * (u & 1);
          e[0] = __uint_as_float(bfma2(blo2(xv[u].x), ds.x, 0)); e[1] = __uint_as_float(bfma2(xv[u].x, ds.y, 0));
          e[4] = __uint_as_float(bfma2(blo2(xv[u].y), ds.z, 0)); e[5] = __uint_as_float(bfma2(xv[u].y, ds.w, 0));
        }
      }
      fence_regs<128>(d);
      if (t == 0) STAMP(17);
      so = 8 * (33 % STAGES); ph = (33 / STAGES) & 1;
      const uint64_t da0 = make_desc(sb + OFF_RING + 16384, 512, 1024, 2), db0 = make_desc(sb + OFF_RING, 16, 1024, 1);
      bar_sync(2, 256);
#pragma unroll 1
      for (int kb = 0; kb < QSW; kb++) block(std::integral_constant<int, 1>(), da0, db0, kb == 0, false, 32 + kb);
#pragma unroll 1
      for (int kb = QSW; kb < 32 - TAILB; kb++) block(std::integral_constant<int, 2>(), da0, db0, false, false, 32 + kb);
      float* op = P.out + (size_t)trow * 2048 + 1024 + dcol;
      auto mma = [&](int i, int kb, int k0, int k1) {
        const int s = (33 + kb) % STAGES;
        wg_fence();
#pragma unroll
        for (int k = k0; k < k1; k++) wgmma_n128<1>(d + 64 * i, da0 + s * 2048 + 512 * i + 128 * k, db0 + s * 2048 + 2 * k, 1);
        wg_commit();
      };
      auto store = [&](int i, int J0, int J1) {
#pragma unroll
        for (int J = J0; J < J1; J++) {
#pragma unroll
          for (int h = 0; h < 2; h++) {
            const float* e = d + 64 * i + 8 * J + 2 * h;
            stg128(op + (size_t)(16 * i + 32 * h) * 2048 + 16 * J, make_uint4(__float_as_uint(e[0]), __float_as_uint(e[1]), __float_as_uint(e[4]), __float_as_uint(e[5])));
          }
        }
        PMFENCE();
      };
      constexpr int K0 = 32 - TAILB;
#pragma unroll
      for (int kb = K0; kb < 32; kb++) {
        mbar_wait(bars + (B_FULL + (33 + kb) % STAGES) * 8, ((33 + kb) / STAGES) & 1);
        if (TAILB == 5 && kb == K0) { mma(0, kb, 0, 2); wg_wait<1>(); release(false); mma(0, kb, 2, 4); }
        else mma(0, kb, 0, 4);
      }
      mma(1, K0, 0, 4);
      wg_wait<1>();
      fence_regs<64>(d);
      if (t == 0) STAMP(48);
#pragma unroll
      for (int kb = K0 + 1; kb < 32; kb++) {
        mma(1, kb, 0, 4);
        if (T_FENCE) PMFENCE();
        store(0, T_ST * (kb - K0 - 1), kb == 31 ? 8 : T_ST * (kb - K0));
      }
      if (t == 0) STAMP(49);
      wg_wait<0>();
      fence_regs<64>(d + 64);
      if (t == 0) STAMP(50);
      store(1, 0, 8);
      if (t == 0) { STAMP(51); GSTAMP(51); }
      if (t == 0) g_epoch[b * 32] = lds32(bars + B_EPOCH * 8);
      return;
    }
    asm volatile("setmaxnreg.dec.sync.aligned.u32 %0;" ::"n"(488 - 2 * GREG));
  }
  {
    int lane;
    asm volatile("mov.u32 %0, %%laneid;" : "=r"(lane));
    const int w = warp & 3, g = lane >> 2, c = lane & 3, h = wg & 1;
    const int lc = 2 * (lane & 2) + (lane & 1) + ((lane >> 2) & 2);
    const bool own = ((lane >> 2) & 1) == rank, spare = !own && lc < 2;
    const uint32_t ya = (spare ? sb + OFF_IN + 96 + lc * 2064 : sb + OFF_U + (own ? 4 * rank * U_N8 : 4 * (rank ^ 1) * U_N8 - 2 * U_CH) + lc * U_CH) + w * 128 + (lane >> 4) * 16 + h * 64;
    const uint32_t ys = spare ? 512 : U_N8;
    const uint32_t qa = sb + (8 * w + g) * 32 + 8 * c + 4096 * h;
    const uint32_t ob = sb + (h ? OFF_VP : OFF_F1) + 1024 * w;
    uint32_t y[2][8];
    uint2 q[2][4];
    auto load = [&](int n) {
      mbar_wait(bars + q_bar(2 * n) + 8 * h, n >> 1);
      const uint32_t qs = qa + q_slot(2 * n);
#pragma unroll
      for (int r = 0; r < 4; r++) q[n & 1][r] = lds64(qs + r * 1024);
      if (n == 0) {
        if (h) {
#pragma unroll 1
          for (int r = 0; r < 6; r++) mbar_wait(bars + (B_IN + r) * 8, 0);
          uint32_t src = sb + OFF_U + (4 * (rank ^ 1) + w) * U_N8 + 7 * U_CH, dst = sb + OFF_U + (4 * rank + w) * U_N8 + 5 * U_CH;
          bar_sync(9, 256);
          if (elect_one()) { bulk_send(dst, src, 512, bars + (B_IN + 7) * 8, rank ^ 1); }
          __syncwarp();
        }
        mbar_wait(bars + (B_IN + 6) * 8, 0); mbar_wait(bars + (B_IN + 7) * 8, 0);
      }
      ldsm4t(y[n & 1], ya + n * ys); ldsm4t(y[n & 1] + 4, ya + n * ys + 32);
    };
    load(0);
    if (warp == 8 && lane == 0) mbar_arrive_cta(bars + B_ACK * 8, rank ^ 1);
    if (O_WAIT) mbar_wait(bars + (O_WAIT == 1 ? B_HP : B_HR) * 8, 1);
    uint32_t oc = clk32() + (2 * w + h) * (O_PACE / 2);
    if (warp == 8 && lane == 0) STAMP(30);
#pragma unroll
    for (int n = 0; n < 4; n++) {
      uint32_t* o = y[n & 1];
#pragma unroll
      for (int r = 0; r < 4; r++) { o[2 * r] = bmul2(o[2 * r], q[n & 1][r].x); o[2 * r + 1] = bmul2(o[2 * r + 1], q[n & 1][r].y); }
      if (n < 2 && lane == 0) mbar_arrive(bars + (B_QE + 2 * n + h) * 8 + (o[0] & o[2] & o[4] & o[6] & P.zero));
#pragma unroll
      for (int u = 0; u < 2; u++) {
        if (lane == 0) asm volatile("cp.async.bulk.wait_group.read 0;" ::: "memory");
        __syncwarp();
#pragma unroll
        for (int r = 2 * u; r < 2 * u + 2; r++)
          sts128(ob + (r & 1) * 512 + lane * 16, make_uint4(o[2 * r] << 16, o[2 * r] & 0xffff0000u, o[2 * r + 1] << 16, o[2 * r + 1] & 0xffff0000u));
        if (O_PACE) { while ((int)(clk32() - oc) < 0) { if (O_SLEEP) __nanosleep(O_SLEEP); } }
        oc += 4 * O_PACE;
        fence_proxy_async_smem();
        __syncwarp();
        if (lane == 0)
          asm volatile("cp.async.bulk.tensor.3d.global.shared::cta.bulk_group [%0, {%2, %3, %4}], [%1];\ncp.async.bulk.commit_group;"
                       ::"l"(&mO), "r"(ob), "r"(32 * slot), "r"(32 * rank + 8 * w), "r"(8 * n + 4 * h + 2 * u) : "memory");
        __syncwarp();
        if (u == 0 && n < 3) load(n + 1);
      }
    }
    if (lane == 0) asm volatile("cp.async.bulk.wait_group 0;" ::: "memory");
    if (warp == 8 && lane == 0) STAMP(31);
    mbar_wait(bars + B_ACK * 8, 0);
  }
}

typedef CUresult (*EncodeFn)(CUtensorMap*, CUtensorMapDataType, cuuint32_t, void*, const cuuint64_t*, const cuuint64_t*, const cuuint32_t*,
                             const cuuint32_t*, CUtensorMapInterleave, CUtensorMapSwizzle, CUtensorMapL2promotion, CUtensorMapFloatOOBfill);

bool encode(EncodeFn fn, CUtensorMap* m, int rank, const void* base, const cuuint64_t* dims, const cuuint64_t* strides, const cuuint32_t* box, CUtensorMapSwizzle swz,
            CUtensorMapL2promotion promo = CU_TENSOR_MAP_L2_PROMOTION_L2_128B) {
  const cuuint32_t es[5] = {1, 1, 1, 1, 1};
  return fn(m, CU_TENSOR_MAP_DATA_TYPE_BFLOAT16, rank, const_cast<void*>(base), dims, strides, box, es, CU_TENSOR_MAP_INTERLEAVE_NONE, swz,
            promo, CU_TENSOR_MAP_FLOAT_OOB_FILL_NONE) == CUDA_SUCCESS;
}

}

extern "C" void kernel_launch(void* const* d_in, const int* in_sizes, int n_in, void* d_out, int out_size) {
  (void)in_sizes; (void)n_in; (void)out_size;
  typedef const __nv_bfloat16* In;
  const In q = (In)d_in[0], k = (In)d_in[1], v = (In)d_in[2], ssm_k = (In)d_in[4], x = (In)d_in[6], B_re = (In)d_in[9], B_im = (In)d_in[10], C_re = (In)d_in[11], C_im = (In)d_in[12];
  Params P = {};
  P.shift_k = (In)d_in[3]; P.ssm_D = (In)d_in[5]; P.lam_re = (In)d_in[7]; P.lam_im = (In)d_in[8]; P.log_dt = (In)d_in[13]; P.Dskip = (In)d_in[14];
  P.out = (float*)d_out;
  for (int cl = 0; cl < 64; cl++) P.slot[cl >> 2] |= (cl < 4 ? 4 + cl : cl < 36 ? 8 * ((cl - 4) & 7) + ((cl - 4) >> 3) : 8 * (1 + (cl - 36) % 7) + 4 + (cl - 36) / 7) << (8 * (cl & 3));
  const bool swapB = (uintptr_t)B_im < (uintptr_t)B_re;

  EncodeFn fn = nullptr;
  cudaDriverEntryPointQueryResult qr;
  cudaGetDriverEntryPoint("cuTensorMapEncodeTiled", (void**)&fn, cudaEnableDefault, &qr);
  if (!fn) return;

  CUtensorMap mX, mB, mCre, mCim, mXs, mK, mV, mQ, mS, mO;
  bool ok = true;
  {
    const cuuint64_t dims[4] = {1024, 2, 64, 16}, str[3] = {2048, 32 * 2048, 2 * 2048};
    const cuuint32_t box[4] = {64, 2, 4, 16};
    ok &= encode(fn, &mX, 4, x, dims, str, box, CU_TENSOR_MAP_SWIZZLE_128B, (CUtensorMapL2promotion)X_PROMO);
  }
  {
    const uintptr_t lo = swapB ? (uintptr_t)B_im : (uintptr_t)B_re, hi = swapB ? (uintptr_t)B_re : (uintptr_t)B_im;
    const cuuint64_t dims[4] = {1024, 8, 2, 128}, str[3] = {2048, (cuuint64_t)(hi - lo), 8 * 2048};
    const cuuint32_t box[4] = {64, 8, 2, 4};
    ok &= encode(fn, &mB, 4, (const void*)lo, dims, str, box, CU_TENSOR_MAP_SWIZZLE_128B, (CUtensorMapL2promotion)B_PROMO);
  }
  {
    const cuuint64_t dims[5] = {1024, 2, 4, 2, 64}, str[4] = {2048, 4 * 2048, 2 * 2048, 16 * 2048};
    const cuuint32_t box[5] = {64, 2, 4, 2, 4};
    ok &= encode(fn, &mCre, 5, C_re, dims, str, box, CU_TENSOR_MAP_SWIZZLE_128B, (CUtensorMapL2promotion)C_PROMO);
    ok &= encode(fn, &mCim, 5, C_im, dims, str, box, CU_TENSOR_MAP_SWIZZLE_128B, (CUtensorMapL2promotion)C_PROMO);
  }
  {
    const cuuint64_t dims[4] = {1024, 2, 4, 256}, str[3] = {4 * 2048, 2048, 8 * 2048};
    const cuuint32_t box[4] = {64, 2, 4, 16};
    ok &= encode(fn, &mXs, 4, x, dims, str, box, CU_TENSOR_MAP_SWIZZLE_128B);
  }
  {
    const cuuint64_t dims[3] = {1024, 64, 32}, str[2] = {32 * 2048, 2048};
    const cuuint32_t box[3] = {16, 32, 4};
    ok &= encode(fn, &mQ, 3, q, dims, str, box, CU_TENSOR_MAP_SWIZZLE_NONE, (CUtensorMapL2promotion)Q_PROMO);
    ok &= encode(fn, &mK, 3, k, dims, str, box, CU_TENSOR_MAP_SWIZZLE_32B, (CUtensorMapL2promotion)KV_PROMO);
    ok &= encode(fn, &mV, 3, v, dims, str, box, CU_TENSOR_MAP_SWIZZLE_32B, (CUtensorMapL2promotion)KV_PROMO);
  }
  {
    const cuuint64_t dims[2] = {32, 65536}, str[1] = {64};
    const cuuint32_t box[2] = {32, 64};
    ok &= encode(fn, &mS, 2, ssm_k, dims, str, box, CU_TENSOR_MAP_SWIZZLE_64B, (CUtensorMapL2promotion)S_PROMO);
  }
  {
    const cuuint64_t dims[3] = {2048, 64, 32}, str[2] = {32 * 8192, 8192};
    const cuuint32_t box[3] = {32, 8, 2};
    ok &= encode(fn, &mO, 3, d_out, dims, str, box, CU_TENSOR_MAP_SWIZZLE_NONE);
  }
  if (!ok) return;
  auto kern = swapB ? fused_kernel<1> : fused_kernel<0>;
  cudaFuncSetAttribute(kern, cudaFuncAttributeMaxDynamicSharedMemorySize, SMEM_BYTES);
  kern<<<NCTA, 512, SMEM_BYTES, cudaStreamPerThread>>>(P, mX, mB, mCre, mCim, mXs, mK, mV, mQ, mS, mO);
}
```

```cpp
#include <cuda_runtime.h>
#include <cuda_bf16.h>
#include <cuda.h>
#include <stdint.h>
#include <type_traits>

#define PROFILE 0

namespace {

constexpr int D_DIM = 1024;
constexpr int NCTA = 128;

constexpr int STAGES = 5, STAGE_BYTES = 32768;
constexpr int OFF_RING = 0;
constexpr int OFF_F1 = STAGES * STAGE_BYTES, OFF_F2 = OFF_F1 + 4096, OFF_K = OFF_F2 + 2048, OFF_VP = OFF_K + 8192, OFF_Q = OFF_VP + 4096, OFF_IN = OFF_Q + 8192;
constexpr int OFF_KV = OFF_K;
constexpr int U_CH = 528, U_N8 = 8 * U_CH, OFF_U = OFF_IN + U_N8;
constexpr int OFF_COEF = OFF_U + 8 * U_N8;
constexpr int OFF_DS = OFF_COEF + 2048, OFF_D = OFF_DS + 512;
constexpr int OFF_BAR = OFF_D + 64;
constexpr int OFF_PROF = OFF_BAR + 512;
constexpr int SMEM_BYTES = OFF_PROF + 512;
static_assert(SMEM_BYTES <= 232448 && OFF_K % 1024 == 0 && (OFF_U + 3 * U_N8) % 512 == 0 && (4 * U_N8) % 512 == 0, "smem map");
constexpr int B_FULL = 0, B_XI = 5, B_HR = 6, B_HP = 7, B_KVF = 8, B_KF = 11, B_KE = 13, B_QF = 15, B_IN = 19, B_UF = 27, B_Y = 31, B_CD = 35, B_ACK = 36,
              B_EMPTY = 38, B_PEER = 43, B_COEF = 48, B_KVE = 49, B_EPOCH = 52;
#define QD1 8
#define QD2 2
#define QD3 8
#define QSW 16
#define HEAD 3
#define ST_T0 200
#define ST_DELAY 300
#define XPOS 28
#define K_T0 800
#define KV_T0 1500
#define KV_DT 500
#define KV_DV 100
#define O_PACE 0
#define H_PACE 0
#define CARRY_WAIT 600
#define POLL_NS 30
#define GREEDY 0
#define P2_SPLIT 0
#define TAILB 5
#define GREG 176
#define O_WAIT 2
#define COEF_T0 2500
#define O_EVERY 1
#define X_P1 32
#define X_P2 8
#define X_NOXI 0
#define RELPOS 0
#define O_UNR 4
constexpr int O_UNROLL = O_UNR;
#define C_AT 0
#define C_AT2 1
#define T_FENCE 0
#define T_ST 2
#define X_PROMO 2
#define B_PROMO 2
#define C_PROMO 2
#define KV_PROMO 2
#define Q_PROMO 2
#define S_PROMO 2
#define SHAKE 0
#define PRE_S 0
#define PRE_G 2
#define POW2 0
#define O_SLEEP 20
#define PFC_D 16
#define PFC_0 16
#define PFC_ALL 0
#define CFM 0x40f1
constexpr int SPIN_LIMIT = 1 << 14;

struct Params {
  unsigned slot[16];
  unsigned zero;
  const __nv_bfloat16 *shift_k, *ssm_D, *lam_re, *lam_im, *log_dt, *Dskip;
  float* out;
};

__device__ __align__(1024) uint4 g_h[16 * 32 * 1024];
__device__ __align__(128) uint2 g_carry[32 * 16 * 32];
__device__ unsigned g_flagH[2 * 16 * 32];
__device__ unsigned g_epoch[NCTA * 32];
#define STAMP(i)
#define GSTAMP(i)
#define TSTAMP(k, n)
#define KSTAMP(k, n)

__device__ __forceinline__ uint64_t make_desc(uint32_t addr, uint32_t lbo, uint32_t sbo, uint32_t swz) {
  return (uint64_t)((addr & 0x3FFFF) >> 4) | ((uint64_t)(lbo >> 4) << 16) | ((uint64_t)(sbo >> 4) << 32) | ((uint64_t)swz << 62);
}
__device__ __forceinline__ void wg_fence() { asm volatile("wgmma.fence.sync.aligned;" ::: "memory"); }
__device__ __forceinline__ void wg_commit() { asm volatile("wgmma.commit_group.sync.aligned;" ::: "memory"); }
template <int N> __device__ __forceinline__ void wg_wait() { asm volatile("wgmma.wait_group.sync.aligned %0;" ::"n"(N) : "memory"); }
__device__ __forceinline__ void mbar_init(uint32_t bar, int cnt) { asm volatile("mbarrier.init.shared::cta.b64 [%0], %1;" ::"r"(bar), "r"(cnt) : "memory"); }
__device__ __forceinline__ void mbar_expect(uint32_t bar, uint32_t bytes) { asm volatile("mbarrier.arrive.expect_tx.shared::cta.b64 _, [%0], %1;" ::"r"(bar), "r"(bytes) : "memory"); }
__device__ __forceinline__ void mbar_wait(uint32_t bar, uint32_t parity) {
  uint32_t ok; int n = 0;
  do {
    asm volatile("{\n.reg .pred p;\nmbarrier.try_wait.parity.shared::cta.b64 p, [%1], %2;\nselp.u32 %0, 1, 0, p;\n}\n" : "=r"(ok) : "r"(bar), "r"(parity) : "memory");
    if (++n > SPIN_LIMIT) break;
  } while (!ok);
}
__device__ __forceinline__ void mbar_arrive(uint32_t bar) { asm volatile("mbarrier.arrive.shared::cta.b64 _, [%0];" ::"r"(bar) : "memory"); }
__device__ __forceinline__ void mbar_arrive_cta(uint32_t bar, uint32_t cta) {
  asm volatile("{\n.reg .b32 ra;\nmapa.shared::cluster.u32 ra, %0, %1;\nmbarrier.arrive.shared::cluster.b64 _, [ra];\n}\n" ::"r"(bar), "r"(cta) : "memory");
}
__device__ __forceinline__ bool elect_one() {
  uint32_t p;
  asm volatile("{\n.reg .pred P;\nelect.sync _|P, 0xffffffff;\nselp.u32 %0, 1, 0, P;\n}\n" : "=r"(p));
  return p != 0;
}
__device__ __forceinline__ void bar_sync(int id, int n) { asm volatile("bar.sync %0, %1;" ::"r"(id), "r"(n) : "memory"); }
#define TMA_LD(dim) "cp.async.bulk.tensor." dim ".shared::cluster.global.mbarrier::complete_tx::bytes"
__device__ __forceinline__ void tma2d(uint32_t dst, const CUtensorMap* m, int c0, int c1, uint32_t bar) {
  asm volatile(TMA_LD("2d") " [%0], [%1, {%3, %4}], [%2];" ::"r"(dst), "l"(m), "r"(bar), "r"(c0), "r"(c1) : "memory");
}
__device__ __forceinline__ void tma3d(uint32_t dst, const CUtensorMap* m, int c0, int c1, int c2, uint32_t bar) {
  asm volatile(TMA_LD("3d") " [%0], [%1, {%3, %4, %5}], [%2];" ::"r"(dst), "l"(m), "r"(bar), "r"(c0), "r"(c1), "r"(c2) : "memory");
}
__device__ __forceinline__ void tma4d(uint32_t dst, const CUtensorMap* m, int c0, int c1, int c2, int c3, uint32_t bar) {
  asm volatile(TMA_LD("4d") " [%0], [%1, {%3, %4, %5, %6}], [%2];" ::"r"(dst), "l"(m), "r"(bar), "r"(c0), "r"(c1), "r"(c2), "r"(c3) : "memory");
}
__device__ __forceinline__ void tma4d_mc(uint32_t dst, const CUtensorMap* m, int c0, int c1, int c2, int c3, uint32_t bar) {
  asm volatile(TMA_LD("4d") ".multicast::cluster [%0], [%1, {%3, %4, %5, %6}], [%2], %7;" ::"r"(dst), "l"(m), "r"(bar), "r"(c0), "r"(c1), "r"(c2), "r"(c3), "h"((uint16_t)3) : "memory");
}
__device__ __forceinline__ void tma5d_mc(uint32_t dst, const CUtensorMap* m, int c0, int c1, int c2, int c3, int c4, uint32_t bar) {
  asm volatile(TMA_LD("5d") ".multicast::cluster [%0], [%1, {%3, %4, %5, %6, %7}], [%2], %8;" ::"r"(dst), "l"(m), "r"(bar), "r"(c0), "r"(c1), "r"(c2), "r"(c3), "r"(c4), "h"((uint16_t)3) : "memory");
}
__device__ __forceinline__ void bulk_load(uint32_t dst, const void* src, uint32_t bytes, uint32_t bar) {
  asm volatile("cp.async.bulk.shared::cluster.global.mbarrier::complete_tx::bytes [%0], [%1], %2, [%3];" ::"r"(dst), "l"(src), "r"(bytes), "r"(bar) : "memory");
}
__device__ __forceinline__ void bulk_send(uint32_t dst, uint32_t src, uint32_t bytes, uint32_t bar, uint32_t cta) {
  asm volatile("{\n.reg .b32 rd, rb;\nmapa.shared::cluster.u32 rd, %0, %3;\nmapa.shared::cluster.u32 rb, %2, %3;\n"
               "cp.async.bulk.shared::cluster.shared::cta.mbarrier::complete_tx::bytes [rd], [%1], %4, [rb];\n}\n"
               ::"r"(dst), "r"(src), "r"(bar), "r"(cta), "r"(bytes) : "memory");
}
__device__ __forceinline__ void fence_proxy_async_smem() { asm volatile("fence.proxy.async.shared::cta;" ::: "memory"); }
__device__ __forceinline__ void fence_proxy_async_global() { asm volatile("fence.proxy.async.global;" ::: "memory"); }
__device__ __forceinline__ void red_release(unsigned* p, unsigned v) { asm volatile("red.release.gpu.global.add.u32 [%0], %1;" ::"l"(p), "r"(v) : "memory"); }
__device__ __forceinline__ uint32_t clk32() { uint32_t c; asm volatile("mov.u32 %0, %%clock;" : "=r"(c)::"memory"); return c; }
__device__ __forceinline__ void wait_until(uint32_t t0, uint32_t dt) { while (clk32() - t0 < dt) __nanosleep(32); }
__device__ __forceinline__ void spin_until(uint32_t t0, uint32_t dt) { while (clk32() - t0 < dt) {} }
__device__ __forceinline__ void prefetch_map(const CUtensorMap* m) { asm volatile("prefetch.tensormap [%0];" ::"l"(m) : "memory"); }
__device__ __forceinline__ void prefetch_line(const void* p) { asm volatile("prefetch.global.L2 [%0];" ::"l"(p) : "memory"); }
__device__ __forceinline__ unsigned ld_acquire(const unsigned* p) { unsigned v; asm volatile("ld.acquire.gpu.global.u32 %0, [%1];" : "=r"(v) : "l"(p) : "memory"); return v; }
__device__ __forceinline__ unsigned ld_relaxed(const unsigned* p) { unsigned v; asm volatile("ld.relaxed.gpu.global.u32 %0, [%1];" : "=r"(v) : "l"(p) : "memory"); return v; }
__device__ __forceinline__ uint32_t lds32(uint32_t a) { uint32_t v; asm volatile("ld.shared.u32 %0, [%1];" : "=r"(v) : "r"(a)); return v; }
__device__ __forceinline__ uint2 lds64(uint32_t a) { uint2 v; asm volatile("ld.shared.v2.u32 {%0,%1}, [%2];" : "=r"(v.x), "=r"(v.y) : "r"(a) : "memory"); return v; }
__device__ __forceinline__ uint4 lds128(uint32_t a) { uint4 v; asm volatile("ld.shared.v4.u32 {%0,%1,%2,%3}, [%4];" : "=r"(v.x), "=r"(v.y), "=r"(v.z), "=r"(v.w) : "r"(a) : "memory"); return v; }
__device__ __forceinline__ void sts32(uint32_t a, uint32_t v) { asm volatile("st.shared.u32 [%0], %1;" ::"r"(a), "r"(v) : "memory"); }
__device__ __forceinline__ void sts128(uint32_t a, uint4 v) { asm volatile("st.shared.v4.u32 [%0], {%1,%2,%3,%4};" ::"r"(a), "r"(v.x), "r"(v.y), "r"(v.z), "r"(v.w) : "memory"); }
__device__ __forceinline__ void ldsm4(uint32_t* r, uint32_t a) { asm volatile("ldmatrix.sync.aligned.m8n8.x4.shared.b16 {%0,%1,%2,%3}, [%4];" : "=r"(r[0]), "=r"(r[1]), "=r"(r[2]), "=r"(r[3]) : "r"(a) : "memory"); }
__device__ __forceinline__ void ldsm4t(uint32_t* r, uint32_t a) { asm volatile("ldmatrix.sync.aligned.m8n8.x4.trans.shared.b16 {%0,%1,%2,%3}, [%4];" : "=r"(r[0]), "=r"(r[1]), "=r"(r[2]), "=r"(r[3]) : "r"(a) : "memory"); }
__device__ __forceinline__ void stsm4t(uint32_t a, uint32_t r0, uint32_t r1, uint32_t r2, uint32_t r3) {
  asm volatile("stmatrix.sync.aligned.m8n8.x4.trans.shared.b16 [%0], {%1,%2,%3,%4};" ::"r"(a), "r"(r0), "r"(r1), "r"(r2), "r"(r3) : "memory");
}
__device__ __forceinline__ uint4 ldg128_nc(const void* p) { uint4 v; asm volatile("ld.global.nc.L1::no_allocate.v4.u32 {%0,%1,%2,%3}, [%4];" : "=r"(v.x), "=r"(v.y), "=r"(v.z), "=r"(v.w) : "l"(p)); return v; }
__device__ __forceinline__ void stg128(void* p, uint4 v) { asm volatile("st.global.L1::no_allocate.v4.u32 [%0], {%1,%2,%3,%4};" ::"l"(p), "r"(v.x), "r"(v.y), "r"(v.z), "r"(v.w) : "memory"); }
__device__ __forceinline__ uint32_t pack_bf16(float lo, float hi) { uint32_t r; asm("cvt.rn.bf16x2.f32 %0, %1, %2;" : "=r"(r) : "f"(hi), "f"(lo)); return r; }
__device__ __forceinline__ uint32_t bmul2(uint32_t a, uint32_t b) { uint32_t r; asm("mul.rn.bf16x2 %0, %1, %2;" : "=r"(r) : "r"(a), "r"(b)); return r; }
__device__ __forceinline__ uint32_t bfma2(uint32_t a, uint32_t b, uint32_t c) { uint32_t r; asm("fma.rn.bf16x2 %0, %1, %2, %3;" : "=r"(r) : "r"(a), "r"(b), "r"(c)); return r; }
__device__ __forceinline__ uint32_t blo2(uint32_t a) { uint32_t r; asm("{\n.reg .b16 l, h;\nmov.b32 {l, h}, %1;\nmov.b32 %0, {l, l};\n}" : "=r"(r) : "r"(a)); return r; }
__device__ __forceinline__ float bf2f(__nv_bfloat16 v) { return __bfloat162float(v); }

#define R8(d, o) "+f"(d[o]), "+f"(d[o + 1]), "+f"(d[o + 2]), "+f"(d[o + 3]), "+f"(d[o + 4]), "+f"(d[o + 5]), "+f"(d[o + 6]), "+f"(d[o + 7])
#define R16(d, o) R8(d, o), R8(d, o + 8)
#define R64(d, o) R16(d, o), R16(d, o + 16), R16(d, o + 32), R16(d, o + 48)
template <int TA> __device__ __forceinline__ void wgmma_n128(float* d, uint64_t da, uint64_t db, int scale_d) {
  asm volatile("{\n.reg .pred p;\nsetp.ne.b32 p, %66, 0;\n"
    "wgmma.mma_async.sync.aligned.m64n128k16.f32.bf16.bf16 {"
    "%0,%1,%2,%3,%4,%5,%6,%7,%8,%9,%10,%11,%12,%13,%14,%15,%16,%17,%18,%19,%20,%21,%22,%23,%24,%25,%26,%27,%28,%29,%30,%31,"
    "%32,%33,%34,%35,%36,%37,%38,%39,%40,%41,%42,%43,%44,%45,%46,%47,%48,%49,%50,%51,%52,%53,%54,%55,%56,%57,%58,%59,%60,%61,%62,%63"
    "}, %64, %65, p, 1, 1, %67, 0;\n}\n"
    : R64(d, 0)
    : "l"(da), "l"(db), "r"(scale_d), "n"(TA));
}
template <int N> __device__ __forceinline__ void fence_regs(float* d) {
#pragma unroll
  for (int i = 0; i < N; i++) asm volatile("" : "+f"(d[i])::"memory");
}
#define PMFENCE() asm volatile("pmevent 0;" ::: "memory")
__device__ __forceinline__ void cmul(float ar, float ai, float br, float bi, float& cr, float& ci) {
  cr = ar * br - ai * bi; ci = ar * bi + ai * br;
}
__device__ __forceinline__ void csq(float& r, float& i) { const float x = fmaf(r, r, -i * i), y = (r + r) * i; r = x; i = y; }

#define W8(d, o) "=f"(d[o]), "=f"(d[o + 1]), "=f"(d[o + 2]), "=f"(d[o + 3]), "=f"(d[o + 4]), "=f"(d[o + 5]), "=f"(d[o + 6]), "=f"(d[o + 7])
#define L16 "{%0,%1,%2,%3,%4,%5,%6,%7,%8,%9,%10,%11,%12,%13,%14,%15}"
#define L32 "{%0,%1,%2,%3,%4,%5,%6,%7,%8,%9,%10,%11,%12,%13,%14,%15,%16,%17,%18,%19,%20,%21,%22,%23,%24,%25,%26,%27,%28,%29,%30,%31}"
template <int ACC, int TB> __device__ __forceinline__ void rs_n32(float* d, const uint32_t* a, uint64_t db) {
  if constexpr (ACC) asm volatile("wgmma.mma_async.sync.aligned.m64n32k16.f32.bf16.bf16 " L16 ", {%16,%17,%18,%19}, %20, 1, 1, 1, %21;" : R16(d, 0) : "r"(a[0]), "r"(a[1]), "r"(a[2]), "r"(a[3]), "l"(db), "n"(TB));
  else asm volatile("wgmma.mma_async.sync.aligned.m64n32k16.f32.bf16.bf16 " L16 ", {%16,%17,%18,%19}, %20, 0, 1, 1, %21;" : W8(d, 0), W8(d, 8) : "r"(a[0]), "r"(a[1]), "r"(a[2]), "r"(a[3]), "l"(db), "n"(TB));
}
template <int ACC, int TB> __device__ __forceinline__ void ss_n64(float* d, uint64_t da, uint64_t db) {
  if constexpr (ACC) asm volatile("wgmma.mma_async.sync.aligned.m64n64k16.f32.bf16.bf16 " L32 ", %32, %33, 1, 1, 1, 0, %34;" : R16(d, 0), R16(d, 16) : "l"(da), "l"(db), "n"(TB));
  else asm volatile("wgmma.mma_async.sync.aligned.m64n64k16.f32.bf16.bf16 " L32 ", %32, %33, 0, 1, 1, 0, %34;" : W8(d, 0), W8(d, 8), W8(d, 16), W8(d, 24) : "l"(da), "l"(db), "n"(TB));
}
template <int ACC> __device__ __forceinline__ void ss_n32_tt(float* d, uint64_t da, uint64_t db) {
  if constexpr (ACC) asm volatile("wgmma.mma_async.sync.aligned.m64n32k16.f32.bf16.bf16 " L16 ", %16, %17, 1, 1, 1, 1, 1;" : R16(d, 0) : "l"(da), "l"(db));
  else asm volatile("wgmma.mma_async.sync.aligned.m64n32k16.f32.bf16.bf16 " L16 ", %16, %17, 0, 1, 1, 1, 1;" : W8(d, 0), W8(d, 8) : "l"(da), "l"(db));
}
__device__ __forceinline__ void stsm4(uint32_t a, uint32_t r0, uint32_t r1, uint32_t r2, uint32_t r3) {
  asm volatile("stmatrix.sync.aligned.m8n8.x4.shared.b16 [%0], {%1,%2,%3,%4};" ::"r"(a), "r"(r0), "r"(r1), "r"(r2), "r"(r3) : "memory");
}
template <int N> __device__ __forceinline__ void fence_u32(uint32_t* d) {
#pragma unroll
  for (int i = 0; i < N; i++) asm volatile("" : "+r"(d[i])::"memory");
}
__device__ __forceinline__ void pack32(uint32_t* f, const float* z) {
#pragma unroll
  for (int i = 0; i < 16; i++) f[i] = pack_bf16(z[2 * i], z[2 * i + 1]);
}
template <int INV> __device__ __forceinline__ void twiddle(uint32_t* f, const uint32_t* tp, const uint32_t* ts) {
#pragma unroll
  for (int i = 0; i < 8; i++) {
    uint32_t x = f[2 * i + INV], y = f[2 * i + 1 - INV];
    x = bfma2(tp[i & 3], y, x); y = bfma2(ts[i & 3], x, y); x = bfma2(tp[i & 3], y, x);
    f[2 * i + INV] = x; f[2 * i + 1 - INV] = y;
  }
}
__device__ __forceinline__ uint32_t bfnma2(uint32_t a, uint32_t b, uint32_t c) { uint32_t r; asm("{\n.reg .b32 t;\nmul.bf16x2 t, %1, %2;\nsub.bf16x2 %0, %3, t;\n}" : "=r"(r) : "r"(a), "r"(b), "r"(c)); return r; }
__device__ __forceinline__ uint32_t bfms2(uint32_t a, uint32_t b, uint32_t c) { uint32_t r; asm("{\n.reg .b32 t;\nmul.bf16x2 t, %1, %2;\nsub.bf16x2 %0, t, %3;\n}" : "=r"(r) : "r"(a), "r"(b), "r"(c)); return r; }
template <int ADD> __device__ __forceinline__ void bimac(uint32_t* o, const uint32_t* a, const uint32_t* b, const uint32_t* c) {
#pragma unroll
  for (int J = 0; J < 2; J++) {
    const uint32_t Pr = a[2 * J], Pi = a[2 * J + 1], Qr = a[2 * J + 4], Qi = a[2 * J + 5], pr = b[2 * J], pi = b[2 * J + 1], qr = b[2 * J + 4], qi = b[2 * J + 5];
    uint32_t x0, x1, x2, x3;
    if (ADD == 0) { x0 = bmul2(Pr, pr); x1 = bmul2(Pr, pi); x2 = bmul2(Pr, qr); x3 = bmul2(Pr, qi); }
    if (ADD == 1) { x0 = bfma2(Pr, pr, c[2 * J]); x1 = bfma2(Pr, pi, c[2 * J + 1]); x2 = bfma2(Pr, qr, c[2 * J + 4]); x3 = bfma2(Pr, qi, c[2 * J + 5]); }
    if (ADD == 2) { x0 = bfma2(Pr, pr, c[2 * J + 1]); x1 = bfms2(Pr, pi, c[2 * J]); x2 = bfma2(Pr, qr, c[2 * J + 5]); x3 = bfms2(Pr, qi, c[2 * J + 4]); }
    x0 = bfnma2(Pi, pi, x0); x1 = bfma2(Pi, pr, x1); x2 = bfnma2(Pi, qi, x2); x3 = bfma2(Pi, qr, x3);
    x0 = bfnma2(Qr, qr, x0); x1 = bfnma2(Qr, qi, x1); x2 = bfma2(Qr, pr, x2); x3 = bfma2(Qr, pi, x3);
    x0 = bfma2(Qi, qi, x0); x1 = bfnma2(Qi, qr, x1); x2 = bfnma2(Qi, pi, x2); x3 = bfma2(Qi, pr, x3);
    o[2 * J] = x0; o[2 * J + 1] = x1; o[2 * J + 4] = x2; o[2 * J + 5] = x3;
  }
}
__device__ __forceinline__ void sincos8k(int n, float& s, float& c) {
  const float x = (float)((n << 19) >> 19) * (6.283185307179586f / 8192.f);
  s = __sinf(x); c = __cosf(x);
}
__device__ __forceinline__ void fft_tables(uint32_t f1a, uint32_t f2a, int w, int lane, uint32_t* tp, uint32_t* ts, float& d0r, float& d0i) {
  const int c = lane & 3, f1 = 8 * w + (lane >> 2);
#pragma unroll 1
  for (int J = 3; J >= 0; J--) {
    const int a = 8 * J + 2 * c;
    float s0, c0, s1, c1;
    sincos8k(64 * (4 * f1 + 1) * a + 31 * (4 * f1 - 63), d0i, d0r); sincos8k(64 * (4 * f1 + 1) * (a + 1) + 31 * (4 * f1 - 63), s1, c1);
    d0r *= 0.125f; d0i *= 0.125f;
    sts32(f1a + w * 1024 + J * 128 + lane * 4, pack_bf16(d0r, 0.125f * c1)); sts32(f1a + w * 1024 + 512 + J * 128 + lane * 4, pack_bf16(d0i, 0.125f * s1));
    sincos8k(128 * (2 * (a & 15) + 1) * f1 - 128 * (a & 16), s0, c0); sincos8k(128 * (2 * (a & 15) + 3) * f1 - 128 * (a & 16), s1, c1);
    sts32(f2a + w * 512 + J * 128 + lane * 4, pack_bf16(c0, c1));
    sincos8k((4 * f1 - 63) * (2 * a - 31), s0, c0); sincos8k((4 * f1 - 63) * (2 * a - 29), s1, c1);
#pragma unroll
    for (int i = 3; i > 0; i--) { ts[i] = ts[i - 1]; tp[i] = tp[i - 1]; }
    ts[0] = pack_bf16(s0, s1); tp[0] = pack_bf16(-__fdividef(s0, 1.f + c0), -__fdividef(s1, 1.f + c1));
  }
  if (c != 0) d0r = d0i = 0.f;
}

template <int SWAPB>
__global__ void __cluster_dims__(2, 1, 1) __launch_bounds__(512, 1)
fused_kernel(const __grid_constant__ Params P, const __grid_constant__ CUtensorMap mX, const __grid_constant__ CUtensorMap mB,
             const __grid_constant__ CUtensorMap mCre, const __grid_constant__ CUtensorMap mCim, const __grid_constant__ CUtensorMap mXs,
             const __grid_constant__ CUtensorMap mK, const __grid_constant__ CUtensorMap mV, const __grid_constant__ CUtensorMap mQ, const __grid_constant__ CUtensorMap mS,
             const __grid_constant__ CUtensorMap mO) {
  extern __shared__ __align__(1024) uint8_t smem_raw[];
  const uint32_t sb = (uint32_t)__cvta_generic_to_shared(smem_raw);
  const uint32_t bars = sb + OFF_BAR;
  const int slot = (P.slot[blockIdx.x >> 3] >> (4 * (blockIdx.x & 6))) & 63, rank = blockIdx.x & 1;
  const int j = slot & 7, tc = 2 * (slot >> 3) + rank, b = 2 * slot + rank;
  const int tid = threadIdx.x;
  const int warp = __shfl_sync(0xffffffffu, tid >> 5, 0);
  const int wg = warp >> 2;
  const uint32_t c_start = clk32();
  auto kblock = [&](int n) { return ((n & 14) == 0 || (n & 14) == 2 * j ? n ^ (2 * j) : n) & 31; };
  auto send_y = [&](int r, int n0 = 0, int n1 = 4) {
    const uint32_t src = sb + OFF_U + 4 * (rank ^ 1) * U_N8 + r * U_CH, dst = r >= 2 ? sb + OFF_U + 4 * rank * U_N8 + (r - 2) * U_CH : sb + OFF_IN + 96 + r * 2064;
#pragma unroll 1
    for (int n = n0; n < n1; n++) bulk_send(dst + n * (r >= 2 ? U_N8 : 512), src + n * U_N8, 512, bars + (B_IN + r) * 8, rank ^ 1);
  };
  auto load_q = [&](int i, int off, int bar) {
    const uint32_t fb = bars + bar * 8 + 4 * (i & 2);
    mbar_expect(fb, 4096); tma4d(sb + off + 2048 * (i & 2), &mQ, 16 * slot, 0, 4 * i, 4 * rank, fb);
  };
  auto head = [&](int n) {
    const uint32_t fb = bars + (B_FULL + n) * 8, dst = sb + OFF_RING + n * STAGE_BYTES;
    mbar_expect(fb, STAGE_BYTES);
    tma4d(dst + 16384, &mX, 64 * n, 0, 4 * tc, 0, fb);
    tma4d(dst, &mB, 64 * n, 0, 0, 8 * j, fb);
    tma4d(dst + 8192, &mB, 64 * n, 0, 0, 8 * j + 4, fb);
  };
  if (warp == 0 && elect_one()) {
    STAMP(0); GSTAMP(0);
#pragma unroll
    for (int s = 0; s < STAGES; s++) mbar_init(bars + (B_FULL + s) * 8, 1);
    head(0);
    STAMP(1);
    asm volatile("fence.mbarrier_init.release.cluster;" ::: "memory");
  }
  if (wg == 3 && elect_one()) {
    if (warp < 15) {
#pragma unroll
      for (int s = 0; s < 11; s++) mbar_init(bars + 8 * B_XI + (warp & 3) * 88 + 8 * s, 1);
    } else {
#pragma unroll
      for (int s = B_EMPTY; s < B_KVE + 3; s++) mbar_init(bars + 8 * s, s < B_PEER ? (SHAKE ? 1 : 2) : s < B_COEF ? (SHAKE == 2 ? 2 : 1) : s == B_COEF ? 128 : 4);
    }
    asm volatile("fence.mbarrier_init.release.cluster;" ::: "memory");
  }
  __syncwarp();
  asm volatile("barrier.cluster.arrive.relaxed.aligned;" ::: "memory");
  if (warp == 0 && elect_one()) {
#pragma unroll 1
    for (int n = 1; n < HEAD; n++) { spin_until(c_start, ST_T0 + n * ST_DELAY); head(n); }
  }
  __syncwarp();
#define CLUSTER_WAIT() asm volatile("barrier.cluster.wait.aligned;" ::: "memory")

  if (wg == 3) {
    asm volatile("setmaxnreg.dec.sync.aligned.u32 24;");
    CLUSTER_WAIT();
    if (warp < 14) {
      if (elect_one()) {
        uint32_t so = 8 * (HEAD % STAGES), ph = HEAD < STAGES;
        auto step = [&](auto issue) {
          mbar_wait(bars + (SHAKE == 2 && warp == 12 ? B_PEER : B_EMPTY) * 8 + so, ph);
          issue(sb + OFF_RING + (so << 12), bars + B_FULL * 8 + so);
          so += 8;
          if (so == 8 * STAGES) { so = 0; ph ^= 1; }
        };
        if (warp == 12) {
          uint64_t pp = 0;
          auto shake = [&](uint32_t fb) {
            if (SHAKE == 1) mbar_arrive_cta(bars + B_PEER * 8 + so, rank ^ 1);
            mbar_expect(fb, STAGE_BYTES);
            if (SHAKE == 1) {
              mbar_wait(bars + B_PEER * 8 + so, (uint32_t)(pp >> so) & 1);
              pp ^= 1ull << so;
            }
          };
          auto g1 = [&](int n0, int n1, int grp) {
#pragma unroll 1
            for (int n = n0; n < n1; n++) step([&](uint32_t dst, uint32_t fb) { shake(fb); tma4d_mc(dst + rank * 8192, &mB, n * 64, 0, 0, grp + 4 * rank, fb); });
          };
#pragma unroll 1
          for (int n = HEAD; n < STAGES; n++) { spin_until(c_start, ST_T0 + n * ST_DELAY); g1(n, n + 1, 8 * j); }
          g1(STAGES, 16, 8 * j);
          g1(0, XPOS - 16, 8 * j + 64);
          step([&](uint32_t dst, uint32_t fb) { mbar_expect(fb, STAGE_BYTES); tma4d(dst, &mXs, 128 * j, 0, 0, 16 * tc, fb); mbar_arrive(bars + B_XI * 8); });
          g1(XPOS - 16, 16, 8 * j + 64);
#pragma unroll 1
          for (int n = 0; n < 32; n += 2) {
            const int col = kblock(n) * 32;
            if (PFC_D && n + PFC_D >= PFC_0 && n + PFC_D < 32 && (PFC_ALL || ((n >> 1) & 7) == (slot >> 3))) {
#pragma unroll
              for (int part = 0; part < 2; part++)
                asm volatile("cp.async.bulk.prefetch.tensor.5d.L2.global [%0, {%1, %2, %2, %2, %3}];" ::"l"(part ? &mCim : &mCre), "r"(kblock(n + PFC_D) * 32), "r"(0), "r"(8 * j + 4 * rank) : "memory");
            }
#pragma unroll
            for (int part = 0; part < 2; part++)
              step([&](uint32_t dst, uint32_t fb) { shake(fb); tma5d_mc(dst + rank * 8192, part ? &mCim : &mCre, col, 0, 0, 0, 8 * j + 4 * rank, fb); });
          }
        } else {
          auto g1 = [&](int n0, int n1, int nb) {
#pragma unroll 1
            for (int n = n0; n < n1; n++) step([&](uint32_t dst, uint32_t fb) { tma4d(dst + 16384, &mX, n * 64, 0, 4 * tc, 0, fb); TSTAMP(1, n + nb); });
          };
          auto g2 = [&](int n0, int n1) {
#pragma unroll 1
            for (int n = n0; n < n1; n++) step([&](uint32_t dst, uint32_t fb) { bulk_load(dst + 16384, g_h + (32 * tc + kblock(n)) * 1024, 16384, fb); TSTAMP(1, n + 32); });
          };
#pragma unroll 1
          for (int n = HEAD; n < STAGES; n++) { spin_until(c_start, ST_T0 + n * ST_DELAY); g1(n, n + 1, 0); }
          g1(STAGES, 16, 0);
          g1(0, XPOS - 16, 16);
          step([&](uint32_t dst, uint32_t fb) { tma4d(dst + 16384, &mXs, 128 * j + 64, 0, 0, 16 * tc, fb); });
          g1(XPOS - 16, 16, 16);
#pragma unroll 1
          for (int v = 0; v < 2; v++) {
            STAMP(4 + v);
            mbar_wait(bars + B_HP * 8, v);
            fence_proxy_async_global();
            STAMP(6 + v);
            g2(16 * v, 16 * v + 2);
            mbar_wait(bars + B_HR * 8, v);
            fence_proxy_async_global();
            g2(16 * v + 2, 16 * v + 16);
          }
        }
      }
    } else if (warp == 15) {
      mbar_wait(bars + B_COEF * 8, 0);
      const unsigned epoch = lds32(bars + B_EPOCH * 8);
#pragma unroll 1
      for (int v = 0; v < 2; v++) {
        unsigned* fp = &g_flagH[(16 * v + tc) * 32];
        bar_sync(4 + v, 160);
        if (elect_one()) {
          red_release(fp, 1);
          mbar_arrive(bars + B_HP * 8);
          STAMP(16 + 10 * v);
          int it = 0;
          while (ld_acquire(fp) != 8 * epoch && ++it < (SPIN_LIMIT << 4)) __nanosleep(POLL_NS);
          STAMP(2 + v);
          mbar_arrive(bars + B_HR * 8);
        }
        __syncwarp();
      }
    } else if (elect_one()) {
      const int ch0 = 16 * slot;
      auto load_k = [&](int s, uint32_t dst) { const uint32_t fb = bars + (B_KF + (s & 1)) * 8; mbar_expect(fb, 4096); tma2d(dst, &mS, 0, 64 * (8 * b + s), fb); };
      prefetch_map(&mS); prefetch_map(&mK); prefetch_map(&mV);
      wait_until(c_start, K_T0);
      load_k(0, sb + OFF_U + (4 * rank + 3) * U_N8); load_k(1, sb + OFF_U + (4 * rank + 3) * U_N8 - 4096);
      {
        uint32_t so = 16, ph = 1;
#pragma unroll 1
        for (int e = 0; e < 9; e++) {
          const uint32_t fb = bars + B_KVF * 8 + so, dst = sb + OFF_KV + (so << 10);
          wait_until(c_start, KV_T0 + (e ? 2 * e - 1 : 0) * KV_DT);
          mbar_wait(bars + B_KVE * 8 + so, ph);
          const uint32_t c1 = clk32();
          mbar_expect(fb, e ? 8192 : 4096);
          if (e > 0) KSTAMP(1, e - 1);
          tma3d(dst, &mK, ch0, 32 * rank - (e == 0), (4 * e - 4) & 31, fb);
          if (e > 0) { wait_until(c1, KV_DV); tma3d(dst + 4096, &mV, ch0, 32 * rank, 4 * e - 4, fb); }
          so += 8;
          if (so == 24) so = 0;
          if (so == 16) ph ^= 1;
        }
      }
      prefetch_map(&mCre); prefetch_map(&mCim); prefetch_map(&mXs); prefetch_map(&mQ); prefetch_map(&mO);
      mbar_wait(bars + B_KVE * 8, 0);
      load_k(2, sb + OFF_K); load_k(3, sb + OFF_K + 4096);
      mbar_wait(bars + (B_UF + 3) * 8, 0);
#pragma unroll 1
      for (int ch = 0; ch < 8; ch++) {
        if (ch > 0) {
          mbar_wait(bars + (B_Y + (ch & 3)) * 8, ch >> 2);
          if (ch > 2) mbar_wait(bars + (B_IN + ch - 3) * 8, 0);
          send_y(ch - 1);
        }
        if (ch < 6) {
          mbar_wait(bars + (B_KE + (ch & 1)) * 8, (ch >> 1) & 1);
          if (ch < 4) load_k(ch + 4, sb + OFF_K + (ch & 1) * 4096);
          if (ch >= 2) load_q(2 * (ch & 1) + (ch < 4), ch < 4 ? OFF_Q : OFF_K, ch < 4 ? B_QF : B_KF);
        }
      }
    }
    return;
  } else if (wg == 2) {
    asm volatile("setmaxnreg.inc.sync.aligned.u32 %0;" ::"n"(488 - 2 * GREG));
    const int t = tid & 127, w = warp & 3, lane = t & 31, g = lane >> 2, c = lane & 3;
    const uint4 s2[2] = {ldg128_nc(P.shift_k + (8 * b + 2 * c) * 4), ldg128_nc(P.shift_k + (8 * (b ^ 1) + 2 * c) * 4)};
    const uint32_t dskip = __bfloat16_as_ushort(P.ssm_D[8 * b + (t & 7)]);
    uint32_t tp[4] = {}, ts[4] = {};
    float d0r, d0i;
    fft_tables(sb + OFF_F1, sb + OFF_F2, w, lane, tp, ts, d0r, d0i);
    if (t == 0) STAMP(19);
    CLUSTER_WAIT();
    if (t < 12) mbar_expect(bars + (B_IN + t) * 8, t < 8 ? 2048 : U_N8);
    if (t < 8) sts32(sb + OFF_D + 4 * t, dskip << 16);
    const uint64_t dF1a = make_desc(sb + OFF_F1, 128, 512, 0), dF1b = make_desc(sb + OFF_F1, 512, 128, 0);
    const uint64_t dF2f = make_desc(sb + OFF_F2, 512, 128, 0), dF2i = make_desc(sb + OFF_F2, 128, 512, 0);
    auto T1k = [&](float* z, uint64_t dk) { wg_fence(); ss_n64<0, 1>(z, dF1a, dk); ss_n64<1, 1>(z, dF1a + 16, dk + 64); wg_commit(); };
    auto T1u = [&](float* z, uint64_t du) { wg_fence(); ss_n64<0, 0>(z, dF1a, du); ss_n64<1, 0>(z, dF1a + 16, du + 16); wg_commit(); };
    auto T2 = [&](float* s, const uint32_t* f) {
      wg_fence();
      rs_n32<0, 1>(s, f, dF2f); rs_n32<0, 1>(s + 16, f + 8, dF2f); rs_n32<1, 1>(s, f + 4, dF2f + 64); rs_n32<1, 1>(s + 16, f + 12, dF2f + 64);
      wg_commit();
    };
    auto product = [&](uint32_t* pr, const uint32_t* kh, const uint32_t* uh) {
      bimac<0>(pr, kh, uh, pr); bimac<2>(pr + 8, kh + 8, uh, pr); bimac<1>(pr + 8, kh, uh + 8, pr + 8);
      fence_u32<16>(pr);
    };
    float zk[32] = {};
    uint32_t pr[16];
    {
      uint32_t kh0[16];
      {
        float z0[32], sk[32];
        uint32_t fk[16];
        const uint64_t dk = make_desc(sb + OFF_U + (4 * rank + 3) * U_N8, 2048, 512, 2);
        fence_proxy_async_smem();
        bar_sync(7, 128);
        mbar_wait(bars + B_KF * 8, 0);
        T1k(z0, dk);
        mbar_wait(bars + (B_KF + 1) * 8, 0);
        T1k(zk, dk - 256);
        wg_wait<0>(); fence_regs<32>(z0); fence_regs<32>(zk);
        const float dd = __uint_as_float(lds32(sb + OFF_D));
        z0[0] = fmaf(d0r, dd, z0[0]); z0[2] = fmaf(d0i, dd, z0[2]);
        pack32(fk, z0); twiddle<0>(fk, tp, ts); fence_u32<16>(fk);
        T2(sk, fk);
        wg_wait<0>(); fence_regs<32>(sk); fence_u32<16>(fk);
        pack32(kh0, sk); fence_u32<16>(kh0);
      }
      {
        uint32_t sk[2][4], kx[2][8];
#pragma unroll
        for (int o = 0; o < 2; o++) {
          sk[o][0] = __byte_perm(s2[o].x, s2[o].z, 0x5410); sk[o][1] = __byte_perm(s2[o].x, s2[o].z, 0x7632);
          sk[o][2] = __byte_perm(s2[o].y, s2[o].w, 0x5410); sk[o][3] = __byte_perm(s2[o].y, s2[o].w, 0x7632);
        }
        const uint32_t la = sb + OFF_KV + (lane >> 3) * 1024 + (8 * w + (lane & 7)) * 32 + ((rank ^ ((lane >> 2) & 1)) << 4);
        const uint32_t uo = (lane & 7) * U_CH + w * 128 + (lane >> 3) * 16;
        mbar_wait(bars + (B_KVF + 2) * 8, 0);
        if (t == 0) STAMP(27);
        ldsm4(kx[0], la + 16384); ldsm4(kx[1], (la ^ 16) + 16384);
        if (lane == 0) mbar_arrive(bars + (B_KVE + 2) * 8 + (kx[0][1] & kx[1][1] & P.zero));
        uint32_t so = 0, ph = 0;
#pragma unroll 1
        for (int n = 0; n < 4; n++) {
          const uint32_t own = sb + OFF_U + (4 * rank + n) * U_N8, box = n < 3 ? sb + OFF_U + (4 * (rank ^ 1) + n + 1) * U_N8 : sb + OFF_IN;
#pragma unroll
          for (int e = 0; e < 2; e++) {
            uint32_t vx[2][4];
            mbar_wait(bars + B_KVF * 8 + so, ph);
            if (t == 0) KSTAMP(2, 2 * n + e);
#pragma unroll
            for (int o = 0; o < 2; o++) { ldsm4(kx[o] + 4, (la ^ (16 * o)) + (so << 10)); ldsm4(vx[o], (la ^ (16 * o)) + (so << 10) + 4096); }
            if (lane == 0) mbar_arrive(bars + B_KVE * 8 + so + (kx[0][4] & kx[1][4] & vx[0][0] & vx[1][0] & P.zero));
#pragma unroll
            for (int o = 0; o < 2; o++) {
#pragma unroll
              for (int i = 0; i < 4; i++) vx[o][i] = bmul2(bfma2(kx[o][i + 4], sk[o][0], bfma2(kx[o][i + 3], sk[o][1], bfma2(kx[o][i + 2], sk[o][2], bmul2(kx[o][i + 1], sk[o][3])))), vx[o][i]);
              stsm4t((o ? box : own) + uo + e * 64, vx[o][0], vx[o][1], vx[o][2], vx[o][3]);
              kx[o][1] = kx[o][5]; kx[o][2] = kx[o][6]; kx[o][3] = kx[o][7];
            }
            if (t == 0) KSTAMP(3, 2 * n + e);
            so += 8;
            if (so == 24) so = 0;
            if (so == 16) ph ^= 1;
          }
          fence_proxy_async_smem();
          bar_sync(7, 128);
          if (w == 0 && elect_one()) {
            if (n > 0) mbar_wait(bars + B_UF * 8 + 8 * (n - 1), 0);
            bulk_send(own, box, U_N8, bars + B_UF * 8 + 8 * n, rank ^ 1);
          }
          __syncwarp();
        }
        if (t == 0) STAMP(28);
      }
      float zu[32], su[32];
      uint32_t fu[16], uh[16];
#pragma unroll
      for (int n = 0; n < 4; n++) mbar_wait(bars + (B_UF + n) * 8, 0);
      T1u(zu, make_desc(sb + OFF_U, 128, U_N8, 0));
      wg_wait<0>(); fence_regs<32>(zu);
      pack32(fu, zu); twiddle<0>(fu, tp, ts); fence_u32<16>(fu);
      T2(su, fu);
      wg_wait<0>(); fence_regs<32>(su); fence_u32<16>(fu);
      pack32(uh, su);
      product(pr, kh0, uh);
      if (t == 0) STAMP(54);
    }
    {
#define CF(i) do { if ((CFM >> (i)) & 1) PMFENCE(); } while (0)
#define CP(i)
      const uint32_t vs = w < 2 ? 512 : U_N8;
      uint32_t va = (w < 2 ? sb + OFF_VP : sb + OFF_U) + ((lane >> 4) & 1) * vs + (w & 1) * 256 + (lane & 15) * 16;
      uint32_t ya = sb + OFF_U + (2 * w + ((lane >> 3) & 1)) * U_N8 + (lane >> 4) * 128 + (lane & 7) * 16;
      uint64_t du = make_desc(sb + OFF_U, 128, U_N8, 0), dk = make_desc(sb + OFF_K, 2048, 512, 2);
      const uint64_t dv = make_desc(sb + OFF_VP, 128, 512, 0);
      uint32_t yp[8] = {};
      uint32_t yq = sb + OFF_Q + lane * 16;
      auto store_y = [&]() { stsm4(yq, yp[0], yp[1], yp[2], yp[3]); stsm4(yq + 256, yp[4], yp[5], yp[6], yp[7]); };
      auto step = [&](int ch, auto fwd) {
        constexpr bool FWD = decltype(fwd)::value;
        float zu[32], sk[32], su[32], v[32], y[16];
        uint32_t kh[16], uh[16], fk[16], fu[16], fv[16];
        CP(16);
        wg_fence();
        rs_n32<0, 0>(v, pr, dF2i); rs_n32<0, 0>(v + 16, pr + 8, dF2i); rs_n32<1, 0>(v, pr + 4, dF2i + 16); rs_n32<1, 0>(v + 16, pr + 12, dF2i + 16);
        wg_commit();
        CF(0);
        store_y();
        if (FWD) {
          const float dd = __uint_as_float(lds32(sb + OFF_D + 4 * (ch + 1)));
          zk[0] = fmaf(d0r, dd, zk[0]); zk[2] = fmaf(d0i, dd, zk[2]);
          pack32(fk, zk); twiddle<0>(fk, tp, ts); fence_u32<16>(fk);
          CP(1);
          T2(sk, fk);
          CF(2);
          mbar_wait(bars + (B_KF + (ch & 1)) * 8, ((ch >> 1) & 1) ^ 1);
          wg_wait<1>();
        } else wg_wait<0>();
        fence_regs<32>(v); fence_u32<16>(pr); CP(3);
        pack32(fv, v); fence_u32<16>(fv);
        CF(4);
        if (FWD) T1u(zu, du + U_CH / 16);
        CF(5);
        twiddle<1>(fv, tp, ts);
#pragma unroll
        for (int i = 0; i < 4; i++) stsm4(va + 2 * i * vs, fv[4 * i], fv[4 * i + 1], fv[4 * i + 2], fv[4 * i + 3]);
        if (FWD) {
          CF(6);
          wg_wait<1>(); fence_regs<32>(sk); fence_u32<16>(fk);
          pack32(kh, sk); fence_u32<16>(kh);
          CF(7);
          T1k(zk, dk);
          CF(8);
          wg_wait<1>(); fence_regs<32>(zu);
          pack32(fu, zu); twiddle<0>(fu, tp, ts); fence_u32<16>(fu);
          CP(9);
          T2(su, fu);
          CF(10);
        }
        fence_proxy_async_smem();
        bar_sync(7, 128);
        wg_fence(); CP(11);
        ss_n32_tt<0>(y, dv, dF1b); ss_n32_tt<1>(y, dv + 16, dF1b + 64); ss_n32_tt<1>(y, du, dF1b + 128); ss_n32_tt<1>(y, du + 16, dF1b + 192);
        wg_commit();
        if (t == 0) mbar_arrive(bars + (B_Y + (ch & 3)) * 8);
        CF(12);
        if (FWD) {
          wg_wait<1>(); fence_regs<32>(su); fence_u32<16>(fu); fence_regs<32>(zk); CP(13);
          if (t == 0) mbar_arrive(bars + (B_KE + (ch & 1)) * 8);
          pack32(uh, su);
          product(pr, kh, uh);
          du += U_CH / 16; dk += (ch & 1) ? -256 : 256;
          if (w >= 2) va += U_CH;
        }
        CF(14);
        wg_wait<0>(); fence_regs<16>(y); CP(15);
#pragma unroll
        for (int i = 0; i < 8; i++) yp[i] = pack_bf16(y[2 * i], y[2 * i + 1]);
        fence_u32<8>(yp);
        yq = ya;
        ya += U_CH; CP(17);
        if (t == 0) STAMP(55 + ch);
      };
#pragma unroll 1
      for (int ch = 0; ch < 7; ch++) step(ch, std::true_type());
      step(7, std::false_type());
      store_y();
    }
    fence_proxy_async_smem();
    bar_sync(9, 256);
    if (t == 0) STAMP(29);
  } else {
    asm volatile("setmaxnreg.inc.sync.aligned.u32 %0;" ::"n"(GREG));
    const int t = tid & 127, w = warp & 3, lane = t & 31, g = lane >> 2, c = lane & 3;
    if (wg == 1) {
      wait_until(c_start, COEF_T0);
      const int p = 64 * j + (t & 63) + 8 * (t & 64);
      const float Lr = bf2f(P.lam_re[p]), Li = bf2f(P.lam_im[p]);
      const uint32_t ds = __bfloat16_as_ushort(P.Dskip[128 * j + t]);
      const unsigned epoch = ld_relaxed(&g_epoch[b * 32]) + 1;
      const float dt = bf2f(__float2bfloat16_rn(expf(bf2f(P.log_dt[p]))));
      const float e = expf(dt * Lr);
      float sn, cs;
      {
        const double z = (double)(dt * Li) * 0.15915494309189535;
        sincospif(2.f * (float)(z - rint(z)), &sn, &cs);
      }
      const float lr = e * cs, li = e * sn;
      const float nr = lr - 1.0f, ni = li;
      const bool big = fabsf(Lr) >= fabsf(Li);
      const float la = big ? Lr : Li, lb = big ? Li : Lr, r = __fdiv_rn(lb, la), inv = __frcp_rn(fmaf(lb, r, la));
      const float br = (big ? fmaf(ni, r, nr) : fmaf(nr, r, ni)) * inv, bi = (big ? fmaf(-nr, r, ni) : fmaf(ni, r, -nr)) * inv;
      sts128(sb + OFF_COEF + t * 16, make_uint4(__float_as_uint(lr), __float_as_uint(li), __float_as_uint(2.f * br), __float_as_uint(-2.f * bi)));
      sts32(sb + OFF_DS + 4 * t, ds << 16);
      if (t == 0) sts32(bars + B_EPOCH * 8, epoch);
      if (t == 0) STAMP(52);
    }
    CLUSTER_WAIT();
    if (wg == 1) mbar_arrive(bars + B_COEF * 8);
    float d[128];
    uint32_t so = 0, ph = 0, po = 0;
    uint32_t ra;
    auto set_ra = [&]() { asm volatile("mapa.shared::cluster.u32 %0, %1, %2;" : "=r"(ra) : "r"(bars + (SHAKE == 2 && (t & 3) != 2 ? B_PEER : B_EMPTY) * 8), "r"((t & 1) ? rank ^ 1 : rank)); };
    set_ra();
    auto release_at = [&](uint32_t off, bool skip) {
      asm volatile("{\n.reg .pred p;\nsetp.lt.u32 p, %1, %2;\n@p mbarrier.arrive.shared::cluster.b64 _, [%0];\n}\n" ::"r"(ra + off), "r"(t), "r"(skip ? 0 : SHAKE == 2 ? 3 : SHAKE == 1 ? 1 : 2) : "memory");
    };
    auto release = [&](bool first) { release_at(po, first); };
    auto block = [&](auto ta, uint64_t da0, uint64_t db0, bool first, bool zero, int nn) {
      constexpr int PH = decltype(ta)::value, TA = PH > 0, KS = TA ? 128 : 2, QD = PH == 0 ? QD1 : PH == 1 ? QD2 : QD3;
      if (t == 0) TSTAMP(2, nn);
      mbar_wait(bars + B_FULL * 8 + so, ph);
      if (t == 0) TSTAMP(3, nn);
      const uint64_t da = da0 + (so << 8), db = db0 + (so << 8);
      wg_fence();
      wgmma_n128<TA>(d, da, db, !zero);
      wgmma_n128<TA>(d + 64, da + 512, db, !zero);
      wg_commit();
      wg_wait<1>();
      if (RELPOS == 0) release(first);
#pragma unroll
      for (int k = 1; k < 4; k++) {
        if (QD == 2 || (QD == 4 && k == 2)) wg_fence();
        wgmma_n128<TA>(d, da + KS * k, db + 2 * k, 1);
        wgmma_n128<TA>(d + 64, da + 512 + KS * k, db + 2 * k, 1);
        if (QD == 2 || (QD == 4 && k == 1)) wg_commit();
        if (RELPOS == 1 && k == 1) release(first);
        if ((QD == 2 && k < 3) || (QD == 4 && k == 1)) wg_wait<1>();
      }
      if (QD != 2) wg_commit();
      if (RELPOS == 2) release(first);
      po = so;
      so += 8;
      if (so == 8 * STAGES) { so = 0; ph ^= 1; }
    };
    {
      so = wg ? 8 * (16 % STAGES) : 0; ph = wg ? (16 / STAGES) & 1 : 0; po = 0;
      const uint64_t da0 = make_desc(sb + OFF_RING, 16, 1024, 1), db0 = make_desc(sb + OFF_RING + 16384, 16, 1024, 1);
      if (wg == 1) bar_sync(1, 256);
#pragma unroll 1
      for (int kb = 0; kb < 16; kb++) {
        if (16 * wg + kb == XPOS) { so += 8; if (so == 8 * STAGES) { so = 0; ph ^= 1; } }
        block(std::integral_constant<int, 0>(), da0, db0, kb == 0, kb == 0, 16 * wg + kb);
      }
      asm volatile("bar.arrive %0, 256;" ::"r"(1 + wg) : "memory");
    }
    mbar_wait(bars + B_COEF * 8, 0);
    const uint32_t ca = sb + OFF_COEF + (64 * wg + 8 * w + g) * 16;
    const uint32_t tag = __shfl_sync(0xffffffffu, lds32(bars + B_EPOCH * 8) & 3, 0);
    constexpr int RE = SWAPB ? 2 : 0, IM = 2 - RE;
    uint2* cp = &g_carry[((16 * wg + 2 * j) * 16 + tc) * 32 + 8 * w];
    const int ct = lane >> 3;
    uint2 cv[4];
    auto load_carry = [&](int i) {
#pragma unroll
      for (int m = 0; m < 4; m++)
        asm volatile("{\n.reg .pred p;\n.reg .b64 v;\nsetp.lt.s32 p, %3, %4;\nmov.b64 v, {%0,%1};\n@p ld.relaxed.gpu.global.b64 v, [%2];\nmov.b64 {%0,%1}, v;\n}\n"
                     : "+r"(cv[m].x), "+r"(cv[m].y) : "l"(cp + 512 * i + (lane & 7) - 32 * (1 + ct) - 128 * m), "r"(ct), "r"(tc - 4 * m) : "memory");
    };
    auto first_load = [&](int i) {
#pragma unroll
      for (int m = 0; m < 4; m++) cv[m] = make_uint2(tag, 0);
      load_carry(i);
    };
    float lr[2], li[2], pr[2], pi[2], wr[2], wi[2], vr[2], vi[2], qr[2], qi[2], er[2], ei[2], gr[2], gi[2];
    auto powers = [&](int i) {
      const uint2 cf = lds64(ca + 512 * i);
      pr[i] = lr[i] = __uint_as_float(cf.x); pi[i] = li[i] = __uint_as_float(cf.y);
#pragma unroll
      for (int s = 0; s < 4; s++) csq(pr[i], pi[i]);
      gr[i] = pr[i]; gi[i] = pi[i];
      csq(pr[i], pi[i]);
      qr[i] = pr[i]; qi[i] = pi[i];
      csq(qr[i], qi[i]);
      er[i] = qr[i]; ei[i] = qi[i];
      wr[i] = (c & 1) ? pr[i] : 1.f; wi[i] = (c & 1) ? pi[i] : 0.f;
      if (c & 2) { float x, y; cmul(wr[i], wi[i], qr[i], qi[i], x, y); wr[i] = x; wi[i] = y; }
      vr[i] = wr[i]; vi[i] = wi[i];
      csq(vr[i], vi[i]); csq(vr[i], vi[i]);
      csq(qr[i], qi[i]); csq(qr[i], qi[i]); csq(qr[i], qi[i]);
      const int src = 4 * (lane & 7) + ct;
      vr[i] = __shfl_sync(0xffffffffu, vr[i], src); vi[i] = __shfl_sync(0xffffffffu, vi[i], src);
      qr[i] = __shfl_sync(0xffffffffu, qr[i], src); qi[i] = __shfl_sync(0xffffffffu, qi[i], src);
      asm volatile("" : "+f"(wr[i]), "+f"(wi[i]), "+f"(pr[i]), "+f"(pi[i]), "+f"(er[i]), "+f"(ei[i]));
    };
    powers(0);
    if (POW2 == 0) powers(1);
    PMFENCE();
    wg_wait<0>();
    fence_regs<128>(d);
    release(false);
    if (t == 0) STAMP(10 + 10 * wg);
#pragma unroll
    for (int i = 0; i < 2; i++) {
      const float* e = d + 64 * i;
      auto chain = [&](int s0, int s1, float& sr, float& si) {
        sr = e[2 * s0 + RE]; si = e[2 * s0 + IM];
#pragma unroll
        for (int s = s0 + 1; s < s1; s++) {
          const int ia = 4 * (s >> 1) + (s & 1);
          const float nr = fmaf(-li[i], si, fmaf(lr[i], sr, e[ia + RE])), ni = fmaf(li[i], sr, fmaf(lr[i], si, e[ia + IM]));
          sr = nr; si = ni;
        }
      };
      float sr, si;
      if (POW2 == 1 && i == 1) powers(1);
      if ((GREEDY >> i) & 1) {
        float ar, ai;
        chain(0, 16, ar, ai); chain(16, 32, sr, si);
        sr = fmaf(gr[i], ar, fmaf(-gi[i], ai, sr)); si = fmaf(gr[i], ai, fmaf(gi[i], ar, si));
      } else chain(0, 32, sr, si);
      if (i == 1 && C_AT == 0) { asm volatile("pmevent 0;" : "+f"(sr), "+f"(si)::"memory"); first_load(0); }
      float ur = __shfl_up_sync(0xffffffffu, sr, 1, 4), ui = __shfl_up_sync(0xffffffffu, si, 1, 4);
      if (c >= 1) { sr = fmaf(pr[i], ur, fmaf(-pi[i], ui, sr)); si = fmaf(pr[i], ui, fmaf(pi[i], ur, si)); }
      ur = __shfl_up_sync(0xffffffffu, sr, 2, 4); ui = __shfl_up_sync(0xffffffffu, si, 2, 4);
      if (c >= 2) { sr = fmaf(er[i], ur, fmaf(-ei[i], ui, sr)); si = fmaf(er[i], ui, fmaf(ei[i], ur, si)); }
      if (c == 3 && tc < 15)
        asm volatile("{\n.reg .b64 v;\nmov.b64 v, {%1,%2};\nst.relaxed.gpu.global.b64 [%0], v;\n}\n" ::"l"(cp + 512 * i + g), "r"((__float_as_uint(sr) & ~3u) | tag), "r"(__float_as_uint(si)) : "memory");
      if (i == 1 && C_AT == 1) first_load(0);
      PMFENCE();
      if (t == 0) STAMP(11 + i + 10 * wg);
      er[i] = __shfl_up_sync(0xffffffffu, sr, 1, 4); ei[i] = __shfl_up_sync(0xffffffffu, si, 1, 4);
      if (c == 0) er[i] = ei[i] = 0.f;
    }
    uint4* hp = g_h + (32 * tc + 16 * wg + 2 * j) * 1024 + 64 * w + 4 * g + (c ^ (g >> 1));
#pragma unroll
    for (int i = 0; i < 2; i++) {
      float* e = d + 64 * i;
      const uint2 cf = lds64(ca + 512 * i + 8);
      const float mr = __uint_as_float(cf.x), mi = __uint_as_float(cf.y);
      const uint32_t gp = pack_bf16(mr, mr), gms = pack_bf16(mi, mi);
      const int NS = i == 0 ? PRE_S : 0;
#pragma unroll
      for (int s = 32 - 8 * NS; s < 32; s++) {
        const int ia = 4 * (s >> 1) + (s & 1);
        asm volatile("{\n.reg .f32 u, v, n;\nmul.f32 u, %3, %1;\nmul.f32 v, %3, %0;\nneg.f32 n, %2;\nfma.rn.f32 %0, %2, %0, u;\nfma.rn.f32 %1, n, %1, v;\n}\n"
                     : "+f"(e[ia + RE]), "+f"(e[ia + IM]) : "f"(mr), "f"(mi));
        if (s % PRE_G == PRE_G - 1) PMFENCE();
      }
      PMFENCE();
      int n = 0;
#pragma unroll 1
      while (!__all_sync(0xffffffffu, (((cv[0].x ^ tag) | (cv[1].x ^ tag) | (cv[2].x ^ tag) | (cv[3].x ^ tag)) & 3) == 0) && ++n <= (SPIN_LIMIT << 4)) load_carry(i);
      if (t == 0 && i == 0) STAMP(13 + 10 * wg);
      float hr = __uint_as_float(cv[3].x), hi = __uint_as_float(cv[3].y);
#pragma unroll
      for (int m = 2; m >= 0; m--) {
        const float nr = fmaf(qr[i], hr, fmaf(-qi[i], hi, __uint_as_float(cv[m].x))), ni = fmaf(qr[i], hi, fmaf(qi[i], hr, __uint_as_float(cv[m].y)));
        hr = nr; hi = ni;
      }
      { float x, y; cmul(hr, hi, vr[i], vi[i], x, y); hr = x; hi = y; }
      hr += __shfl_xor_sync(0xffffffffu, hr, 8); hi += __shfl_xor_sync(0xffffffffu, hi, 8);
      hr = __shfl_sync(0xffffffffu, hr, g) + __shfl_sync(0xffffffffu, hr, g + 16); hi = __shfl_sync(0xffffffffu, hi, g) + __shfl_sync(0xffffffffu, hi, g + 16);
      float sr = fmaf(wr[i], hr, fmaf(-wi[i], hi, er[i])), si = fmaf(wr[i], hi, fmaf(wi[i], hr, ei[i]));
      if (t == 0 && i == 0) STAMP(14 + 10 * wg);
#pragma unroll
      for (int i8 = 0; i8 < 4; i8++) {
        const bool pre = i8 >= 4 - NS;
        if (i8 == 4 - NS) { const float x = sr; sr = fmaf(mr, x, mi * si); si = fmaf(-mr, si, mi * x); }
        asm volatile("pmevent 0;" : "+f"(sr), "+f"(si)::"memory");
        if (i == 0 && i8 == C_AT2) first_load(1);
        const float ls = pre ? -li[i] : li[i];
#pragma unroll
        for (int s = 8 * i8; s < 8 * i8 + 8; s++) {
          const int ia = 4 * (s >> 1) + (s & 1);
          const float nr = fmaf(-ls, si, fmaf(lr[i], sr, e[ia + RE])), ni = fmaf(ls, sr, fmaf(lr[i], si, e[ia + IM]));
          sr = nr; si = ni;
          e[ia + RE] = nr; e[ia + IM] = ni;
        }
        if (P2_SPLIT) PMFENCE();
        uint32_t hp0[4], hp1[4];
#pragma unroll
        for (int m = 0; m < 4; m++) {
          const float* f = e + 16 * i8 + 4 * m;
          const uint32_t x = pack_bf16(f[RE], f[RE + 1]), y = pack_bf16(f[IM], f[IM + 1]);
          hp0[m] = pre ? x : bfma2(gp, x, bmul2(gms, y)); hp1[m] = pre ? y : bfnma2(gp, y, bmul2(gms, x));
        }
        uint4* o = hp + 512 * (i8 >> 1) + 256 * i + 32 * (i8 & 1);
        stg128(o, make_uint4(hp0[0], hp0[1], hp0[2], hp0[3]));
        stg128(o + 1024, make_uint4(hp1[0], hp1[1], hp1[2], hp1[3]));
      }
    }
    if (t == 0) STAMP(15 + 10 * wg);
    const int trow = 128 * tc + 64 * (w & 1) + 8 * (w >> 1) + g;
    const int dcol = 128 * j + 4 * c;
    asm volatile("bar.arrive %0, 160;" ::"r"(4 + wg) : "memory");
    if (wg == 0) {
      set_ra();
      uint2 xv[32];
      {
        const int gp = 2 * (g & 3) + (g >> 2);
        const uint32_t xa = sb + OFF_RING + (XPOS % STAGES) * STAGE_BYTES + (64 * (w & 1) + 8 * (w >> 1) + gp) * 128 + (c & 1) * 8;
        mbar_wait(bars + B_XI * 8, 0);
        mbar_wait(bars + (B_FULL + XPOS % STAGES) * 8, (XPOS / STAGES) & 1);
        if (t == 0) STAMP(18);
#pragma unroll
        for (int u = 0; u < 32; u++) {
          const int J = (u >> 1) & 7;
          if (X_NOXI) xv[u] = make_uint2(0, 0); else
          asm volatile("ld.shared.v2.u32 {%0,%1}, [%2];" : "=r"(xv[u].x), "=r"(xv[u].y) : "r"(xa + (J >> 2) * 16384 + (u >> 4) * 2048 + (u & 1) * 4096 + (((2 * (J & 3) + (c >> 1)) ^ gp) << 4)) : "memory");
        }
        uint32_t dep = P.zero;
#pragma unroll
        for (int u = 0; u < 32; u++) dep &= xv[u].x;
        bar_sync(3 + dep, 128);
        release_at(8 * (XPOS % STAGES), false);
      }
#pragma unroll
      for (int J = 0; J < (X_NOXI ? 0 : 8); J++) {
        const uint4 ds = lds128(sb + OFF_DS + 16 * c + 64 * J);
#pragma unroll
        for (int r = 0; r < 4; r++) {
          const int u = 16 * (r >> 1) + 2 * J + (r & 1);
          float* e = d + 8 * (u >> 1) + 2 * (u & 1);
          e[0] = __uint_as_float(bfma2(blo2(xv[u].x), ds.x, 0)); e[1] = __uint_as_float(bfma2(xv[u].x, ds.y, 0));
          e[4] = __uint_as_float(bfma2(blo2(xv[u].y), ds.z, 0)); e[5] = __uint_as_float(bfma2(xv[u].y, ds.w, 0));
        }
      }
      fence_regs<128>(d);
      if (t == 0) STAMP(17);
      so = 8 * (33 % STAGES); ph = (33 / STAGES) & 1;
      const uint64_t da0 = make_desc(sb + OFF_RING + 16384, 512, 1024, 2), db0 = make_desc(sb + OFF_RING, 16, 1024, 1);
      bar_sync(2, 256);
#pragma unroll 1
      for (int kb = 0; kb < QSW; kb++) block(std::integral_constant<int, 1>(), da0, db0, kb == 0, false, 32 + kb);
#pragma unroll 1
      for (int kb = QSW; kb < 32 - TAILB; kb++) block(std::integral_constant<int, 2>(), da0, db0, false, false, 32 + kb);
      float* op = P.out + (size_t)trow * 2048 + 1024 + dcol;
      auto mma = [&](int i, int kb, int k0, int k1) {
        const int s = (33 + kb) % STAGES;
        wg_fence();
#pragma unroll
        for (int k = k0; k < k1; k++) wgmma_n128<1>(d + 64 * i, da0 + s * 2048 + 512 * i + 128 * k, db0 + (i ? 0 : P.zero) + s * 2048 + 2 * k, 1);
        wg_commit();
      };
      auto store = [&](int i, int J0, int J1) {
#pragma unroll
        for (int J = J0; J < J1; J++) {
#pragma unroll
          for (int h = 0; h < 2; h++) {
            const float* e = d + 64 * i + 8 * J + 2 * h;
            stg128(op + (size_t)(16 * i + 32 * h) * 2048 + 16 * J, make_uint4(__float_as_uint(e[0]), __float_as_uint(e[1]), __float_as_uint(e[4]), __float_as_uint(e[5])));
          }
        }
        PMFENCE();
      };
      constexpr int K0 = 32 - TAILB;
#pragma unroll
      for (int kb = K0; kb < 32; kb++) {
        mbar_wait(bars + (B_FULL + (33 + kb) % STAGES) * 8, ((33 + kb) / STAGES) & 1);
        if (TAILB == 5 && kb == K0) { mma(0, kb, 0, 2); wg_wait<1>(); release(false); mma(0, kb, 2, 4); }
        else mma(0, kb, 0, 4);
      }
      mma(1, K0, 0, 4);
      wg_wait<1>();
      fence_regs<64>(d);
      if (t == 0) STAMP(48);
#pragma unroll
      for (int kb = K0 + 1; kb < 32; kb++) {
        mma(1, kb, 0, 4);
        if (T_FENCE) PMFENCE();
        store(0, T_ST * (kb - K0 - 1), kb == 31 ? 8 : T_ST * (kb - K0));
      }
      if (t == 0) STAMP(49);
      wg_wait<0>();
      fence_regs<64>(d + 64);
      if (t == 0) STAMP(50);
      store(1, 0, 8);
      if (t == 0) { STAMP(51); GSTAMP(51); }
      if (t == 0) g_epoch[b * 32] = lds32(bars + B_EPOCH * 8);
      return;
    }
    asm volatile("setmaxnreg.dec.sync.aligned.u32 %0;" ::"n"(488 - 2 * GREG));
  }
  {
    int lane;
    asm volatile("mov.u32 %0, %%laneid;" : "=r"(lane));
    const int w = warp & 3, h = wg & 1;
    const int lc = 2 * (lane & 2) + (lane & 1) + ((lane >> 2) & 2);
    const bool own = ((lane >> 2) & 1) == rank, spare = !own && lc < 2;
    const uint32_t ya = (spare ? sb + OFF_IN + 96 + lc * 2064 : sb + OFF_U + (own ? 4 * rank * U_N8 : 4 * (rank ^ 1) * U_N8 - 2 * U_CH) + lc * U_CH) + w * 128 + (lane >> 4) * 16 + h * 64;
    const uint32_t ys = spare ? 512 : U_N8;
    const uint32_t ob0 = sb + (h ? OFF_F1 : OFF_K) + 1024 * w, ob1 = sb + (h ? OFF_VP : OFF_K + 4096) + 1024 * w;
    uint32_t y[2][8];
    uint2 q[4][4];
    auto get_q = [&](int n, int off, int bar, int ph) {
#pragma unroll
      for (int u = 0; u < 2; u++) {
        mbar_wait(bars + (bar + u) * 8, ph);
#pragma unroll
        for (int r = 0; r < 4; r++) q[n + u][r] = lds64(sb + off + 4096 * u + 1024 * w + 256 * r + 8 * lane);
      }
    };
    auto get_y = [&](int n) { ldsm4t(y[n & 1], ya + n * ys); ldsm4t(y[n & 1] + 4, ya + n * ys + 32); };
    if (h) {
#pragma unroll
      for (int n = 0; n < 4; n += 2) {
        get_q(n, OFF_Q, B_QF, n >> 1);
        uint32_t dep = P.zero;
#pragma unroll
        for (int r = 0; r < 8; r++) dep &= q[n + (r >> 2)][r & 3].x;
        bar_sync(6 + dep, 128);
        if (w < 2 && elect_one()) load_q(5 + 2 * w - (n >> 1), OFF_Q, B_QF);
        __syncwarp();
      }
#pragma unroll 1
      for (int r = 0; r < 6; r++) mbar_wait(bars + (B_IN + r) * 8, 0);
      const uint32_t src = sb + OFF_U + (4 * (rank ^ 1) + w) * U_N8 + 7 * U_CH, dst = sb + OFF_U + (4 * rank + w) * U_N8 + 5 * U_CH;
      bar_sync(9, 256);
      if (elect_one()) bulk_send(dst, src, 512, bars + (B_IN + 7) * 8, rank ^ 1);
      __syncwarp();
    } else get_q(0, OFF_K, B_KF, 0);
    mbar_wait(bars + (B_IN + 6) * 8, 0); mbar_wait(bars + (B_IN + 7) * 8, 0);
    get_y(0);
    if (warp == 8 && lane == 0) mbar_arrive_cta(bars + B_ACK * 8, rank ^ 1);
    if (O_WAIT) mbar_wait(bars + (O_WAIT == 1 ? B_HP : B_HR) * 8, 1);
    uint32_t oc = clk32() + (2 * w + h) * (O_PACE / 2);
    if (warp == 8 && lane == 0) STAMP(30);
#pragma unroll
    for (int n = 0; n < 4; n++) {
      uint32_t* o = y[n & 1];
#pragma unroll
      for (int r = 0; r < 4; r++) { o[2 * r] = bmul2(o[2 * r], q[n][r].x); o[2 * r + 1] = bmul2(o[2 * r + 1], q[n][r].y); }
#pragma unroll
      for (int u = 0; u < 2; u++) {
        const uint32_t ob = u ? ob1 : ob0;
        if (n > 0 && lane == 0) asm volatile("cp.async.bulk.wait_group.read 1;" ::: "memory");
        __syncwarp();
#pragma unroll
        for (int r = 2 * u; r < 2 * u + 2; r++)
          sts128(ob + (r & 1) * 512 + lane * 16, make_uint4(o[2 * r] << 16, o[2 * r] & 0xffff0000u, o[2 * r + 1] << 16, o[2 * r + 1] & 0xffff0000u));
        if (O_PACE) { while ((int)(clk32() - oc) < 0) { if (O_SLEEP) __nanosleep(O_SLEEP); } }
        oc += 4 * O_PACE;
        fence_proxy_async_smem();
        __syncwarp();
        if (lane == 0)
          asm volatile("cp.async.bulk.tensor.3d.global.shared::cta.bulk_group [%0, {%2, %3, %4}], [%1];\ncp.async.bulk.commit_group;"
                       ::"l"(&mO), "r"(ob), "r"(32 * slot), "r"(32 * rank + 8 * w), "r"(8 * n + 4 * h + 2 * u) : "memory");
        __syncwarp();
        if (u == 0 && n < 3) get_y(n + 1);
        if (u == 0 && n == 1 && !h) get_q(2, OFF_Q, B_QF, 0);
      }
    }
    if (lane == 0) asm volatile("cp.async.bulk.wait_group 0;" ::: "memory");
    if (warp == 8 && lane == 0) STAMP(31);
    mbar_wait(bars + B_ACK * 8, 0);
  }
}

typedef CUresult (*EncodeFn)(CUtensorMap*, CUtensorMapDataType, cuuint32_t, void*, const cuuint64_t*, const cuuint64_t*, const cuuint32_t*,
                             const cuuint32_t*, CUtensorMapInterleave, CUtensorMapSwizzle, CUtensorMapL2promotion, CUtensorMapFloatOOBfill);

bool encode(EncodeFn fn, CUtensorMap* m, int rank, const void* base, const cuuint64_t* dims, const cuuint64_t* strides, const cuuint32_t* box, CUtensorMapSwizzle swz,
            CUtensorMapL2promotion promo = CU_TENSOR_MAP_L2_PROMOTION_L2_128B) {
  const cuuint32_t es[5] = {1, 1, 1, 1, 1};
  return fn(m, CU_TENSOR_MAP_DATA_TYPE_BFLOAT16, rank, const_cast<void*>(base), dims, strides, box, es, CU_TENSOR_MAP_INTERLEAVE_NONE, swz,
            promo, CU_TENSOR_MAP_FLOAT_OOB_FILL_NONE) == CUDA_SUCCESS;
}

}

extern "C" void kernel_launch(void* const* d_in, const int* in_sizes, int n_in, void* d_out, int out_size) {
  (void)in_sizes; (void)n_in; (void)out_size;
  typedef const __nv_bfloat16* In;
  const In q = (In)d_in[0], k = (In)d_in[1], v = (In)d_in[2], ssm_k = (In)d_in[4], x = (In)d_in[6], B_re = (In)d_in[9], B_im = (In)d_in[10], C_re = (In)d_in[11], C_im = (In)d_in[12];
  Params P = {};
  P.shift_k = (In)d_in[3]; P.ssm_D = (In)d_in[5]; P.lam_re = (In)d_in[7]; P.lam_im = (In)d_in[8]; P.log_dt = (In)d_in[13]; P.Dskip = (In)d_in[14];
  P.out = (float*)d_out;
  for (int cl = 0; cl < 64; cl++) P.slot[cl >> 2] |= (cl < 4 ? 4 + cl : cl < 36 ? 8 * ((cl - 4) & 7) + ((cl - 4) >> 3) : 8 * (1 + (cl - 36) % 7) + 4 + (cl - 36) / 7) << (8 * (cl & 3));
  const bool swapB = (uintptr_t)B_im < (uintptr_t)B_re;

  EncodeFn fn = nullptr;
  cudaDriverEntryPointQueryResult qr;
  cudaGetDriverEntryPoint("cuTensorMapEncodeTiled", (void**)&fn, cudaEnableDefault, &qr);
  if (!fn) return;

  CUtensorMap mX, mB, mCre, mCim, mXs, mK, mV, mQ, mS, mO;
  bool ok = true;
  {
    const cuuint64_t dims[4] = {1024, 2, 64, 16}, str[3] = {2048, 32 * 2048, 2 * 2048};
    const cuuint32_t box[4] = {64, 2, 4, 16};
    ok &= encode(fn, &mX, 4, x, dims, str, box, CU_TENSOR_MAP_SWIZZLE_128B, (CUtensorMapL2promotion)X_PROMO);
  }
  {
    const uintptr_t lo = swapB ? (uintptr_t)B_im : (uintptr_t)B_re, hi = swapB ? (uintptr_t)B_re : (uintptr_t)B_im;
    const cuuint64_t dims[4] = {1024, 8, 2, 128}, str[3] = {2048, (cuuint64_t)(hi - lo), 8 * 2048};
    const cuuint32_t box[4] = {64, 8, 2, 4};
    ok &= encode(fn, &mB, 4, (const void*)lo, dims, str, box, CU_TENSOR_MAP_SWIZZLE_128B, (CUtensorMapL2promotion)B_PROMO);
  }
  {
    const cuuint64_t dims[5] = {1024, 2, 4, 2, 64}, str[4] = {2048, 4 * 2048, 2 * 2048, 16 * 2048};
    const cuuint32_t box[5] = {64, 2, 4, 2, 4};
    ok &= encode(fn, &mCre, 5, C_re, dims, str, box, CU_TENSOR_MAP_SWIZZLE_128B, (CUtensorMapL2promotion)C_PROMO);
    ok &= encode(fn, &mCim, 5, C_im, dims, str, box, CU_TENSOR_MAP_SWIZZLE_128B, (CUtensorMapL2promotion)C_PROMO);
  }
  {
    const cuuint64_t dims[4] = {1024, 2, 4, 256}, str[3] = {4 * 2048, 2048, 8 * 2048};
    const cuuint32_t box[4] = {64, 2, 4, 16};
    ok &= encode(fn, &mXs, 4, x, dims, str, box, CU_TENSOR_MAP_SWIZZLE_128B);
  }
  {
    const cuuint64_t dims[3] = {1024, 64, 32}, str[2] = {32 * 2048, 2048};
    const cuuint32_t box[3] = {16, 32, 4};
    const cuuint64_t dimq[4] = {1024, 8, 32, 8}, strq[3] = {32 * 2048, 2048, 256 * 2048};
    const cuuint32_t boxq[4] = {16, 8, 4, 4};
    ok &= encode(fn, &mQ, 4, q, dimq, strq, boxq, CU_TENSOR_MAP_SWIZZLE_NONE, (CUtensorMapL2promotion)Q_PROMO);
    ok &= encode(fn, &mK, 3, k, dims, str, box, CU_TENSOR_MAP_SWIZZLE_32B, (CUtensorMapL2promotion)KV_PROMO);
    ok &= encode(fn, &mV, 3, v, dims, str, box, CU_TENSOR_MAP_SWIZZLE_32B, (CUtensorMapL2promotion)KV_PROMO);
  }
  {
    const cuuint64_t dims[2] = {32, 65536}, str[1] = {64};
    const cuuint32_t box[2] = {32, 64};
    ok &= encode(fn, &mS, 2, ssm_k, dims, str, box, CU_TENSOR_MAP_SWIZZLE_64B, (CUtensorMapL2promotion)S_PROMO);
  }
  {
    const cuuint64_t dims[3] = {2048, 64, 32}, str[2] = {32 * 8192, 8192};
    const cuuint32_t box[3] = {32, 8, 2};
    ok &= encode(fn, &mO, 3, d_out, dims, str, box, CU_TENSOR_MAP_SWIZZLE_NONE);
  }
  if (!ok) return;
  auto kern = swapB ? fused_kernel<1> : fused_kernel<0>;
  cudaFuncSetAttribute(kern, cudaFuncAttributeMaxDynamicSharedMemorySize, SMEM_BYTES);
  kern<<<NCTA, 512, SMEM_BYTES, cudaStreamPerThread>>>(P, mX, mB, mCre, mCim, mXs, mK, mV, mQ, mS, mO);
}
```

```cpp
#include <cuda_runtime.h>
#include <cuda_bf16.h>
#include <cuda.h>
#include <stdint.h>
#include <type_traits>

#define PROFILE 0

namespace {

constexpr int D_DIM = 1024;
constexpr int NCTA = 128;

constexpr int STAGES = 5, STAGE_BYTES = 32768;
constexpr int OFF_RING = 0;
constexpr int OFF_F1 = STAGES * STAGE_BYTES, OFF_F2 = OFF_F1 + 4096, OFF_K = OFF_F2 + 2048, OFF_VP = OFF_K + 8192, OFF_Q = OFF_VP + 4096, OFF_IN = OFF_Q + 8192;
constexpr int OFF_KV = OFF_K;
constexpr int U_CH = 528, U_N8 = 8 * U_CH, OFF_U = OFF_IN + U_N8;
constexpr int OFF_COEF = OFF_U + 8 * U_N8;
constexpr int OFF_DS = OFF_COEF + 2048, OFF_D = OFF_DS + 512;
constexpr int OFF_BAR = OFF_D + 64;
constexpr int OFF_PROF = OFF_BAR + 512;
constexpr int SMEM_BYTES = OFF_PROF + 512;
static_assert(SMEM_BYTES <= 232448 && OFF_K % 1024 == 0 && (OFF_U + 3 * U_N8) % 512 == 0 && (4 * U_N8) % 512 == 0, "smem map");
constexpr int B_FULL = 0, B_XI = 5, B_HR = 6, B_HP = 7, B_KVF = 8, B_KF = 11, B_KE = 13, B_QF = 15, B_IN = 19, B_UF = 27, B_Y = 31, B_ACK = 36,
              B_EMPTY = 38, B_PEER = 43, B_COEF = 48, B_KVE = 49, B_EPOCH = 52;
#define QD1 8
#define QD2 2
#define QD3 8
#define QSW 16
#define HEAD 3
#define ST_T0 200
#define ST_DELAY 300
#define XPOS 28
#define K_T0 800
#define KV_T0 1500
#define KV_DT 500
#define KV_DV 100
#define O_PACE 0
#define H_PACE 0
#define CARRY_WAIT 600
#define POLL_NS 30
#define GREEDY 1
#define P2_SPLIT 0
#define TAILB 5
#define GREG 176
#define O_WAIT 2
#define COEF_T0 2500
#define O_EVERY 1
#define X_P1 32
#define X_P2 8
#define X_NOXI 0
#define RELPOS 0
#define O_UNR 4
constexpr int O_UNROLL = O_UNR;
#define C_AT 1
#define C_AT2 1
#define T_FENCE 0
#define T_ST 2
#define X_PROMO 2
#define B_PROMO 2
#define C_PROMO 2
#define KV_PROMO 2
#define Q_PROMO 2
#define S_PROMO 2
#define SHAKE 0
#define PRE_S 0
#define PRE_G 2
#define POW2 0
#define O_SLEEP 20
#define PFC_D 16
#define PFC_0 16
#define PFC_ALL 0
#define CFM 0x40f1
constexpr int SPIN_LIMIT = 1 << 14;

struct Params {
  unsigned slot[16];
  unsigned zero;
  const __nv_bfloat16 *shift_k, *ssm_D, *lam_re, *lam_im, *log_dt, *Dskip;
  float* out;
};

__device__ __align__(1024) uint4 g_h[16 * 32 * 1024];
__device__ __align__(128) uint2 g_carry[32 * 16 * 32];
__device__ unsigned g_flagH[2 * 16 * 32];
__device__ unsigned g_epoch[NCTA * 32];
#define STAMP(i)
#define GSTAMP(i)
#define TSTAMP(k, n)
#define KSTAMP(k, n)

__device__ __forceinline__ uint64_t make_desc(uint32_t addr, uint32_t lbo, uint32_t sbo, uint32_t swz) {
  return (uint64_t)((addr & 0x3FFFF) >> 4) | ((uint64_t)(lbo >> 4) << 16) | ((uint64_t)(sbo >> 4) << 32) | ((uint64_t)swz << 62);
}
__device__ __forceinline__ void wg_fence() { asm volatile("wgmma.fence.sync.aligned;" ::: "memory"); }
__device__ __forceinline__ void wg_commit() { asm volatile("wgmma.commit_group.sync.aligned;" ::: "memory"); }
template <int N> __device__ __forceinline__ void wg_wait() { asm volatile("wgmma.wait_group.sync.aligned %0;" ::"n"(N) : "memory"); }
__device__ __forceinline__ void mbar_init(uint32_t bar, int cnt) { asm volatile("mbarrier.init.shared::cta.b64 [%0], %1;" ::"r"(bar), "r"(cnt) : "memory"); }
__device__ __forceinline__ void mbar_expect(uint32_t bar, uint32_t bytes) { asm volatile("mbarrier.arrive.expect_tx.shared::cta.b64 _, [%0], %1;" ::"r"(bar), "r"(bytes) : "memory"); }
__device__ __forceinline__ void mbar_wait(uint32_t bar, uint32_t parity) {
  uint32_t ok; int n = 0;
  do {
    asm volatile("{\n.reg .pred p;\nmbarrier.try_wait.parity.shared::cta.b64 p, [%1], %2;\nselp.u32 %0, 1, 0, p;\n}\n" : "=r"(ok) : "r"(bar), "r"(parity) : "memory");
    if (++n > SPIN_LIMIT) break;
  } while (!ok);
}
__device__ __forceinline__ void mbar_arrive(uint32_t bar) { asm volatile("mbarrier.arrive.shared::cta.b64 _, [%0];" ::"r"(bar) : "memory"); }
__device__ __forceinline__ void mbar_arrive_cta(uint32_t bar, uint32_t cta) {
  asm volatile("{\n.reg .b32 ra;\nmapa.shared::cluster.u32 ra, %0, %1;\nmbarrier.arrive.shared::cluster.b64 _, [ra];\n}\n" ::"r"(bar), "r"(cta) : "memory");
}
__device__ __forceinline__ bool elect_one() {
  uint32_t p;
  asm volatile("{\n.reg .pred P;\nelect.sync _|P, 0xffffffff;\nselp.u32 %0, 1, 0, P;\n}\n" : "=r"(p));
  return p != 0;
}
__device__ __forceinline__ void bar_sync(int id, int n) { asm volatile("bar.sync %0, %1;" ::"r"(id), "r"(n) : "memory"); }
#define TMA_LD(dim) "cp.async.bulk.tensor." dim ".shared::cluster.global.mbarrier::complete_tx::bytes"
__device__ __forceinline__ void tma2d(uint32_t dst, const CUtensorMap* m, int c0, int c1, uint32_t bar) {
  asm volatile(TMA_LD("2d") " [%0], [%1, {%3, %4}], [%2];" ::"r"(dst), "l"(m), "r"(bar), "r"(c0), "r"(c1) : "memory");
}
__device__ __forceinline__ void tma3d(uint32_t dst, const CUtensorMap* m, int c0, int c1, int c2, uint32_t bar) {
  asm volatile(TMA_LD("3d") " [%0], [%1, {%3, %4, %5}], [%2];" ::"r"(dst), "l"(m), "r"(bar), "r"(c0), "r"(c1), "r"(c2) : "memory");
}
__device__ __forceinline__ void tma4d(uint32_t dst, const CUtensorMap* m, int c0, int c1, int c2, int c3, uint32_t bar) {
  asm volatile(TMA_LD("4d") " [%0], [%1, {%3, %4, %5, %6}], [%2];" ::"r"(dst), "l"(m), "r"(bar), "r"(c0), "r"(c1), "r"(c2), "r"(c3) : "memory");
}
__device__ __forceinline__ void tma4d_mc(uint32_t dst, const CUtensorMap* m, int c0, int c1, int c2, int c3, uint32_t bar) {
  asm volatile(TMA_LD("4d") ".multicast::cluster [%0], [%1, {%3, %4, %5, %6}], [%2], %7;" ::"r"(dst), "l"(m), "r"(bar), "r"(c0), "r"(c1), "r"(c2), "r"(c3), "h"((uint16_t)3) : "memory");
}
__device__ __forceinline__ void tma5d_mc(uint32_t dst, const CUtensorMap* m, int c0, int c1, int c2, int c3, int c4, uint32_t bar) {
  asm volatile(TMA_LD("5d") ".multicast::cluster [%0], [%1, {%3, %4, %5, %6, %7}], [%2], %8;" ::"r"(dst), "l"(m), "r"(bar), "r"(c0), "r"(c1), "r"(c2), "r"(c3), "r"(c4), "h"((uint16_t)3) : "memory");
}
__device__ __forceinline__ void bulk_load(uint32_t dst, const void* src, uint32_t bytes, uint32_t bar) {
  asm volatile("cp.async.bulk.shared::cluster.global.mbarrier::complete_tx::bytes [%0], [%1], %2, [%3];" ::"r"(dst), "l"(src), "r"(bytes), "r"(bar) : "memory");
}
__device__ __forceinline__ void bulk_send(uint32_t dst, uint32_t src, uint32_t bytes, uint32_t bar, uint32_t cta) {
  asm volatile("{\n.reg .b32 rd, rb;\nmapa.shared::cluster.u32 rd, %0, %3;\nmapa.shared::cluster.u32 rb, %2, %3;\n"
               "cp.async.bulk.shared::cluster.shared::cta.mbarrier::complete_tx::bytes [rd], [%1], %4, [rb];\n}\n"
               ::"r"(dst), "r"(src), "r"(bar), "r"(cta), "r"(bytes) : "memory");
}
__device__ __forceinline__ void fence_proxy_async_smem() { asm volatile("fence.proxy.async.shared::cta;" ::: "memory"); }
__device__ __forceinline__ void fence_proxy_async_global() { asm volatile("fence.proxy.async.global;" ::: "memory"); }
__device__ __forceinline__ uint32_t clk32() { uint32_t c; asm volatile("mov.u32 %0, %%clock;" : "=r"(c)::"memory"); return c; }
__device__ __forceinline__ void wait_until(uint32_t t0, uint32_t dt) { while (clk32() - t0 < dt) __nanosleep(32); }
__device__ __forceinline__ void spin_until(uint32_t t0, uint32_t dt) { while (clk32() - t0 < dt) {} }
__device__ __forceinline__ void prefetch_map(const CUtensorMap* m) { asm volatile("prefetch.tensormap [%0];" ::"l"(m) : "memory"); }
__device__ __forceinline__ void prefetch_line(const void* p) { asm volatile("prefetch.global.L2 [%0];" ::"l"(p) : "memory"); }
__device__ __forceinline__ unsigned ld_acquire(const unsigned* p) { unsigned v; asm volatile("ld.acquire.gpu.global.u32 %0, [%1];" : "=r"(v) : "l"(p) : "memory"); return v; }
__device__ __forceinline__ unsigned ld_relaxed(const unsigned* p) { unsigned v; asm volatile("ld.relaxed.gpu.global.u32 %0, [%1];" : "=r"(v) : "l"(p) : "memory"); return v; }
__device__ __forceinline__ uint32_t lds32(uint32_t a) { uint32_t v; asm volatile("ld.shared.u32 %0, [%1];" : "=r"(v) : "r"(a)); return v; }
__device__ __forceinline__ uint2 lds64(uint32_t a) { uint2 v; asm volatile("ld.shared.v2.u32 {%0,%1}, [%2];" : "=r"(v.x), "=r"(v.y) : "r"(a) : "memory"); return v; }
__device__ __forceinline__ uint4 lds128(uint32_t a) { uint4 v; asm volatile("ld.shared.v4.u32 {%0,%1,%2,%3}, [%4];" : "=r"(v.x), "=r"(v.y), "=r"(v.z), "=r"(v.w) : "r"(a) : "memory"); return v; }
__device__ __forceinline__ void sts32(uint32_t a, uint32_t v) { asm volatile("st.shared.u32 [%0], %1;" ::"r"(a), "r"(v) : "memory"); }
__device__ __forceinline__ void sts128(uint32_t a, uint4 v) { asm volatile("st.shared.v4.u32 [%0], {%1,%2,%3,%4};" ::"r"(a), "r"(v.x), "r"(v.y), "r"(v.z), "r"(v.w) : "memory"); }
__device__ __forceinline__ void ldsm4(uint32_t* r, uint32_t a) { asm volatile("ldmatrix.sync.aligned.m8n8.x4.shared.b16 {%0,%1,%2,%3}, [%4];" : "=r"(r[0]), "=r"(r[1]), "=r"(r[2]), "=r"(r[3]) : "r"(a) : "memory"); }
__device__ __forceinline__ void ldsm4t(uint32_t* r, uint32_t a) { asm volatile("ldmatrix.sync.aligned.m8n8.x4.trans.shared.b16 {%0,%1,%2,%3}, [%4];" : "=r"(r[0]), "=r"(r[1]), "=r"(r[2]), "=r"(r[3]) : "r"(a) : "memory"); }
__device__ __forceinline__ void stsm4t(uint32_t a, uint32_t r0, uint32_t r1, uint32_t r2, uint32_t r3) {
  asm volatile("stmatrix.sync.aligned.m8n8.x4.trans.shared.b16 [%0], {%1,%2,%3,%4};" ::"r"(a), "r"(r0), "r"(r1), "r"(r2), "r"(r3) : "memory");
}
__device__ __forceinline__ uint4 ldg128_nc(const void* p) { uint4 v; asm volatile("ld.global.nc.L1::no_allocate.v4.u32 {%0,%1,%2,%3}, [%4];" : "=r"(v.x), "=r"(v.y), "=r"(v.z), "=r"(v.w) : "l"(p)); return v; }
__device__ __forceinline__ void stg128(void* p, uint4 v) { asm volatile("st.global.L1::no_allocate.v4.u32 [%0], {%1,%2,%3,%4};" ::"l"(p), "r"(v.x), "r"(v.y), "r"(v.z), "r"(v.w) : "memory"); }
__device__ __forceinline__ uint32_t pack_bf16(float lo, float hi) { uint32_t r; asm("cvt.rn.bf16x2.f32 %0, %1, %2;" : "=r"(r) : "f"(hi), "f"(lo)); return r; }
__device__ __forceinline__ uint32_t bmul2(uint32_t a, uint32_t b) { uint32_t r; asm("mul.rn.bf16x2 %0, %1, %2;" : "=r"(r) : "r"(a), "r"(b)); return r; }
__device__ __forceinline__ uint32_t bfma2(uint32_t a, uint32_t b, uint32_t c) { uint32_t r; asm("fma.rn.bf16x2 %0, %1, %2, %3;" : "=r"(r) : "r"(a), "r"(b), "r"(c)); return r; }
__device__ __forceinline__ uint32_t blo2(uint32_t a) { uint32_t r; asm("{\n.reg .b16 l, h;\nmov.b32 {l, h}, %1;\nmov.b32 %0, {l, l};\n}" : "=r"(r) : "r"(a)); return r; }
__device__ __forceinline__ float bf2f(__nv_bfloat16 v) { return __bfloat162float(v); }

#define R8(d, o) "+f"(d[o]), "+f"(d[o + 1]), "+f"(d[o + 2]), "+f"(d[o + 3]), "+f"(d[o + 4]), "+f"(d[o + 5]), "+f"(d[o + 6]), "+f"(d[o + 7])
#define R16(d, o) R8(d, o), R8(d, o + 8)
#define R64(d, o) R16(d, o), R16(d, o + 16), R16(d, o + 32), R16(d, o + 48)
template <int TA> __device__ __forceinline__ void wgmma_n128(float* d, uint64_t da, uint64_t db, int scale_d) {
  asm volatile("{\n.reg .pred p;\nsetp.ne.b32 p, %66, 0;\n"
    "wgmma.mma_async.sync.aligned.m64n128k16.f32.bf16.bf16 {"
    "%0,%1,%2,%3,%4,%5,%6,%7,%8,%9,%10,%11,%12,%13,%14,%15,%16,%17,%18,%19,%20,%21,%22,%23,%24,%25,%26,%27,%28,%29,%30,%31,"
    "%32,%33,%34,%35,%36,%37,%38,%39,%40,%41,%42,%43,%44,%45,%46,%47,%48,%49,%50,%51,%52,%53,%54,%55,%56,%57,%58,%59,%60,%61,%62,%63"
    "}, %64, %65, p, 1, 1, %67, 0;\n}\n"
    : R64(d, 0)
    : "l"(da), "l"(db), "r"(scale_d), "n"(TA));
}
template <int N> __device__ __forceinline__ void fence_regs(float* d) {
#pragma unroll
  for (int i = 0; i < N; i++) asm volatile("" : "+f"(d[i])::"memory");
}
#define PMFENCE() asm volatile("pmevent 0;" ::: "memory")
__device__ __forceinline__ void cmul(float ar, float ai, float br, float bi, float& cr, float& ci) {
  cr = ar * br - ai * bi; ci = ar * bi + ai * br;
}
__device__ __forceinline__ void csq(float& r, float& i) { const float x = fmaf(r, r, -i * i), y = (r + r) * i; r = x; i = y; }

#define W8(d, o) "=f"(d[o]), "=f"(d[o + 1]), "=f"(d[o + 2]), "=f"(d[o + 3]), "=f"(d[o + 4]), "=f"(d[o + 5]), "=f"(d[o + 6]), "=f"(d[o + 7])
#define L16 "{%0,%1,%2,%3,%4,%5,%6,%7,%8,%9,%10,%11,%12,%13,%14,%15}"
#define L32 "{%0,%1,%2,%3,%4,%5,%6,%7,%8,%9,%10,%11,%12,%13,%14,%15,%16,%17,%18,%19,%20,%21,%22,%23,%24,%25,%26,%27,%28,%29,%30,%31}"
template <int ACC, int TB> __device__ __forceinline__ void rs_n32(float* d, const uint32_t* a, uint64_t db) {
  if constexpr (ACC) asm volatile("wgmma.mma_async.sync.aligned.m64n32k16.f32.bf16.bf16 " L16 ", {%16,%17,%18,%19}, %20, 1, 1, 1, %21;" : R16(d, 0) : "r"(a[0]), "r"(a[1]), "r"(a[2]), "r"(a[3]), "l"(db), "n"(TB));
  else asm volatile("wgmma.mma_async.sync.aligned.m64n32k16.f32.bf16.bf16 " L16 ", {%16,%17,%18,%19}, %20, 0, 1, 1, %21;" : W8(d, 0), W8(d, 8) : "r"(a[0]), "r"(a[1]), "r"(a[2]), "r"(a[3]), "l"(db), "n"(TB));
}
template <int ACC, int TB> __device__ __forceinline__ void ss_n64(float* d, uint64_t da, uint64_t db) {
  if constexpr (ACC) asm volatile("wgmma.mma_async.sync.aligned.m64n64k16.f32.bf16.bf16 " L32 ", %32, %33, 1, 1, 1, 0, %34;" : R16(d, 0), R16(d, 16) : "l"(da), "l"(db), "n"(TB));
  else asm volatile("wgmma.mma_async.sync.aligned.m64n64k16.f32.bf16.bf16 " L32 ", %32, %33, 0, 1, 1, 0, %34;" : W8(d, 0), W8(d, 8), W8(d, 16), W8(d, 24) : "l"(da), "l"(db), "n"(TB));
}
template <int ACC> __device__ __forceinline__ void ss_n32_tt(float* d, uint64_t da, uint64_t db) {
  if constexpr (ACC) asm volatile("wgmma.mma_async.sync.aligned.m64n32k16.f32.bf16.bf16 " L16 ", %16, %17, 1, 1, 1, 1, 1;" : R16(d, 0) : "l"(da), "l"(db));
  else asm volatile("wgmma.mma_async.sync.aligned.m64n32k16.f32.bf16.bf16 " L16 ", %16, %17, 0, 1, 1, 1, 1;" : W8(d, 0), W8(d, 8) : "l"(da), "l"(db));
}
__device__ __forceinline__ void stsm4(uint32_t a, uint32_t r0, uint32_t r1, uint32_t r2, uint32_t r3) {
  asm volatile("stmatrix.sync.aligned.m8n8.x4.shared.b16 [%0], {%1,%2,%3,%4};" ::"r"(a), "r"(r0), "r"(r1), "r"(r2), "r"(r3) : "memory");
}
template <int N> __device__ __forceinline__ void fence_u32(uint32_t* d) {
#pragma unroll
  for (int i = 0; i < N; i++) asm volatile("" : "+r"(d[i])::"memory");
}
__device__ __forceinline__ void pack32(uint32_t* f, const float* z) {
#pragma unroll
  for (int i = 0; i < 16; i++) f[i] = pack_bf16(z[2 * i], z[2 * i + 1]);
}
template <int INV> __device__ __forceinline__ void twiddle(uint32_t* f, const uint32_t* tp, const uint32_t* ts) {
#pragma unroll
  for (int i = 0; i < 8; i++) {
    uint32_t x = f[2 * i + INV], y = f[2 * i + 1 - INV];
    x = bfma2(tp[i & 3], y, x); y = bfma2(ts[i & 3], x, y); x = bfma2(tp[i & 3], y, x);
    f[2 * i + INV] = x; f[2 * i + 1 - INV] = y;
  }
}
__device__ __forceinline__ uint32_t bfnma2(uint32_t a, uint32_t b, uint32_t c) { uint32_t r; asm("{\n.reg .b32 t;\nmul.bf16x2 t, %1, %2;\nsub.bf16x2 %0, %3, t;\n}" : "=r"(r) : "r"(a), "r"(b), "r"(c)); return r; }
__device__ __forceinline__ uint32_t bfms2(uint32_t a, uint32_t b, uint32_t c) { uint32_t r; asm("{\n.reg .b32 t;\nmul.bf16x2 t, %1, %2;\nsub.bf16x2 %0, t, %3;\n}" : "=r"(r) : "r"(a), "r"(b), "r"(c)); return r; }
template <int ADD> __device__ __forceinline__ void bimac(uint32_t* o, const uint32_t* a, const uint32_t* b, const uint32_t* c) {
#pragma unroll
  for (int J = 0; J < 2; J++) {
    const uint32_t Pr = a[2 * J], Pi = a[2 * J + 1], Qr = a[2 * J + 4], Qi = a[2 * J + 5], pr = b[2 * J], pi = b[2 * J + 1], qr = b[2 * J + 4], qi = b[2 * J + 5];
    uint32_t x0, x1, x2, x3;
    if (ADD == 0) { x0 = bmul2(Pr, pr); x1 = bmul2(Pr, pi); x2 = bmul2(Pr, qr); x3 = bmul2(Pr, qi); }
    if (ADD == 1) { x0 = bfma2(Pr, pr, c[2 * J]); x1 = bfma2(Pr, pi, c[2 * J + 1]); x2 = bfma2(Pr, qr, c[2 * J + 4]); x3 = bfma2(Pr, qi, c[2 * J + 5]); }
    if (ADD == 2) { x0 = bfma2(Pr, pr, c[2 * J + 1]); x1 = bfms2(Pr, pi, c[2 * J]); x2 = bfma2(Pr, qr, c[2 * J + 5]); x3 = bfms2(Pr, qi, c[2 * J + 4]); }
    x0 = bfnma2(Pi, pi, x0); x1 = bfma2(Pi, pr, x1); x2 = bfnma2(Pi, qi, x2); x3 = bfma2(Pi, qr, x3);
    x0 = bfnma2(Qr, qr, x0); x1 = bfnma2(Qr, qi, x1); x2 = bfma2(Qr, pr, x2); x3 = bfma2(Qr, pi, x3);
    x0 = bfma2(Qi, qi, x0); x1 = bfnma2(Qi, qr, x1); x2 = bfnma2(Qi, pi, x2); x3 = bfma2(Qi, pr, x3);
    o[2 * J] = x0; o[2 * J + 1] = x1; o[2 * J + 4] = x2; o[2 * J + 5] = x3;
  }
}
__device__ __forceinline__ void sincos8k(int n, float& s, float& c) {
  const float x = (float)((n << 19) >> 19) * (6.283185307179586f / 8192.f);
  s = __sinf(x); c = __cosf(x);
}
__device__ __forceinline__ void fft_tables(uint32_t f1a, uint32_t f2a, int w, int lane, uint32_t* tp, uint32_t* ts, float& d0r, float& d0i) {
  const int c = lane & 3, f1 = 8 * w + (lane >> 2);
#pragma unroll 1
  for (int J = 3; J >= 0; J--) {
    const int a = 8 * J + 2 * c;
    float s0, c0, s1, c1;
    sincos8k(64 * (4 * f1 + 1) * a + 31 * (4 * f1 - 63), d0i, d0r); sincos8k(64 * (4 * f1 + 1) * (a + 1) + 31 * (4 * f1 - 63), s1, c1);
    d0r *= 0.125f; d0i *= 0.125f;
    sts32(f1a + w * 1024 + J * 128 + lane * 4, pack_bf16(d0r, 0.125f * c1)); sts32(f1a + w * 1024 + 512 + J * 128 + lane * 4, pack_bf16(d0i, 0.125f * s1));
    sincos8k(128 * (2 * (a & 15) + 1) * f1 - 128 * (a & 16), s0, c0); sincos8k(128 * (2 * (a & 15) + 3) * f1 - 128 * (a & 16), s1, c1);
    sts32(f2a + w * 512 + J * 128 + lane * 4, pack_bf16(c0, c1));
    sincos8k((4 * f1 - 63) * (2 * a - 31), s0, c0); sincos8k((4 * f1 - 63) * (2 * a - 29), s1, c1);
#pragma unroll
    for (int i = 3; i > 0; i--) { ts[i] = ts[i - 1]; tp[i] = tp[i - 1]; }
    ts[0] = pack_bf16(s0, s1); tp[0] = pack_bf16(-__fdividef(s0, 1.f + c0), -__fdividef(s1, 1.f + c1));
  }
  if (c != 0) d0r = d0i = 0.f;
}

template <int SWAPB>
__global__ void __cluster_dims__(2, 1, 1) __launch_bounds__(512, 1)
fused_kernel(const __grid_constant__ Params P, const __grid_constant__ CUtensorMap mX, const __grid_constant__ CUtensorMap mB,
             const __grid_constant__ CUtensorMap mCre, const __grid_constant__ CUtensorMap mCim, const __grid_constant__ CUtensorMap mXs,
             const __grid_constant__ CUtensorMap mK, const __grid_constant__ CUtensorMap mV, const __grid_constant__ CUtensorMap mQ, const __grid_constant__ CUtensorMap mS,
             const __grid_constant__ CUtensorMap mO) {
  extern __shared__ __align__(1024) uint8_t smem_raw[];
  const uint32_t sb = (uint32_t)__cvta_generic_to_shared(smem_raw);
  const uint32_t bars = sb + OFF_BAR;
  const int slot = (P.slot[blockIdx.x >> 3] >> (4 * (blockIdx.x & 6))) & 63, rank = blockIdx.x & 1;
  const int j = slot & 7, tc = 2 * (slot >> 3) + rank, b = 2 * slot + rank;
  const int tid = threadIdx.x;
  const int warp = __shfl_sync(0xffffffffu, tid >> 5, 0);
  const int wg = warp >> 2;
  const uint32_t c_start = clk32();
  auto kblock = [&](int n) { return ((n & 14) == 0 || (n & 14) == 2 * j ? n ^ (2 * j) : n) & 31; };
  auto send_y = [&](int r) {
    const uint32_t src = sb + OFF_U + 4 * (rank ^ 1) * U_N8 + r * U_CH, dst = r >= 2 ? sb + OFF_U + 4 * rank * U_N8 + (r - 2) * U_CH : sb + OFF_IN + 96 + r * 2064;
#pragma unroll 1
    for (int n = 0; n < 4; n++) bulk_send(dst + n * (r >= 2 ? U_N8 : 512), src + n * U_N8, 512, bars + (B_IN + r) * 8, rank ^ 1);
  };
  auto load_q = [&](int i, int off, int bar) {
    const uint32_t fb = bars + bar * 8 + 4 * (i & 2);
    mbar_expect(fb, 4096); tma4d(sb + off + 2048 * (i & 2), &mQ, 16 * slot, 0, 4 * i, 4 * rank, fb);
  };
  auto head = [&](int n) {
    const uint32_t fb = bars + (B_FULL + n) * 8, dst = sb + OFF_RING + n * STAGE_BYTES;
    mbar_expect(fb, STAGE_BYTES);
    tma4d(dst + 16384, &mX, 64 * n, 0, 4 * tc, 0, fb);
    tma4d(dst, &mB, 64 * n, 0, 0, 8 * j, fb);
    tma4d(dst + 8192, &mB, 64 * n, 0, 0, 8 * j + 4, fb);
  };
  if (warp == 0 && elect_one()) {
    STAMP(0); GSTAMP(0);
#pragma unroll
    for (int s = 0; s < STAGES; s++) mbar_init(bars + (B_FULL + s) * 8, 1);
    head(0);
    STAMP(1);
    asm volatile("fence.mbarrier_init.release.cluster;" ::: "memory");
  }
  if (wg == 3 && elect_one()) {
    if (warp < 15) {
#pragma unroll
      for (int s = 0; s < 11; s++) mbar_init(bars + 8 * B_XI + (warp & 3) * 88 + 8 * s, 1);
    } else {
#pragma unroll
      for (int s = B_EMPTY; s < B_KVE + 3; s++) mbar_init(bars + 8 * s, s < B_PEER ? (SHAKE ? 1 : 2) : s < B_COEF ? (SHAKE == 2 ? 2 : 1) : s == B_COEF ? 128 : 4);
    }
    asm volatile("fence.mbarrier_init.release.cluster;" ::: "memory");
  }
  __syncwarp();
  asm volatile("barrier.cluster.arrive.relaxed.aligned;" ::: "memory");
  if (warp == 0 && elect_one()) {
#pragma unroll 1
    for (int n = 1; n < HEAD; n++) { spin_until(c_start, ST_T0 + n * ST_DELAY); head(n); }
  }
  __syncwarp();
#define CLUSTER_WAIT() asm volatile("barrier.cluster.wait.aligned;" ::: "memory")

  if (wg == 3) {
    asm volatile("setmaxnreg.dec.sync.aligned.u32 24;");
    CLUSTER_WAIT();
    if (warp < 14) {
      if (elect_one()) {
        uint32_t so = 8 * (HEAD % STAGES), ph = HEAD < STAGES;
        auto step = [&](auto issue) {
          mbar_wait(bars + (SHAKE == 2 && warp == 12 ? B_PEER : B_EMPTY) * 8 + so, ph);
          issue(sb + OFF_RING + (so << 12), bars + B_FULL * 8 + so);
          so += 8;
          if (so == 8 * STAGES) { so = 0; ph ^= 1; }
        };
        if (warp == 12) {
          uint64_t pp = 0;
          auto shake = [&](uint32_t fb) {
            if (SHAKE == 1) mbar_arrive_cta(bars + B_PEER * 8 + so, rank ^ 1);
            mbar_expect(fb, STAGE_BYTES);
            if (SHAKE == 1) {
              mbar_wait(bars + B_PEER * 8 + so, (uint32_t)(pp >> so) & 1);
              pp ^= 1ull << so;
            }
          };
          auto g1 = [&](int n0, int n1, int grp) {
#pragma unroll 1
            for (int n = n0; n < n1; n++) step([&](uint32_t dst, uint32_t fb) { shake(fb); tma4d_mc(dst + rank * 8192, &mB, n * 64, 0, 0, grp + 4 * rank, fb); });
          };
#pragma unroll 1
          for (int n = HEAD; n < STAGES; n++) { spin_until(c_start, ST_T0 + n * ST_DELAY); g1(n, n + 1, 8 * j); }
          g1(STAGES, 16, 8 * j);
          g1(0, XPOS - 16, 8 * j + 64);
          step([&](uint32_t dst, uint32_t fb) { mbar_expect(fb, STAGE_BYTES); tma4d(dst, &mXs, 128 * j, 0, 0, 16 * tc, fb); mbar_arrive(bars + B_XI * 8); });
          g1(XPOS - 16, 16, 8 * j + 64);
#pragma unroll 1
          for (int n = 0; n < 32; n += 2) {
            const int col = kblock(n) * 32;
            if (PFC_D && n + PFC_D >= PFC_0 && n + PFC_D < 32 && (PFC_ALL || ((n >> 1) & 7) == (slot >> 3))) {
#pragma unroll
              for (int part = 0; part < 2; part++)
                asm volatile("cp.async.bulk.prefetch.tensor.5d.L2.global [%0, {%1, %2, %2, %2, %3}];" ::"l"(part ? &mCim : &mCre), "r"(kblock(n + PFC_D) * 32), "r"(0), "r"(8 * j + 4 * rank) : "memory");
            }
#pragma unroll
            for (int part = 0; part < 2; part++)
              step([&](uint32_t dst, uint32_t fb) { shake(fb); tma5d_mc(dst + rank * 8192, part ? &mCim : &mCre, col, 0, 0, 0, 8 * j + 4 * rank, fb); });
          }
        } else {
          auto g1 = [&](int n0, int n1, int nb) {
#pragma unroll 1
            for (int n = n0; n < n1; n++) step([&](uint32_t dst, uint32_t fb) { tma4d(dst + 16384, &mX, n * 64, 0, 4 * tc, 0, fb); TSTAMP(1, n + nb); });
          };
          auto g2 = [&](int n0, int n1) {
#pragma unroll 1
            for (int n = n0; n < n1; n++) step([&](uint32_t dst, uint32_t fb) { bulk_load(dst + 16384, g_h + (32 * tc + kblock(n)) * 1024, 16384, fb); TSTAMP(1, n + 32); });
          };
#pragma unroll 1
          for (int n = HEAD; n < STAGES; n++) { spin_until(c_start, ST_T0 + n * ST_DELAY); g1(n, n + 1, 0); }
          g1(STAGES, 16, 0);
          g1(0, XPOS - 16, 16);
          step([&](uint32_t dst, uint32_t fb) { tma4d(dst + 16384, &mXs, 128 * j + 64, 0, 0, 16 * tc, fb); });
          g1(XPOS - 16, 16, 16);
#pragma unroll 1
          for (int v = 0; v < 2; v++) {
            STAMP(4 + v);
            mbar_wait(bars + B_HP * 8, v);
            fence_proxy_async_global();
            STAMP(6 + v);
            g2(16 * v, 16 * v + 2);
            mbar_wait(bars + B_HR * 8, v);
            fence_proxy_async_global();
            g2(16 * v + 2, 16 * v + 16);
          }
        }
      }
    } else if (warp == 15) {
      mbar_wait(bars + B_COEF * 8, 0);
      const unsigned epoch = lds32(bars + B_EPOCH * 8);
#pragma unroll 1
      for (int v = 0; v < 2; v++) {
        unsigned* fp = &g_flagH[(16 * v + tc) * 32];
        bar_sync(4 + v, 160);
        if (elect_one()) {
          asm volatile("red.release.gpu.global.add.u32 [%0], 1;" ::"l"(fp) : "memory");
          mbar_arrive(bars + B_HP * 8);
          STAMP(16 + 10 * v);
          int it = 0;
          while (ld_acquire(fp) != 8 * epoch && ++it < (SPIN_LIMIT << 4)) __nanosleep(POLL_NS);
          STAMP(2 + v);
          mbar_arrive(bars + B_HR * 8);
        }
        __syncwarp();
      }
    } else if (elect_one()) {
      const int ch0 = 16 * slot;
      auto load_k = [&](int s, uint32_t dst) { const uint32_t fb = bars + (B_KF + (s & 1)) * 8; mbar_expect(fb, 4096); tma2d(dst, &mS, 0, 64 * (8 * b + s), fb); };
      prefetch_map(&mS); prefetch_map(&mK); prefetch_map(&mV);
      wait_until(c_start, K_T0);
      load_k(0, sb + OFF_U + (4 * rank + 3) * U_N8); load_k(1, sb + OFF_U + (4 * rank + 3) * U_N8 - 4096);
      {
        uint32_t so = 16, ph = 1;
#pragma unroll 1
        for (int e = 0; e < 9; e++) {
          const uint32_t fb = bars + B_KVF * 8 + so, dst = sb + OFF_KV + (so << 10);
          wait_until(c_start, KV_T0 + (e ? 2 * e - 1 : 0) * KV_DT);
          mbar_wait(bars + B_KVE * 8 + so, ph);
          const uint32_t c1 = clk32();
          mbar_expect(fb, e ? 8192 : 4096);
          if (e > 0) KSTAMP(1, e - 1);
          tma3d(dst, &mK, ch0, 32 * rank - (e == 0), (4 * e - 4) & 31, fb);
          if (e > 0) { wait_until(c1, KV_DV); tma3d(dst + 4096, &mV, ch0, 32 * rank, 4 * e - 4, fb); }
          so += 8;
          if (so == 24) so = 0;
          if (so == 16) ph ^= 1;
        }
      }
      prefetch_map(&mCre); prefetch_map(&mCim); prefetch_map(&mXs); prefetch_map(&mQ); prefetch_map(&mO);
      mbar_wait(bars + B_KVE * 8, 0);
      load_k(2, sb + OFF_K); load_k(3, sb + OFF_K + 4096);
      mbar_wait(bars + (B_UF + 3) * 8, 0);
#pragma unroll 1
      for (int ch = 0; ch < 7; ch++) {
        if (ch > 0) {
          mbar_wait(bars + (B_Y + (ch & 3)) * 8, ch >> 2);
          if (ch > 2) mbar_wait(bars + (B_IN + ch - 3) * 8, 0);
          send_y(ch - 1);
        }
        if (ch < 6) {
          mbar_wait(bars + (B_KE + (ch & 1)) * 8, (ch >> 1) & 1);
          if (ch < 4) load_k(ch + 4, sb + OFF_K + (ch & 1) * 4096);
          if (ch >= 2) load_q(2 * (ch & 1) + (ch < 4), ch < 4 ? OFF_Q : OFF_K, ch < 4 ? B_QF : B_KF);
        }
      }
    }
    return;
  } else if (wg == 2) {
    asm volatile("setmaxnreg.inc.sync.aligned.u32 %0;" ::"n"(488 - 2 * GREG));
    const int t = tid & 127, w = warp & 3, lane = t & 31, g = lane >> 2, c = lane & 3;
    const uint4 s2[2] = {ldg128_nc(P.shift_k + (8 * b + 2 * c) * 4), ldg128_nc(P.shift_k + (8 * (b ^ 1) + 2 * c) * 4)};
    const uint32_t dskip = __bfloat16_as_ushort(P.ssm_D[8 * b + (t & 7)]);
    uint32_t tp[4] = {}, ts[4] = {};
    float d0r, d0i;
    fft_tables(sb + OFF_F1, sb + OFF_F2, w, lane, tp, ts, d0r, d0i);
    if (t == 0) STAMP(19);
    CLUSTER_WAIT();
    if (t < 12) mbar_expect(bars + (B_IN + t) * 8, t < 6 ? 2048 : t < 8 ? 4 * (U_CH + 512) : U_N8);
    if (t < 8) sts32(sb + OFF_D + 4 * t, dskip << 16);
    const uint64_t dF1a = make_desc(sb + OFF_F1, 128, 512, 0), dF1b = make_desc(sb + OFF_F1, 512, 128, 0);
    const uint64_t dF2f = make_desc(sb + OFF_F2, 512, 128, 0), dF2i = make_desc(sb + OFF_F2, 128, 512, 0);
    auto T1k = [&](float* z, uint64_t dk) { wg_fence(); ss_n64<0, 1>(z, dF1a, dk); ss_n64<1, 1>(z, dF1a + 16, dk + 64); wg_commit(); };
    auto T1u = [&](float* z, uint64_t du) { wg_fence(); ss_n64<0, 0>(z, dF1a, du); ss_n64<1, 0>(z, dF1a + 16, du + 16); wg_commit(); };
    auto T2 = [&](float* s, const uint32_t* f) {
      wg_fence();
      rs_n32<0, 1>(s, f, dF2f); rs_n32<0, 1>(s + 16, f + 8, dF2f); rs_n32<1, 1>(s, f + 4, dF2f + 64); rs_n32<1, 1>(s + 16, f + 12, dF2f + 64);
      wg_commit();
    };
    auto product = [&](uint32_t* pr, const uint32_t* kh, const uint32_t* uh) {
      bimac<0>(pr, kh, uh, pr); bimac<2>(pr + 8, kh + 8, uh, pr); bimac<1>(pr + 8, kh, uh + 8, pr + 8);
      fence_u32<16>(pr);
    };
    float zk[32] = {};
    uint32_t pr[16];
    {
      uint32_t kh0[16];
      {
        float z0[32], sk[32];
        uint32_t fk[16];
        const uint64_t dk = make_desc(sb + OFF_U + (4 * rank + 3) * U_N8, 2048, 512, 2);
        fence_proxy_async_smem();
        bar_sync(7, 128);
        mbar_wait(bars + B_KF * 8, 0);
        T1k(z0, dk);
        mbar_wait(bars + (B_KF + 1) * 8, 0);
        T1k(zk, dk - 256);
        wg_wait<0>(); fence_regs<32>(z0); fence_regs<32>(zk);
        const float dd = __uint_as_float(lds32(sb + OFF_D));
        z0[0] = fmaf(d0r, dd, z0[0]); z0[2] = fmaf(d0i, dd, z0[2]);
        pack32(fk, z0); twiddle<0>(fk, tp, ts); fence_u32<16>(fk);
        T2(sk, fk);
        wg_wait<0>(); fence_regs<32>(sk); fence_u32<16>(fk);
        pack32(kh0, sk); fence_u32<16>(kh0);
      }
      {
        uint32_t sk[2][4], kx[2][8];
#pragma unroll
        for (int o = 0; o < 2; o++) {
          sk[o][0] = __byte_perm(s2[o].x, s2[o].z, 0x5410); sk[o][1] = __byte_perm(s2[o].x, s2[o].z, 0x7632);
          sk[o][2] = __byte_perm(s2[o].y, s2[o].w, 0x5410); sk[o][3] = __byte_perm(s2[o].y, s2[o].w, 0x7632);
        }
        const uint32_t la = sb + OFF_KV + (lane >> 3) * 1024 + (8 * w + (lane & 7)) * 32 + ((rank ^ ((lane >> 2) & 1)) << 4);
        const uint32_t uo = (lane & 7) * U_CH + w * 128 + (lane >> 3) * 16;
        mbar_wait(bars + (B_KVF + 2) * 8, 0);
        if (t == 0) STAMP(27);
        ldsm4(kx[0], la + 16384); ldsm4(kx[1], (la ^ 16) + 16384);
        if (lane == 0) mbar_arrive(bars + (B_KVE + 2) * 8 + (kx[0][1] & kx[1][1] & P.zero));
        uint32_t so = 0, ph = 0;
#pragma unroll 1
        for (int n = 0; n < 4; n++) {
          const uint32_t own = sb + OFF_U + (4 * rank + n) * U_N8, box = n < 3 ? sb + OFF_U + (4 * (rank ^ 1) + n + 1) * U_N8 : sb + OFF_IN;
#pragma unroll
          for (int e = 0; e < 2; e++) {
            uint32_t vx[2][4];
            mbar_wait(bars + B_KVF * 8 + so, ph);
            if (t == 0) KSTAMP(2, 2 * n + e);
#pragma unroll
            for (int o = 0; o < 2; o++) { ldsm4(kx[o] + 4, (la ^ (16 * o)) + (so << 10)); ldsm4(vx[o], (la ^ (16 * o)) + (so << 10) + 4096); }
            if (lane == 0) mbar_arrive(bars + B_KVE * 8 + so + (kx[0][4] & kx[1][4] & vx[0][0] & vx[1][0] & P.zero));
#pragma unroll
            for (int o = 0; o < 2; o++) {
#pragma unroll
              for (int i = 0; i < 4; i++) vx[o][i] = bmul2(bfma2(kx[o][i + 4], sk[o][0], bfma2(kx[o][i + 3], sk[o][1], bfma2(kx[o][i + 2], sk[o][2], bmul2(kx[o][i + 1], sk[o][3])))), vx[o][i]);
              stsm4t((o ? box : own) + uo + e * 64, vx[o][0], vx[o][1], vx[o][2], vx[o][3]);
              kx[o][1] = kx[o][5]; kx[o][2] = kx[o][6]; kx[o][3] = kx[o][7];
            }
            if (t == 0) KSTAMP(3, 2 * n + e);
            so += 8;
            if (so == 24) so = 0;
            if (so == 16) ph ^= 1;
          }
          fence_proxy_async_smem();
          bar_sync(7, 128);
          if (w == 0 && elect_one()) {
            if (n > 0) mbar_wait(bars + B_UF * 8 + 8 * (n - 1), 0);
            bulk_send(own, box, U_N8, bars + B_UF * 8 + 8 * n, rank ^ 1);
          }
          __syncwarp();
        }
        if (t == 0) STAMP(28);
      }
      float zu[32], su[32];
      uint32_t fu[16], uh[16];
#pragma unroll
      for (int n = 0; n < 4; n++) mbar_wait(bars + (B_UF + n) * 8, 0);
      T1u(zu, make_desc(sb + OFF_U, 128, U_N8, 0));
      wg_wait<0>(); fence_regs<32>(zu);
      pack32(fu, zu); twiddle<0>(fu, tp, ts); fence_u32<16>(fu);
      T2(su, fu);
      wg_wait<0>(); fence_regs<32>(su); fence_u32<16>(fu);
      pack32(uh, su);
      product(pr, kh0, uh);
      if (t == 0) STAMP(54);
    }
    {
#define CF(i) do { if ((CFM >> (i)) & 1) PMFENCE(); } while (0)
#define CP(i)
      const uint32_t vs = w < 2 ? 512 : U_N8;
      uint32_t va = (w < 2 ? sb + OFF_VP : sb + OFF_U) + ((lane >> 4) & 1) * vs + (w & 1) * 256 + (lane & 15) * 16;
      uint32_t ya = sb + OFF_U + (2 * w + ((lane >> 3) & 1)) * U_N8 + (lane >> 4) * 128 + (lane & 7) * 16;
      uint64_t du = make_desc(sb + OFF_U, 128, U_N8, 0), dk = make_desc(sb + OFF_K, 2048, 512, 2);
      const uint64_t dv = make_desc(sb + OFF_VP, 128, 512, 0);
      uint32_t yp[8] = {};
      uint32_t yq = sb + OFF_Q + lane * 16;
      auto store_y = [&]() { stsm4(yq, yp[0], yp[1], yp[2], yp[3]); stsm4(yq + 256, yp[4], yp[5], yp[6], yp[7]); };
      auto step = [&](int ch, auto fwd) {
        constexpr bool FWD = decltype(fwd)::value;
        float zu[32], sk[32], su[32], v[32], y[16];
        uint32_t kh[16], uh[16], fk[16], fu[16], fv[16];
        CP(16);
        wg_fence();
        rs_n32<0, 0>(v, pr, dF2i); rs_n32<0, 0>(v + 16, pr + 8, dF2i); rs_n32<1, 0>(v, pr + 4, dF2i + 16); rs_n32<1, 0>(v + 16, pr + 12, dF2i + 16);
        wg_commit();
        CF(0);
        store_y();
        if (FWD) {
          const float dd = __uint_as_float(lds32(sb + OFF_D + 4 * (ch + 1)));
          zk[0] = fmaf(d0r, dd, zk[0]); zk[2] = fmaf(d0i, dd, zk[2]);
          pack32(fk, zk); twiddle<0>(fk, tp, ts); fence_u32<16>(fk);
          CP(1);
          T2(sk, fk);
          CF(2);
          mbar_wait(bars + (B_KF + (ch & 1)) * 8, ((ch >> 1) & 1) ^ 1);
          wg_wait<1>();
        } else {
#pragma unroll
          for (int r = 3; r < 6; r++) mbar_wait(bars + (B_IN + r) * 8, 0);
          wg_wait<0>();
        }
        fence_regs<32>(v); fence_u32<16>(pr); CP(3);
        pack32(fv, v); fence_u32<16>(fv);
        CF(4);
        if (FWD) T1u(zu, du + U_CH / 16);
        CF(5);
        twiddle<1>(fv, tp, ts);
#pragma unroll
        for (int i = 0; i < 4; i++) stsm4(va + 2 * i * vs, fv[4 * i], fv[4 * i + 1], fv[4 * i + 2], fv[4 * i + 3]);
        if (FWD) {
          CF(6);
          wg_wait<1>(); fence_regs<32>(sk); fence_u32<16>(fk);
          pack32(kh, sk); fence_u32<16>(kh);
          CF(7);
          T1k(zk, dk);
          CF(8);
          wg_wait<1>(); fence_regs<32>(zu);
          pack32(fu, zu); twiddle<0>(fu, tp, ts); fence_u32<16>(fu);
          CP(9);
          T2(su, fu);
          CF(10);
        }
        fence_proxy_async_smem();
        bar_sync(7, 128);
        wg_fence(); CP(11);
        ss_n32_tt<0>(y, dv, dF1b); ss_n32_tt<1>(y, dv + 16, dF1b + 64); ss_n32_tt<1>(y, du, dF1b + 128); ss_n32_tt<1>(y, du + 16, dF1b + 192);
        wg_commit();
        if (FWD && t == 0) mbar_arrive(bars + (B_Y + (ch & 3)) * 8);
        CF(12);
        if (FWD) {
          wg_wait<1>(); fence_regs<32>(su); fence_u32<16>(fu); fence_regs<32>(zk); CP(13);
          if (t == 0) mbar_arrive(bars + (B_KE + (ch & 1)) * 8);
          pack32(uh, su);
          product(pr, kh, uh);
          du += U_CH / 16; dk += (ch & 1) ? -256 : 256;
          if (w >= 2) va += U_CH;
        }
        CF(14);
        wg_wait<0>(); fence_regs<16>(y); CP(15);
#pragma unroll
        for (int i = 0; i < 8; i++) yp[i] = pack_bf16(y[2 * i], y[2 * i + 1]);
        fence_u32<8>(yp);
        yq = ya;
        ya += U_CH; CP(17);
        if (t == 0) STAMP(55 + ch);
      };
#pragma unroll 1
      for (int ch = 0; ch < 7; ch++) step(ch, std::true_type());
      step(7, std::false_type());
      store_y();
    }
    fence_proxy_async_smem();
    bar_sync(7, 128);
    if (elect_one()) bulk_send(sb + OFF_U + (4 * rank + w) * U_N8 + 4 * U_CH, sb + OFF_U + (4 * (rank ^ 1) + w) * U_N8 + 6 * U_CH, U_CH + 512, bars + (B_IN + 6) * 8, rank ^ 1);
    __syncwarp();
    asm volatile("bar.arrive 9, 256;" ::: "memory");
    if (t == 0) STAMP(29);
  } else {
    asm volatile("setmaxnreg.inc.sync.aligned.u32 %0;" ::"n"(GREG));
    const int t = tid & 127, w = warp & 3, lane = t & 31, g = lane >> 2, c = lane & 3;
    if (wg == 1) {
      wait_until(c_start, COEF_T0);
      const int p = 64 * j + (t & 63) + 8 * (t & 64);
      const float Lr = bf2f(P.lam_re[p]), Li = bf2f(P.lam_im[p]);
      const uint32_t ds = __bfloat16_as_ushort(P.Dskip[128 * j + t]);
      const unsigned epoch = ld_relaxed(&g_epoch[b * 32]) + 1;
      const float dt = bf2f(__float2bfloat16_rn(expf(bf2f(P.log_dt[p]))));
      const float e = expf(dt * Lr);
      float sn, cs;
      {
        const double z = (double)(dt * Li) * 0.15915494309189535;
        sincospif(2.f * (float)(z - rint(z)), &sn, &cs);
      }
      const float lr = e * cs, li = e * sn;
      const float nr = lr - 1.0f, ni = li;
      const bool big = fabsf(Lr) >= fabsf(Li);
      const float la = big ? Lr : Li, lb = big ? Li : Lr, r = __fdiv_rn(lb, la), inv = __frcp_rn(fmaf(lb, r, la));
      const float br = (big ? fmaf(ni, r, nr) : fmaf(nr, r, ni)) * inv, bi = (big ? fmaf(-nr, r, ni) : fmaf(ni, r, -nr)) * inv;
      sts128(sb + OFF_COEF + t * 16, make_uint4(__float_as_uint(lr), __float_as_uint(li), __float_as_uint(2.f * br), __float_as_uint(-2.f * bi)));
      sts32(sb + OFF_DS + 4 * t, ds << 16);
      if (t == 0) sts32(bars + B_EPOCH * 8, epoch);
      if (t == 0) STAMP(52);
    }
    CLUSTER_WAIT();
    if (wg == 1) mbar_arrive(bars + B_COEF * 8);
    float d[128];
    uint32_t so = 0, ph = 0, po = 0;
    uint32_t ra;
    auto set_ra = [&]() { asm volatile("mapa.shared::cluster.u32 %0, %1, %2;" : "=r"(ra) : "r"(bars + (SHAKE == 2 && (t & 3) != 2 ? B_PEER : B_EMPTY) * 8), "r"((t & 1) ? rank ^ 1 : rank)); };
    set_ra();
    auto release_at = [&](uint32_t off, bool skip) {
      asm volatile("{\n.reg .pred p;\nsetp.lt.u32 p, %1, %2;\n@p mbarrier.arrive.shared::cluster.b64 _, [%0];\n}\n" ::"r"(ra + off), "r"(t), "r"(skip ? 0 : SHAKE == 2 ? 3 : SHAKE == 1 ? 1 : 2) : "memory");
    };
    auto release = [&](bool first) { release_at(po, first); };
    auto block = [&](auto ta, uint64_t da0, uint64_t db0, bool first, bool zero, int nn) {
      constexpr int PH = decltype(ta)::value, TA = PH > 0, KS = TA ? 128 : 2, QD = PH == 0 ? QD1 : PH == 1 ? QD2 : QD3;
      if (t == 0) TSTAMP(2, nn);
      mbar_wait(bars + B_FULL * 8 + so, ph);
      if (t == 0) TSTAMP(3, nn);
      const uint64_t da = da0 + (so << 8), db = db0 + (so << 8);
      wg_fence();
      wgmma_n128<TA>(d, da, db, !zero);
      wgmma_n128<TA>(d + 64, da + 512, db, !zero);
      wg_commit();
      wg_wait<1>();
      if (RELPOS == 0) release(first);
#pragma unroll
      for (int k = 1; k < 4; k++) {
        if (QD == 2 || (QD == 4 && k == 2)) wg_fence();
        wgmma_n128<TA>(d, da + KS * k, db + 2 * k, 1);
        wgmma_n128<TA>(d + 64, da + 512 + KS * k, db + 2 * k, 1);
        if (QD == 2 || (QD == 4 && k == 1)) wg_commit();
        if (RELPOS == 1 && k == 1) release(first);
        if ((QD == 2 && k < 3) || (QD == 4 && k == 1)) wg_wait<1>();
      }
      if (QD != 2) wg_commit();
      if (RELPOS == 2) release(first);
      po = so;
      so += 8;
      if (so == 8 * STAGES) { so = 0; ph ^= 1; }
    };
    {
      so = wg ? 8 * (16 % STAGES) : 0; ph = wg ? (16 / STAGES) & 1 : 0; po = 0;
      const uint64_t da0 = make_desc(sb + OFF_RING, 16, 1024, 1), db0 = make_desc(sb + OFF_RING + 16384, 16, 1024, 1);
      if (wg == 1) bar_sync(1, 256);
#pragma unroll 1
      for (int kb = 0; kb < 16; kb++) {
        if (16 * wg + kb == XPOS) { so += 8; if (so == 8 * STAGES) { so = 0; ph ^= 1; } }
        block(std::integral_constant<int, 0>(), da0, db0, kb == 0, kb == 0, 16 * wg + kb);
      }
      asm volatile("bar.arrive %0, 256;" ::"r"(1 + wg) : "memory");
    }
    mbar_wait(bars + B_COEF * 8, 0);
    const uint32_t ca = sb + OFF_COEF + (64 * wg + 8 * w + g) * 16;
    const uint32_t tag = __shfl_sync(0xffffffffu, lds32(bars + B_EPOCH * 8) & 3, 0);
    constexpr int RE = SWAPB ? 2 : 0, IM = 2 - RE;
    uint2* cp = &g_carry[((16 * wg + 2 * j) * 16 + tc) * 32 + 8 * w];
    const int ct = lane >> 3;
    uint2 cv[4];
    auto load_carry = [&](int i) {
#pragma unroll
      for (int m = 0; m < 4; m++)
        asm volatile("{\n.reg .pred p;\n.reg .b64 v;\nsetp.lt.s32 p, %3, %4;\nmov.b64 v, {%0,%1};\n@p ld.relaxed.gpu.global.b64 v, [%2];\nmov.b64 {%0,%1}, v;\n}\n"
                     : "+r"(cv[m].x), "+r"(cv[m].y) : "l"(cp + 512 * i + (lane & 7) - 32 * (1 + ct) - 128 * m), "r"(ct), "r"(tc - 4 * m) : "memory");
    };
    auto first_load = [&](int i) {
#pragma unroll
      for (int m = 0; m < 4; m++) cv[m] = make_uint2(tag, 0);
      load_carry(i);
    };
    float lr[2], li[2], pr[2], pi[2], wr[2], wi[2], vr[2], vi[2], qr[2], qi[2], er[2], ei[2], gr[2], gi[2];
    auto powers = [&](int i) {
      const uint2 cf = lds64(ca + 512 * i);
      pr[i] = lr[i] = __uint_as_float(cf.x); pi[i] = li[i] = __uint_as_float(cf.y);
#pragma unroll
      for (int s = 0; s < 4; s++) csq(pr[i], pi[i]);
      gr[i] = pr[i]; gi[i] = pi[i];
      csq(pr[i], pi[i]);
      qr[i] = pr[i]; qi[i] = pi[i];
      csq(qr[i], qi[i]);
      er[i] = qr[i]; ei[i] = qi[i];
      wr[i] = (c & 1) ? pr[i] : 1.f; wi[i] = (c & 1) ? pi[i] : 0.f;
      if (c & 2) { float x, y; cmul(wr[i], wi[i], qr[i], qi[i], x, y); wr[i] = x; wi[i] = y; }
      vr[i] = wr[i]; vi[i] = wi[i];
      csq(vr[i], vi[i]); csq(vr[i], vi[i]);
      csq(qr[i], qi[i]); csq(qr[i], qi[i]); csq(qr[i], qi[i]);
      const int src = 4 * (lane & 7) + ct;
      vr[i] = __shfl_sync(0xffffffffu, vr[i], src); vi[i] = __shfl_sync(0xffffffffu, vi[i], src);
      qr[i] = __shfl_sync(0xffffffffu, qr[i], src); qi[i] = __shfl_sync(0xffffffffu, qi[i], src);
      asm volatile("" : "+f"(wr[i]), "+f"(wi[i]), "+f"(pr[i]), "+f"(pi[i]), "+f"(er[i]), "+f"(ei[i]));
    };
    powers(0);
    if (POW2 == 0) powers(1);
    PMFENCE();
    wg_wait<0>();
    fence_regs<128>(d);
    release(false);
    if (t == 0) STAMP(10 + 10 * wg);
#pragma unroll
    for (int i = 0; i < 2; i++) {
      const float* e = d + 64 * i;
      auto chain = [&](int s0, int s1, float& sr, float& si) {
        sr = e[2 * s0 + RE]; si = e[2 * s0 + IM];
#pragma unroll
        for (int s = s0 + 1; s < s1; s++) {
          const int ia = 4 * (s >> 1) + (s & 1);
          const float nr = fmaf(-li[i], si, fmaf(lr[i], sr, e[ia + RE])), ni = fmaf(li[i], sr, fmaf(lr[i], si, e[ia + IM]));
          sr = nr; si = ni;
        }
      };
      float sr, si;
      if (POW2 == 1 && i == 1) powers(1);
      if ((GREEDY >> i) & 1) {
        float ar, ai;
        chain(0, 16, ar, ai); chain(16, 32, sr, si);
        sr = fmaf(gr[i], ar, fmaf(-gi[i], ai, sr)); si = fmaf(gr[i], ai, fmaf(gi[i], ar, si));
      } else chain(0, 32, sr, si);
      if (i == 1 && C_AT == 0) { asm volatile("pmevent 0;" : "+f"(sr), "+f"(si)::"memory"); first_load(0); }
      float ur = __shfl_up_sync(0xffffffffu, sr, 1, 4), ui = __shfl_up_sync(0xffffffffu, si, 1, 4);
      if (c >= 1) { sr = fmaf(pr[i], ur, fmaf(-pi[i], ui, sr)); si = fmaf(pr[i], ui, fmaf(pi[i], ur, si)); }
      ur = __shfl_up_sync(0xffffffffu, sr, 2, 4); ui = __shfl_up_sync(0xffffffffu, si, 2, 4);
      if (c >= 2) { sr = fmaf(er[i], ur, fmaf(-ei[i], ui, sr)); si = fmaf(er[i], ui, fmaf(ei[i], ur, si)); }
      if (c == 3 && tc < 15)
        asm volatile("{\n.reg .b64 v;\nmov.b64 v, {%1,%2};\nst.relaxed.gpu.global.b64 [%0], v;\n}\n" ::"l"(cp + 512 * i + g), "r"((__float_as_uint(sr) & ~3u) | tag), "r"(__float_as_uint(si)) : "memory");
      if (i == 1 && C_AT == 1) first_load(0);
      PMFENCE();
      if (t == 0) STAMP(11 + i + 10 * wg);
      er[i] = __shfl_up_sync(0xffffffffu, sr, 1, 4); ei[i] = __shfl_up_sync(0xffffffffu, si, 1, 4);
      if (c == 0) er[i] = ei[i] = 0.f;
    }
    uint4* hp = g_h + (32 * tc + 16 * wg + 2 * j) * 1024 + 64 * w + 4 * g + (c ^ (g >> 1));
#pragma unroll
    for (int i = 0; i < 2; i++) {
      float* e = d + 64 * i;
      const uint2 cf = lds64(ca + 512 * i + 8);
      const float mr = __uint_as_float(cf.x), mi = __uint_as_float(cf.y);
      const uint32_t gp = pack_bf16(mr, mr), gms = pack_bf16(mi, mi);
      const int NS = i == 0 ? PRE_S : 0;
#pragma unroll
      for (int s = 32 - 8 * NS; s < 32; s++) {
        const int ia = 4 * (s >> 1) + (s & 1);
        asm volatile("{\n.reg .f32 u, v, n;\nmul.f32 u, %3, %1;\nmul.f32 v, %3, %0;\nneg.f32 n, %2;\nfma.rn.f32 %0, %2, %0, u;\nfma.rn.f32 %1, n, %1, v;\n}\n"
                     : "+f"(e[ia + RE]), "+f"(e[ia + IM]) : "f"(mr), "f"(mi));
        if (s % PRE_G == PRE_G - 1) PMFENCE();
      }
      PMFENCE();
      int n = 0;
#pragma unroll 1
      while (!__all_sync(0xffffffffu, (((cv[0].x ^ tag) | (cv[1].x ^ tag) | (cv[2].x ^ tag) | (cv[3].x ^ tag)) & 3) == 0) && ++n <= (SPIN_LIMIT << 4)) load_carry(i);
      if (t == 0 && i == 0) STAMP(13 + 10 * wg);
      float hr = __uint_as_float(cv[3].x), hi = __uint_as_float(cv[3].y);
#pragma unroll
      for (int m = 2; m >= 0; m--) {
        const float nr = fmaf(qr[i], hr, fmaf(-qi[i], hi, __uint_as_float(cv[m].x))), ni = fmaf(qr[i], hi, fmaf(qi[i], hr, __uint_as_float(cv[m].y)));
        hr = nr; hi = ni;
      }
      { float x, y; cmul(hr, hi, vr[i], vi[i], x, y); hr = x; hi = y; }
      hr += __shfl_xor_sync(0xffffffffu, hr, 8); hi += __shfl_xor_sync(0xffffffffu, hi, 8);
      hr = __shfl_sync(0xffffffffu, hr, g) + __shfl_sync(0xffffffffu, hr, g + 16); hi = __shfl_sync(0xffffffffu, hi, g) + __shfl_sync(0xffffffffu, hi, g + 16);
      float sr = fmaf(wr[i], hr, fmaf(-wi[i], hi, er[i])), si = fmaf(wr[i], hi, fmaf(wi[i], hr, ei[i]));
      if (t == 0 && i == 0) STAMP(14 + 10 * wg);
#pragma unroll
      for (int i8 = 0; i8 < 4; i8++) {
        const bool pre = i8 >= 4 - NS;
        if (i8 == 4 - NS) { const float x = sr; sr = fmaf(mr, x, mi * si); si = fmaf(-mr, si, mi * x); }
        asm volatile("pmevent 0;" : "+f"(sr), "+f"(si)::"memory");
        if (i == 0 && i8 == C_AT2) first_load(1);
        const float ls = pre ? -li[i] : li[i];
#pragma unroll
        for (int s = 8 * i8; s < 8 * i8 + 8; s++) {
          const int ia = 4 * (s >> 1) + (s & 1);
          const float nr = fmaf(-ls, si, fmaf(lr[i], sr, e[ia + RE])), ni = fmaf(ls, sr, fmaf(lr[i], si, e[ia + IM]));
          sr = nr; si = ni;
          e[ia + RE] = nr; e[ia + IM] = ni;
        }
        if (P2_SPLIT) PMFENCE();
        uint32_t hp0[4], hp1[4];
#pragma unroll
        for (int m = 0; m < 4; m++) {
          const float* f = e + 16 * i8 + 4 * m;
          const uint32_t x = pack_bf16(f[RE], f[RE + 1]), y = pack_bf16(f[IM], f[IM + 1]);
          hp0[m] = pre ? x : bfma2(gp, x, bmul2(gms, y)); hp1[m] = pre ? y : bfnma2(gp, y, bmul2(gms, x));
        }
        uint4* o = hp + 512 * (i8 >> 1) + 256 * i + 32 * (i8 & 1);
        stg128(o, make_uint4(hp0[0], hp0[1], hp0[2], hp0[3]));
        stg128(o + 1024, make_uint4(hp1[0], hp1[1], hp1[2], hp1[3]));
      }
    }
    if (t == 0) STAMP(15 + 10 * wg);
    const int trow = 128 * tc + 64 * (w & 1) + 8 * (w >> 1) + g;
    const int dcol = 128 * j + 4 * c;
    asm volatile("bar.arrive %0, 160;" ::"r"(4 + wg) : "memory");
    if (wg == 0) {
      set_ra();
      uint2 xv[32];
      {
        const int gp = 2 * (g & 3) + (g >> 2);
        const uint32_t xa = sb + OFF_RING + (XPOS % STAGES) * STAGE_BYTES + (64 * (w & 1) + 8 * (w >> 1) + gp) * 128 + (c & 1) * 8;
        mbar_wait(bars + B_XI * 8, 0);
        mbar_wait(bars + (B_FULL + XPOS % STAGES) * 8, (XPOS / STAGES) & 1);
        if (t == 0) STAMP(18);
#pragma unroll
        for (int u = 0; u < 32; u++) {
          const int J = (u >> 1) & 7;
          if (X_NOXI) xv[u] = make_uint2(0, 0); else
          asm volatile("ld.shared.v2.u32 {%0,%1}, [%2];" : "=r"(xv[u].x), "=r"(xv[u].y) : "r"(xa + (J >> 2) * 16384 + (u >> 4) * 2048 + (u & 1) * 4096 + (((2 * (J & 3) + (c >> 1)) ^ gp) << 4)) : "memory");
        }
        uint32_t dep = P.zero;
#pragma unroll
        for (int u = 0; u < 32; u++) dep &= xv[u].x;
        bar_sync(3 + dep, 128);
        release_at(8 * (XPOS % STAGES), false);
      }
#pragma unroll
      for (int J = 0; J < (X_NOXI ? 0 : 8); J++) {
        const uint4 ds = lds128(sb + OFF_DS + 16 * c + 64 * J);
#pragma unroll
        for (int r = 0; r < 4; r++) {
          const int u = 16 * (r >> 1) + 2 * J + (r & 1);
          float* e = d + 8 * (u >> 1) + 2 * (u & 1);
          e[0] = __uint_as_float(bfma2(blo2(xv[u].x), ds.x, 0)); e[1] = __uint_as_float(bfma2(xv[u].x, ds.y, 0));
          e[4] = __uint_as_float(bfma2(blo2(xv[u].y), ds.z, 0)); e[5] = __uint_as_float(bfma2(xv[u].y, ds.w, 0));
        }
      }
      fence_regs<128>(d);
      if (t == 0) STAMP(17);
      so = 8 * (33 % STAGES); ph = (33 / STAGES) & 1;
      const uint64_t da0 = make_desc(sb + OFF_RING + 16384, 512, 1024, 2), db0 = make_desc(sb + OFF_RING, 16, 1024, 1);
      bar_sync(2, 256);
#pragma unroll 1
      for (int kb = 0; kb < QSW; kb++) block(std::integral_constant<int, 1>(), da0, db0, kb == 0, false, 32 + kb);
#pragma unroll 1
      for (int kb = QSW; kb < 32 - TAILB; kb++) block(std::integral_constant<int, 2>(), da0, db0, false, false, 32 + kb);
      float* op = P.out + (size_t)trow * 2048 + 1024 + dcol;
      auto mma = [&](int i, int kb, int k0, int k1) {
        const int s = (33 + kb) % STAGES;
        wg_fence();
#pragma unroll
        for (int k = k0; k < k1; k++) wgmma_n128<1>(d + 64 * i, da0 + s * 2048 + 512 * i + 128 * k, db0 + (i ? 0 : P.zero) + s * 2048 + 2 * k, 1);
        wg_commit();
      };
      auto store = [&](int i, int J0, int J1) {
#pragma unroll
        for (int J = J0; J < J1; J++) {
#pragma unroll
          for (int h = 0; h < 2; h++) {
            const float* e = d + 64 * i + 8 * J + 2 * h;
            stg128(op + (size_t)(16 * i + 32 * h) * 2048 + 16 * J, make_uint4(__float_as_uint(e[0]), __float_as_uint(e[1]), __float_as_uint(e[4]), __float_as_uint(e[5])));
          }
        }
        PMFENCE();
      };
      constexpr int K0 = 32 - TAILB;
#pragma unroll
      for (int kb = K0; kb < 32; kb++) {
        mbar_wait(bars + (B_FULL + (33 + kb) % STAGES) * 8, ((33 + kb) / STAGES) & 1);
        if (TAILB == 5 && kb == K0) { mma(0, kb, 0, 2); wg_wait<1>(); release(false); mma(0, kb, 2, 4); }
        else mma(0, kb, 0, 4);
      }
      mma(1, K0, 0, 4);
      wg_wait<1>();
      fence_regs<64>(d);
      if (t == 0) STAMP(48);
#pragma unroll
      for (int kb = K0 + 1; kb < 32; kb++) {
        mma(1, kb, 0, 4);
        if (T_FENCE) PMFENCE();
        store(0, T_ST * (kb - K0 - 1), kb == 31 ? 8 : T_ST * (kb - K0));
      }
      if (t == 0) STAMP(49);
      wg_wait<0>();
      fence_regs<64>(d + 64);
      if (t == 0) STAMP(50);
      store(1, 0, 8);
      if (t == 0) { STAMP(51); GSTAMP(51); }
      if (t == 0) g_epoch[b * 32] = lds32(bars + B_EPOCH * 8);
      return;
    }
    asm volatile("setmaxnreg.dec.sync.aligned.u32 %0;" ::"n"(488 - 2 * GREG));
  }
  {
    int lane;
    asm volatile("mov.u32 %0, %%laneid;" : "=r"(lane));
    const int w = warp & 3, h = wg & 1;
    const int lc = 2 * (lane & 2) + (lane & 1) + ((lane >> 2) & 2);
    const bool own = ((lane >> 2) & 1) == rank, spare = !own && lc < 2;
    const uint32_t ya = (spare ? sb + OFF_IN + 96 + lc * 2064 : sb + OFF_U + (own ? 4 * rank * U_N8 : 4 * (rank ^ 1) * U_N8 - 2 * U_CH) + lc * U_CH) + w * 128 + (lane >> 4) * 16 + h * 64;
    const uint32_t ys = spare ? 512 : U_N8;
    const uint32_t ob0 = sb + (h ? OFF_F1 : OFF_K) + 1024 * w, ob1 = sb + (h ? OFF_VP : OFF_K + 4096) + 1024 * w;
    uint32_t y[2][8];
    uint2 q[4][4];
    auto get_q = [&](int n, int off, int bar, int ph) {
#pragma unroll
      for (int u = 0; u < 2; u++) {
        mbar_wait(bars + (bar + u) * 8, ph);
#pragma unroll
        for (int r = 0; r < 4; r++) q[n + u][r] = lds64(sb + off + 4096 * u + 1024 * w + 256 * r + 8 * lane);
      }
    };
    auto get_y = [&](int n) { ldsm4t(y[n & 1], ya + n * ys); ldsm4t(y[n & 1] + 4, ya + n * ys + 32); };
    if (h) {
#pragma unroll
      for (int n = 0; n < 4; n += 2) {
        get_q(n, OFF_Q, B_QF, n >> 1);
        uint32_t dep = P.zero;
#pragma unroll
        for (int r = 0; r < 8; r++) dep &= q[n + (r >> 2)][r & 3].x;
        bar_sync(6 + dep, 128);
        if (w < 2 && elect_one()) load_q(5 + 2 * w - (n >> 1), OFF_Q, B_QF + n);
        __syncwarp();
      }
#pragma unroll 1
      for (int r = 0; r < 6; r++) mbar_wait(bars + (B_IN + r) * 8, 0);
      if (warp == 4 && lane == 0) STAMP(52);
      bar_sync(9, 256);
    } else get_q(0, OFF_K, B_KF, 0);
    if (O_WAIT) mbar_wait(bars + (O_WAIT == 1 ? B_HP : B_HR) * 8, 1);
    if (warp == 8 && lane == 0) STAMP(53);
    mbar_wait(bars + (B_IN + 6) * 8, 0);
    if (warp == 8 && lane == 0) STAMP(63);
    get_y(0);
    uint32_t oc = clk32() + (2 * w + h) * (O_PACE / 2);
    if (warp == 8 && lane == 0) STAMP(30);
#pragma unroll
    for (int n = 0; n < 4; n++) {
      uint32_t* o = y[n & 1];
#pragma unroll
      for (int r = 0; r < 4; r++) { o[2 * r] = bmul2(o[2 * r], q[n][r].x); o[2 * r + 1] = bmul2(o[2 * r + 1], q[n][r].y); }
#pragma unroll
      for (int u = 0; u < 2; u++) {
        const uint32_t ob = u ? ob1 : ob0;
        if (n > 0 && lane == 0) asm volatile("cp.async.bulk.wait_group.read 1;" ::: "memory");
        __syncwarp();
#pragma unroll
        for (int r = 2 * u; r < 2 * u + 2; r++)
          sts128(ob + (r & 1) * 512 + lane * 16, make_uint4(o[2 * r] << 16, o[2 * r] & 0xffff0000u, o[2 * r + 1] << 16, o[2 * r + 1] & 0xffff0000u));
        if (O_PACE) { while ((int)(clk32() - oc) < 0) { if (O_SLEEP) __nanosleep(O_SLEEP); } }
        oc += 4 * O_PACE;
        fence_proxy_async_smem();
        __syncwarp();
        if (lane == 0)
          asm volatile("cp.async.bulk.tensor.3d.global.shared::cta.bulk_group [%0, {%2, %3, %4}], [%1];\ncp.async.bulk.commit_group;"
                       ::"l"(&mO), "r"(ob), "r"(32 * slot), "r"(32 * rank + 8 * w), "r"(8 * n + 4 * h + 2 * u) : "memory");
        __syncwarp();
        if (u == 0 && n < 3) get_y(n + 1);
        if (u == 0 && n == 1 && !h) get_q(2, OFF_Q, B_QF + 2, 0);
      }
    }
    if (warp == 8 && lane == 0) mbar_arrive_cta(bars + B_ACK * 8, rank ^ 1);
    if (lane == 0) asm volatile("cp.async.bulk.wait_group 0;" ::: "memory");
    if (warp == 8 && lane == 0) STAMP(31);
    mbar_wait(bars + B_ACK * 8, 0);
  }
}

typedef CUresult (*EncodeFn)(CUtensorMap*, CUtensorMapDataType, cuuint32_t, void*, const cuuint64_t*, const cuuint64_t*, const cuuint32_t*,
                             const cuuint32_t*, CUtensorMapInterleave, CUtensorMapSwizzle, CUtensorMapL2promotion, CUtensorMapFloatOOBfill);

bool encode(EncodeFn fn, CUtensorMap* m, int rank, const void* base, const cuuint64_t* dims, const cuuint64_t* strides, const cuuint32_t* box, CUtensorMapSwizzle swz,
            CUtensorMapL2promotion promo = CU_TENSOR_MAP_L2_PROMOTION_L2_128B) {
  const cuuint32_t es[5] = {1, 1, 1, 1, 1};
  return fn(m, CU_TENSOR_MAP_DATA_TYPE_BFLOAT16, rank, const_cast<void*>(base), dims, strides, box, es, CU_TENSOR_MAP_INTERLEAVE_NONE, swz,
            promo, CU_TENSOR_MAP_FLOAT_OOB_FILL_NONE) == CUDA_SUCCESS;
}

}

extern "C" void kernel_launch(void* const* d_in, const int* in_sizes, int n_in, void* d_out, int out_size) {
  (void)in_sizes; (void)n_in; (void)out_size;
  typedef const __nv_bfloat16* In;
  const In q = (In)d_in[0], k = (In)d_in[1], v = (In)d_in[2], ssm_k = (In)d_in[4], x = (In)d_in[6], B_re = (In)d_in[9], B_im = (In)d_in[10], C_re = (In)d_in[11], C_im = (In)d_in[12];
  Params P = {};
  P.shift_k = (In)d_in[3]; P.ssm_D = (In)d_in[5]; P.lam_re = (In)d_in[7]; P.lam_im = (In)d_in[8]; P.log_dt = (In)d_in[13]; P.Dskip = (In)d_in[14];
  P.out = (float*)d_out;
  for (int cl = 0; cl < 64; cl++) P.slot[cl >> 2] |= (cl < 4 ? 4 + cl : cl < 36 ? 8 * ((cl - 4) & 7) + ((cl - 4) >> 3) : 8 * (1 + (cl - 36) % 7) + 4 + (cl - 36) / 7) << (8 * (cl & 3));
  const bool swapB = (uintptr_t)B_im < (uintptr_t)B_re;

  EncodeFn fn = nullptr;
  cudaDriverEntryPointQueryResult qr;
  cudaGetDriverEntryPoint("cuTensorMapEncodeTiled", (void**)&fn, cudaEnableDefault, &qr);
  if (!fn) return;

  CUtensorMap mX, mB, mCre, mCim, mXs, mK, mV, mQ, mS, mO;
  bool ok = true;
  {
    const cuuint64_t dims[4] = {1024, 2, 64, 16}, str[3] = {2048, 32 * 2048, 2 * 2048};
    const cuuint32_t box[4] = {64, 2, 4, 16};
    ok &= encode(fn, &mX, 4, x, dims, str, box, CU_TENSOR_MAP_SWIZZLE_128B, (CUtensorMapL2promotion)X_PROMO);
  }
  {
    const uintptr_t lo = swapB ? (uintptr_t)B_im : (uintptr_t)B_re, hi = swapB ? (uintptr_t)B_re : (uintptr_t)B_im;
    const cuuint64_t dims[4] = {1024, 8, 2, 128}, str[3] = {2048, (cuuint64_t)(hi - lo), 8 * 2048};
    const cuuint32_t box[4] = {64, 8, 2, 4};
    ok &= encode(fn, &mB, 4, (const void*)lo, dims, str, box, CU_TENSOR_MAP_SWIZZLE_128B, (CUtensorMapL2promotion)B_PROMO);
  }
  {
    const cuuint64_t dims[5] = {1024, 2, 4, 2, 64}, str[4] = {2048, 4 * 2048, 2 * 2048, 16 * 2048};
    const cuuint32_t box[5] = {64, 2, 4, 2, 4};
    ok &= encode(fn, &mCre, 5, C_re, dims, str, box, CU_TENSOR_MAP_SWIZZLE_128B, (CUtensorMapL2promotion)C_PROMO);
    ok &= encode(fn, &mCim, 5, C_im, dims, str, box, CU_TENSOR_MAP_SWIZZLE_128B, (CUtensorMapL2promotion)C_PROMO);
  }
  {
    const cuuint64_t dims[4] = {1024, 2, 4, 256}, str[3] = {4 * 2048, 2048, 8 * 2048};
    const cuuint32_t box[4] = {64, 2, 4, 16};
    ok &= encode(fn, &mXs, 4, x, dims, str, box, CU_TENSOR_MAP_SWIZZLE_128B);
  }
  {
    const cuuint64_t dims[3] = {1024, 64, 32}, str[2] = {32 * 2048, 2048};
    const cuuint32_t box[3] = {16, 32, 4};
    const cuuint64_t dimq[4] = {1024, 8, 32, 8}, strq[3] = {32 * 2048, 2048, 256 * 2048};
    const cuuint32_t boxq[4] = {16, 8, 4, 4};
    ok &= encode(fn, &mQ, 4, q, dimq, strq, boxq, CU_TENSOR_MAP_SWIZZLE_NONE, (CUtensorMapL2promotion)Q_PROMO);
    ok &= encode(fn, &mK, 3, k, dims, str, box, CU_TENSOR_MAP_SWIZZLE_32B, (CUtensorMapL2promotion)KV_PROMO);
    ok &= encode(fn, &mV, 3, v, dims, str, box, CU_TENSOR_MAP_SWIZZLE_32B, (CUtensorMapL2promotion)KV_PROMO);
  }
  {
    const cuuint64_t dims[2] = {32, 65536}, str[1] = {64};
    const cuuint32_t box[2] = {32, 64};
    ok &= encode(fn, &mS, 2, ssm_k, dims, str, box, CU_TENSOR_MAP_SWIZZLE_64B, (CUtensorMapL2promotion)S_PROMO);
  }
  {
    const cuuint64_t dims[3] = {2048, 64, 32}, str[2] = {32 * 8192, 8192};
    const cuuint32_t box[3] = {32, 8, 2};
    ok &= encode(fn, &mO, 3, d_out, dims, str, box, CU_TENSOR_MAP_SWIZZLE_NONE);
  }
  if (!ok) return;
  auto kern = swapB ? fused_kernel<1> : fused_kernel<0>;
  cudaFuncSetAttribute(kern, cudaFuncAttributeMaxDynamicSharedMemorySize, SMEM_BYTES);
  kern<<<NCTA, 512, SMEM_BYTES, cudaStreamPerThread>>>(P, mX, mB, mCre, mCim, mXs, mK, mV, mQ, mS, mO);
}
```

```cpp
#include <cuda_runtime.h>
#include <cuda_bf16.h>
#include <cuda.h>
#include <stdint.h>
#include <type_traits>

#define PROFILE 0

namespace {

constexpr int D_DIM = 1024;
constexpr int NCTA = 128;

constexpr int STAGES = 5, STAGE_BYTES = 32768;
constexpr int OFF_RING = 0;
constexpr int OFF_F1 = STAGES * STAGE_BYTES, OFF_F2 = OFF_F1 + 4096, OFF_K = OFF_F2 + 2048, OFF_VP = OFF_K + 8192, OFF_Q = OFF_VP + 4096, OFF_IN = OFF_Q + 8192;
constexpr int OFF_KV = OFF_K;
constexpr int U_CH = 528, U_N8 = 8 * U_CH, OFF_U = OFF_IN + U_N8;
constexpr int OFF_COEF = OFF_U + 8 * U_N8;
constexpr int OFF_DS = OFF_COEF + 2048, OFF_D = OFF_DS + 512;
constexpr int OFF_BAR = OFF_D + 64;
constexpr int OFF_PROF = OFF_BAR + 512;
constexpr int SMEM_BYTES = OFF_PROF + 512;
static_assert(SMEM_BYTES <= 232448 && OFF_K % 1024 == 0 && (OFF_U + 3 * U_N8) % 512 == 0 && (4 * U_N8) % 512 == 0, "smem map");
constexpr int B_FULL = 0, B_XI = 5, B_HR = 6, B_HP = 7, B_KVF = 8, B_KF = 11, B_KE = 13, B_QF = 15, B_IN = 19, B_UF = 27, B_Y = 31, B_ACK = 36,
              B_EMPTY = 38, B_COEF = 43, B_KVE = 44, B_EPOCH = 48;
#define QD1 8
#define QD2 2
#define QD3 8
#define QSW 16
#define HEAD 3
#define ST_T0 200
#define ST_DELAY 300
#define XPOS 28
#define K_T0 800
#define KV_T0 1500
#define KV_DT 560
#define KV_DV 100
#define O_PACE 0
#define POLL_NS 30
#define GREEDY 1
#define P2_SPLIT 0
#define TAILB 5
#define GREG 176
#define O_WAIT 2
#define COEF_T0 2500
#define RELPOS 0
#define C_AT 1
#define C_AT2 1
#define T_FENCE 0
#define T_ST 2
#define X_PROMO 2
#define B_PROMO 2
#define C_PROMO 2
#define KV_PROMO 2
#define Q_PROMO 2
#define S_PROMO 2
#define POW2 0
#define O_SLEEP 20
#define VO 3
#define CFM 0x40f1
constexpr int SPIN_LIMIT = 1 << 14;

struct Params {
  unsigned slot[16];
  unsigned zero;
  const __nv_bfloat16 *shift_k, *ssm_D, *lam_re, *lam_im, *log_dt, *Dskip;
  float* out;
};

__device__ __align__(1024) uint4 g_h[16 * 32 * 1024];
__device__ __align__(128) uint2 g_carry[32 * 16 * 32];
__device__ unsigned g_flagH[2 * 16 * 32];
__device__ unsigned g_epoch[NCTA * 32];
#define STAMP(i)
#define GSTAMP(i)
#define TSTAMP(k, n)
#define KSTAMP(k, n)

__device__ __forceinline__ uint64_t make_desc(uint32_t addr, uint32_t lbo, uint32_t sbo, uint32_t swz) {
  return (uint64_t)((addr & 0x3FFFF) >> 4) | ((uint64_t)(lbo >> 4) << 16) | ((uint64_t)(sbo >> 4) << 32) | ((uint64_t)swz << 62);
}
__device__ __forceinline__ void wg_fence() { asm volatile("wgmma.fence.sync.aligned;" ::: "memory"); }
__device__ __forceinline__ void wg_commit() { asm volatile("wgmma.commit_group.sync.aligned;" ::: "memory"); }
template <int N> __device__ __forceinline__ void wg_wait() { asm volatile("wgmma.wait_group.sync.aligned %0;" ::"n"(N) : "memory"); }
__device__ __forceinline__ void mbar_init(uint32_t bar, int cnt) { asm volatile("mbarrier.init.shared::cta.b64 [%0], %1;" ::"r"(bar), "r"(cnt) : "memory"); }
__device__ __forceinline__ void mbar_expect(uint32_t bar, uint32_t bytes) { asm volatile("mbarrier.arrive.expect_tx.shared::cta.b64 _, [%0], %1;" ::"r"(bar), "r"(bytes) : "memory"); }
__device__ __forceinline__ void mbar_wait(uint32_t bar, uint32_t parity) {
  uint32_t ok; int n = 0;
  do {
    asm volatile("{\n.reg .pred p;\nmbarrier.try_wait.parity.shared::cta.b64 p, [%1], %2;\nselp.u32 %0, 1, 0, p;\n}\n" : "=r"(ok) : "r"(bar), "r"(parity) : "memory");
    if (++n > SPIN_LIMIT) break;
  } while (!ok);
}
__device__ __forceinline__ void mbar_arrive(uint32_t bar) { asm volatile("mbarrier.arrive.shared::cta.b64 _, [%0];" ::"r"(bar) : "memory"); }
__device__ __forceinline__ void mbar_arrive_cta(uint32_t bar, uint32_t cta) {
  asm volatile("{\n.reg .b32 ra;\nmapa.shared::cluster.u32 ra, %0, %1;\nmbarrier.arrive.shared::cluster.b64 _, [ra];\n}\n" ::"r"(bar), "r"(cta) : "memory");
}
__device__ __forceinline__ bool elect_one() {
  uint32_t p;
  asm volatile("{\n.reg .pred P;\nelect.sync _|P, 0xffffffff;\nselp.u32 %0, 1, 0, P;\n}\n" : "=r"(p));
  return p != 0;
}
__device__ __forceinline__ void bar_sync(int id, int n) { asm volatile("bar.sync %0, %1;" ::"r"(id), "r"(n) : "memory"); }
#define TMA_LD(dim) "cp.async.bulk.tensor." dim ".shared::cluster.global.mbarrier::complete_tx::bytes"
__device__ __forceinline__ void tma2d(uint32_t dst, const CUtensorMap* m, int c0, int c1, uint32_t bar) {
  asm volatile(TMA_LD("2d") " [%0], [%1, {%3, %4}], [%2];" ::"r"(dst), "l"(m), "r"(bar), "r"(c0), "r"(c1) : "memory");
}
__device__ __forceinline__ void tma3d(uint32_t dst, const CUtensorMap* m, int c0, int c1, int c2, uint32_t bar) {
  asm volatile(TMA_LD("3d") " [%0], [%1, {%3, %4, %5}], [%2];" ::"r"(dst), "l"(m), "r"(bar), "r"(c0), "r"(c1), "r"(c2) : "memory");
}
__device__ __forceinline__ void tma4d(uint32_t dst, const CUtensorMap* m, int c0, int c1, int c2, int c3, uint32_t bar) {
  asm volatile(TMA_LD("4d") " [%0], [%1, {%3, %4, %5, %6}], [%2];" ::"r"(dst), "l"(m), "r"(bar), "r"(c0), "r"(c1), "r"(c2), "r"(c3) : "memory");
}
__device__ __forceinline__ void tma4d_mc(uint32_t dst, const CUtensorMap* m, int c0, int c1, int c2, int c3, uint32_t bar) {
  asm volatile(TMA_LD("4d") ".multicast::cluster [%0], [%1, {%3, %4, %5, %6}], [%2], %7;" ::"r"(dst), "l"(m), "r"(bar), "r"(c0), "r"(c1), "r"(c2), "r"(c3), "h"((uint16_t)3) : "memory");
}
__device__ __forceinline__ void tma5d_mc(uint32_t dst, const CUtensorMap* m, int c0, int c1, int c2, int c3, int c4, uint32_t bar) {
  asm volatile(TMA_LD("5d") ".multicast::cluster [%0], [%1, {%3, %4, %5, %6, %7}], [%2], %8;" ::"r"(dst), "l"(m), "r"(bar), "r"(c0), "r"(c1), "r"(c2), "r"(c3), "r"(c4), "h"((uint16_t)3) : "memory");
}
__device__ __forceinline__ void bulk_load(uint32_t dst, const void* src, uint32_t bytes, uint32_t bar) {
  asm volatile("cp.async.bulk.shared::cluster.global.mbarrier::complete_tx::bytes [%0], [%1], %2, [%3];" ::"r"(dst), "l"(src), "r"(bytes), "r"(bar) : "memory");
}
__device__ __forceinline__ void bulk_send(uint32_t dst, uint32_t src, uint32_t bytes, uint32_t bar, uint32_t cta) {
  asm volatile("{\n.reg .b32 rd, rb;\nmapa.shared::cluster.u32 rd, %0, %3;\nmapa.shared::cluster.u32 rb, %2, %3;\n"
               "cp.async.bulk.shared::cluster.shared::cta.mbarrier::complete_tx::bytes [rd], [%1], %4, [rb];\n}\n"
               ::"r"(dst), "r"(src), "r"(bar), "r"(cta), "r"(bytes) : "memory");
}
__device__ __forceinline__ void fence_proxy_async_smem() { asm volatile("fence.proxy.async.shared::cta;" ::: "memory"); }
__device__ __forceinline__ void fence_proxy_async_global() { asm volatile("fence.proxy.async.global;" ::: "memory"); }
__device__ __forceinline__ uint32_t clk32() { uint32_t c; asm volatile("mov.u32 %0, %%clock;" : "=r"(c)::"memory"); return c; }
__device__ __forceinline__ void wait_until(uint32_t t0, uint32_t dt) { while (clk32() - t0 < dt) __nanosleep(32); }
__device__ __forceinline__ void spin_until(uint32_t t0, uint32_t dt) { while (clk32() - t0 < dt) {} }
__device__ __forceinline__ void prefetch_map(const CUtensorMap* m) { asm volatile("prefetch.tensormap [%0];" ::"l"(m) : "memory"); }
__device__ __forceinline__ void prefetch_line(const void* p) { asm volatile("prefetch.global.L2 [%0];" ::"l"(p) : "memory"); }
__device__ __forceinline__ unsigned ld_acquire(const unsigned* p) { unsigned v; asm volatile("ld.acquire.gpu.global.u32 %0, [%1];" : "=r"(v) : "l"(p) : "memory"); return v; }
__device__ __forceinline__ unsigned ld_relaxed(const unsigned* p) { unsigned v; asm volatile("ld.relaxed.gpu.global.u32 %0, [%1];" : "=r"(v) : "l"(p) : "memory"); return v; }
__device__ __forceinline__ uint32_t lds32(uint32_t a) { uint32_t v; asm volatile("ld.shared.u32 %0, [%1];" : "=r"(v) : "r"(a)); return v; }
__device__ __forceinline__ uint2 lds64(uint32_t a) { uint2 v; asm volatile("ld.shared.v2.u32 {%0,%1}, [%2];" : "=r"(v.x), "=r"(v.y) : "r"(a) : "memory"); return v; }
__device__ __forceinline__ uint4 lds128(uint32_t a) { uint4 v; asm volatile("ld.shared.v4.u32 {%0,%1,%2,%3}, [%4];" : "=r"(v.x), "=r"(v.y), "=r"(v.z), "=r"(v.w) : "r"(a) : "memory"); return v; }
__device__ __forceinline__ void sts32(uint32_t a, uint32_t v) { asm volatile("st.shared.u32 [%0], %1;" ::"r"(a), "r"(v) : "memory"); }
__device__ __forceinline__ void sts128(uint32_t a, uint4 v) { asm volatile("st.shared.v4.u32 [%0], {%1,%2,%3,%4};" ::"r"(a), "r"(v.x), "r"(v.y), "r"(v.z), "r"(v.w) : "memory"); }
__device__ __forceinline__ void ldsm4(uint32_t* r, uint32_t a) { asm volatile("ldmatrix.sync.aligned.m8n8.x4.shared.b16 {%0,%1,%2,%3}, [%4];" : "=r"(r[0]), "=r"(r[1]), "=r"(r[2]), "=r"(r[3]) : "r"(a) : "memory"); }
__device__ __forceinline__ void ldsm4t(uint32_t* r, uint32_t a) { asm volatile("ldmatrix.sync.aligned.m8n8.x4.trans.shared.b16 {%0,%1,%2,%3}, [%4];" : "=r"(r[0]), "=r"(r[1]), "=r"(r[2]), "=r"(r[3]) : "r"(a) : "memory"); }
__device__ __forceinline__ void stsm4t(uint32_t a, uint32_t r0, uint32_t r1, uint32_t r2, uint32_t r3) {
  asm volatile("stmatrix.sync.aligned.m8n8.x4.trans.shared.b16 [%0], {%1,%2,%3,%4};" ::"r"(a), "r"(r0), "r"(r1), "r"(r2), "r"(r3) : "memory");
}
__device__ __forceinline__ uint4 ldg128_nc(const void* p) { uint4 v; asm volatile("ld.global.nc.L1::no_allocate.v4.u32 {%0,%1,%2,%3}, [%4];" : "=r"(v.x), "=r"(v.y), "=r"(v.z), "=r"(v.w) : "l"(p)); return v; }
__device__ __forceinline__ void stg128(void* p, uint4 v) { asm volatile("st.global.L1::no_allocate.v4.u32 [%0], {%1,%2,%3,%4};" ::"l"(p), "r"(v.x), "r"(v.y), "r"(v.z), "r"(v.w) : "memory"); }
__device__ __forceinline__ uint32_t pack_bf16(float lo, float hi) { uint32_t r; asm("cvt.rn.bf16x2.f32 %0, %1, %2;" : "=r"(r) : "f"(hi), "f"(lo)); return r; }
__device__ __forceinline__ uint32_t bmul2(uint32_t a, uint32_t b) { uint32_t r; asm("mul.rn.bf16x2 %0, %1, %2;" : "=r"(r) : "r"(a), "r"(b)); return r; }
__device__ __forceinline__ uint32_t bfma2(uint32_t a, uint32_t b, uint32_t c) { uint32_t r; asm("fma.rn.bf16x2 %0, %1, %2, %3;" : "=r"(r) : "r"(a), "r"(b), "r"(c)); return r; }
__device__ __forceinline__ uint32_t blo2(uint32_t a) { uint32_t r; asm("{\n.reg .b16 l, h;\nmov.b32 {l, h}, %1;\nmov.b32 %0, {l, l};\n}" : "=r"(r) : "r"(a)); return r; }
__device__ __forceinline__ float bf2f(__nv_bfloat16 v) { return __bfloat162float(v); }

#define R8(d, o) "+f"(d[o]), "+f"(d[o + 1]), "+f"(d[o + 2]), "+f"(d[o + 3]), "+f"(d[o + 4]), "+f"(d[o + 5]), "+f"(d[o + 6]), "+f"(d[o + 7])
#define R16(d, o) R8(d, o), R8(d, o + 8)
#define R64(d, o) R16(d, o), R16(d, o + 16), R16(d, o + 32), R16(d, o + 48)
template <int TA> __device__ __forceinline__ void wgmma_n128(float* d, uint64_t da, uint64_t db, int scale_d) {
  asm volatile("{\n.reg .pred p;\nsetp.ne.b32 p, %66, 0;\n"
    "wgmma.mma_async.sync.aligned.m64n128k16.f32.bf16.bf16 {"
    "%0,%1,%2,%3,%4,%5,%6,%7,%8,%9,%10,%11,%12,%13,%14,%15,%16,%17,%18,%19,%20,%21,%22,%23,%24,%25,%26,%27,%28,%29,%30,%31,"
    "%32,%33,%34,%35,%36,%37,%38,%39,%40,%41,%42,%43,%44,%45,%46,%47,%48,%49,%50,%51,%52,%53,%54,%55,%56,%57,%58,%59,%60,%61,%62,%63"
    "}, %64, %65, p, 1, 1, %67, 0;\n}\n"
    : R64(d, 0)
    : "l"(da), "l"(db), "r"(scale_d), "n"(TA));
}
template <int N> __device__ __forceinline__ void fence_regs(float* d) {
#pragma unroll
  for (int i = 0; i < N; i++) asm volatile("" : "+f"(d[i])::"memory");
}
#define PMFENCE() asm volatile("pmevent 0;" ::: "memory")
__device__ __forceinline__ void cmul(float ar, float ai, float br, float bi, float& cr, float& ci) {
  cr = ar * br - ai * bi; ci = ar * bi + ai * br;
}
__device__ __forceinline__ void csq(float& r, float& i) { const float x = fmaf(r, r, -i * i), y = (r + r) * i; r = x; i = y; }

#define W8(d, o) "=f"(d[o]), "=f"(d[o + 1]), "=f"(d[o + 2]), "=f"(d[o + 3]), "=f"(d[o + 4]), "=f"(d[o + 5]), "=f"(d[o + 6]), "=f"(d[o + 7])
#define L16 "{%0,%1,%2,%3,%4,%5,%6,%7,%8,%9,%10,%11,%12,%13,%14,%15}"
#define L32 "{%0,%1,%2,%3,%4,%5,%6,%7,%8,%9,%10,%11,%12,%13,%14,%15,%16,%17,%18,%19,%20,%21,%22,%23,%24,%25,%26,%27,%28,%29,%30,%31}"
template <int ACC, int TB> __device__ __forceinline__ void rs_n32(float* d, const uint32_t* a, uint64_t db) {
  if constexpr (ACC) asm volatile("wgmma.mma_async.sync.aligned.m64n32k16.f32.bf16.bf16 " L16 ", {%16,%17,%18,%19}, %20, 1, 1, 1, %21;" : R16(d, 0) : "r"(a[0]), "r"(a[1]), "r"(a[2]), "r"(a[3]), "l"(db), "n"(TB));
  else asm volatile("wgmma.mma_async.sync.aligned.m64n32k16.f32.bf16.bf16 " L16 ", {%16,%17,%18,%19}, %20, 0, 1, 1, %21;" : W8(d, 0), W8(d, 8) : "r"(a[0]), "r"(a[1]), "r"(a[2]), "r"(a[3]), "l"(db), "n"(TB));
}
template <int ACC, int TB> __device__ __forceinline__ void ss_n64(float* d, uint64_t da, uint64_t db) {
  if constexpr (ACC) asm volatile("wgmma.mma_async.sync.aligned.m64n64k16.f32.bf16.bf16 " L32 ", %32, %33, 1, 1, 1, 0, %34;" : R16(d, 0), R16(d, 16) : "l"(da), "l"(db), "n"(TB));
  else asm volatile("wgmma.mma_async.sync.aligned.m64n64k16.f32.bf16.bf16 " L32 ", %32, %33, 0, 1, 1, 0, %34;" : W8(d, 0), W8(d, 8), W8(d, 16), W8(d, 24) : "l"(da), "l"(db), "n"(TB));
}
template <int ACC> __device__ __forceinline__ void ss_n32_tt(float* d, uint64_t da, uint64_t db) {
  if constexpr (ACC) asm volatile("wgmma.mma_async.sync.aligned.m64n32k16.f32.bf16.bf16 " L16 ", %16, %17, 1, 1, 1, 1, 1;" : R16(d, 0) : "l"(da), "l"(db));
  else asm volatile("wgmma.mma_async.sync.aligned.m64n32k16.f32.bf16.bf16 " L16 ", %16, %17, 0, 1, 1, 1, 1;" : W8(d, 0), W8(d, 8) : "l"(da), "l"(db));
}
__device__ __forceinline__ void stsm4(uint32_t a, uint32_t r0, uint32_t r1, uint32_t r2, uint32_t r3) {
  asm volatile("stmatrix.sync.aligned.m8n8.x4.shared.b16 [%0], {%1,%2,%3,%4};" ::"r"(a), "r"(r0), "r"(r1), "r"(r2), "r"(r3) : "memory");
}
template <int N> __device__ __forceinline__ void fence_u32(uint32_t* d) {
#pragma unroll
  for (int i = 0; i < N; i++) asm volatile("" : "+r"(d[i])::"memory");
}
__device__ __forceinline__ void pack32(uint32_t* f, const float* z) {
#pragma unroll
  for (int i = 0; i < 16; i++) f[i] = pack_bf16(z[2 * i], z[2 * i + 1]);
}
template <int INV> __device__ __forceinline__ void twiddle(uint32_t* f, const uint32_t* tp, const uint32_t* ts) {
#pragma unroll
  for (int i = 0; i < 8; i++) {
    uint32_t x = f[2 * i + INV], y = f[2 * i + 1 - INV];
    x = bfma2(tp[i & 3], y, x); y = bfma2(ts[i & 3], x, y); x = bfma2(tp[i & 3], y, x);
    f[2 * i + INV] = x; f[2 * i + 1 - INV] = y;
  }
}
__device__ __forceinline__ uint32_t bfnma2(uint32_t a, uint32_t b, uint32_t c) { uint32_t r; asm("{\n.reg .b32 t;\nmul.bf16x2 t, %1, %2;\nsub.bf16x2 %0, %3, t;\n}" : "=r"(r) : "r"(a), "r"(b), "r"(c)); return r; }
__device__ __forceinline__ uint32_t bfms2(uint32_t a, uint32_t b, uint32_t c) { uint32_t r; asm("{\n.reg .b32 t;\nmul.bf16x2 t, %1, %2;\nsub.bf16x2 %0, t, %3;\n}" : "=r"(r) : "r"(a), "r"(b), "r"(c)); return r; }
template <int ADD> __device__ __forceinline__ void bimac(uint32_t* o, const uint32_t* a, const uint32_t* b, const uint32_t* c) {
#pragma unroll
  for (int J = 0; J < 2; J++) {
    const uint32_t Pr = a[2 * J], Pi = a[2 * J + 1], Qr = a[2 * J + 4], Qi = a[2 * J + 5], pr = b[2 * J], pi = b[2 * J + 1], qr = b[2 * J + 4], qi = b[2 * J + 5];
    uint32_t x0, x1, x2, x3;
    if (ADD == 0) { x0 = bmul2(Pr, pr); x1 = bmul2(Pr, pi); x2 = bmul2(Pr, qr); x3 = bmul2(Pr, qi); }
    if (ADD == 1) { x0 = bfma2(Pr, pr, c[2 * J]); x1 = bfma2(Pr, pi, c[2 * J + 1]); x2 = bfma2(Pr, qr, c[2 * J + 4]); x3 = bfma2(Pr, qi, c[2 * J + 5]); }
    if (ADD == 2) { x0 = bfma2(Pr, pr, c[2 * J + 1]); x1 = bfms2(Pr, pi, c[2 * J]); x2 = bfma2(Pr, qr, c[2 * J + 5]); x3 = bfms2(Pr, qi, c[2 * J + 4]); }
    x0 = bfnma2(Pi, pi, x0); x1 = bfma2(Pi, pr, x1); x2 = bfnma2(Pi, qi, x2); x3 = bfma2(Pi, qr, x3);
    x0 = bfnma2(Qr, qr, x0); x1 = bfnma2(Qr, qi, x1); x2 = bfma2(Qr, pr, x2); x3 = bfma2(Qr, pi, x3);
    x0 = bfma2(Qi, qi, x0); x1 = bfnma2(Qi, qr, x1); x2 = bfnma2(Qi, pi, x2); x3 = bfma2(Qi, pr, x3);
    o[2 * J] = x0; o[2 * J + 1] = x1; o[2 * J + 4] = x2; o[2 * J + 5] = x3;
  }
}
__device__ __forceinline__ void sincos8k(int n, float& s, float& c) {
  const float x = (float)((n << 19) >> 19) * (6.283185307179586f / 8192.f);
  s = __sinf(x); c = __cosf(x);
}
__device__ __forceinline__ void fft_tables(uint32_t f1a, uint32_t f2a, int w, int lane, uint32_t* tp, uint32_t* ts, float& d0r, float& d0i) {
  const int c = lane & 3, f1 = 8 * w + (lane >> 2);
#pragma unroll 1
  for (int J = 3; J >= 0; J--) {
    const int a = 8 * J + 2 * c;
    float s0, c0, s1, c1;
    sincos8k(64 * (4 * f1 + 1) * a + 31 * (4 * f1 - 63), d0i, d0r); sincos8k(64 * (4 * f1 + 1) * (a + 1) + 31 * (4 * f1 - 63), s1, c1);
    d0r *= 0.125f; d0i *= 0.125f;
    sts32(f1a + w * 1024 + J * 128 + lane * 4, pack_bf16(d0r, 0.125f * c1)); sts32(f1a + w * 1024 + 512 + J * 128 + lane * 4, pack_bf16(d0i, 0.125f * s1));
    sincos8k(128 * (2 * (a & 15) + 1) * f1 - 128 * (a & 16), s0, c0); sincos8k(128 * (2 * (a & 15) + 3) * f1 - 128 * (a & 16), s1, c1);
    sts32(f2a + w * 512 + J * 128 + lane * 4, pack_bf16(c0, c1));
    sincos8k((4 * f1 - 63) * (2 * a - 31), s0, c0); sincos8k((4 * f1 - 63) * (2 * a - 29), s1, c1);
#pragma unroll
    for (int i = 3; i > 0; i--) { ts[i] = ts[i - 1]; tp[i] = tp[i - 1]; }
    ts[0] = pack_bf16(s0, s1); tp[0] = pack_bf16(-__fdividef(s0, 1.f + c0), -__fdividef(s1, 1.f + c1));
  }
  if (c != 0) d0r = d0i = 0.f;
}

template <int SWAPB>
__global__ void __cluster_dims__(2, 1, 1) __launch_bounds__(512, 1)
fused_kernel(const __grid_constant__ Params P, const __grid_constant__ CUtensorMap mX, const __grid_constant__ CUtensorMap mB,
             const __grid_constant__ CUtensorMap mCre, const __grid_constant__ CUtensorMap mCim, const __grid_constant__ CUtensorMap mXs,
             const __grid_constant__ CUtensorMap mK, const __grid_constant__ CUtensorMap mV, const __grid_constant__ CUtensorMap mQ, const __grid_constant__ CUtensorMap mS,
             const __grid_constant__ CUtensorMap mO) {
  extern __shared__ __align__(1024) uint8_t smem_raw[];
  const uint32_t sb = (uint32_t)__cvta_generic_to_shared(smem_raw);
  const uint32_t bars = sb + OFF_BAR;
  const int slot = (P.slot[blockIdx.x >> 3] >> (4 * (blockIdx.x & 6))) & 63, rank = blockIdx.x & 1;
  const int j = slot & 7, tc = 2 * (slot >> 3) + rank, b = 2 * slot + rank;
  const int tid = threadIdx.x;
  const int warp = __shfl_sync(0xffffffffu, tid >> 5, 0);
  const int wg = warp >> 2;
  const uint32_t c_start = clk32();
  auto kblock = [&](int n) { return ((n & 14) == 0 || (n & 14) == 2 * j ? n ^ (2 * j) : n) & 31; };
  auto send_y = [&](int r) {
    const uint32_t src = sb + OFF_U + 4 * (rank ^ 1) * U_N8 + r * U_CH, dst = r >= 2 ? sb + OFF_U + 4 * rank * U_N8 + (r - 2) * U_CH : sb + OFF_IN + 96 + r * 2064;
#pragma unroll 1
    for (int n = 0; n < 4; n++) bulk_send(dst + n * (r >= 2 ? U_N8 : 512), src + n * U_N8, 512, bars + (B_IN + r) * 8, rank ^ 1);
  };
  auto load_q = [&](int i, int off, int bar) {
    const uint32_t fb = bars + bar * 8 + 4 * (i & 2);
    mbar_expect(fb, 4096); tma4d(sb + off + 2048 * (i & 2), &mQ, 16 * slot, 0, 4 * i, 4 * rank, fb);
  };
  auto head = [&](int n) {
    const uint32_t fb = bars + (B_FULL + n) * 8, dst = sb + OFF_RING + n * STAGE_BYTES;
    mbar_expect(fb, STAGE_BYTES);
    tma4d(dst + 16384, &mX, 64 * n, 0, 4 * tc, 0, fb);
    tma4d(dst, &mB, 64 * n, 0, 0, 8 * j, fb);
    tma4d(dst + 8192, &mB, 64 * n, 0, 0, 8 * j + 4, fb);
  };
  if (warp == 0 && elect_one()) {
    STAMP(0); GSTAMP(0);
#pragma unroll
    for (int s = 0; s < STAGES; s++) mbar_init(bars + (B_FULL + s) * 8, 1);
    head(0);
    STAMP(1);
    asm volatile("fence.mbarrier_init.release.cluster;" ::: "memory");
  }
  if (wg == 3 && elect_one()) {
    if (warp < 15) {
#pragma unroll
      for (int s = 0; s < 11; s++) mbar_init(bars + 8 * B_XI + (warp & 3) * 88 + 8 * s, 1);
    } else {
#pragma unroll
      for (int s = B_EMPTY; s < B_KVE + 3; s++) mbar_init(bars + 8 * s, s < B_COEF ? 2 : s == B_COEF ? 128 : 4);
    }
    asm volatile("fence.mbarrier_init.release.cluster;" ::: "memory");
  }
  __syncwarp();
  asm volatile("barrier.cluster.arrive.relaxed.aligned;" ::: "memory");
  if (warp == 0 && elect_one()) {
#pragma unroll 1
    for (int n = 1; n < HEAD; n++) { spin_until(c_start, ST_T0 + n * ST_DELAY); head(n); }
  }
  __syncwarp();
#define CLUSTER_WAIT() asm volatile("barrier.cluster.wait.aligned;" ::: "memory")

  if (wg == 3) {
    asm volatile("setmaxnreg.dec.sync.aligned.u32 24;");
    CLUSTER_WAIT();
    if (warp < 14) {
      if (elect_one()) {
        uint32_t so = 8 * (HEAD % STAGES), ph = HEAD < STAGES;
        auto step = [&](auto issue) {
          mbar_wait(bars + B_EMPTY * 8 + so, ph);
          issue(sb + OFF_RING + (so << 12), bars + B_FULL * 8 + so);
          so += 8;
          if (so == 8 * STAGES) { so = 0; ph ^= 1; }
        };
        if (warp == 12) {
          auto g1 = [&](int n0, int n1, int grp) {
#pragma unroll 1
            for (int n = n0; n < n1; n++) step([&](uint32_t dst, uint32_t fb) { mbar_expect(fb, STAGE_BYTES); tma4d_mc(dst + rank * 8192, &mB, n * 64, 0, 0, grp + 4 * rank, fb); });
          };
#pragma unroll 1
          for (int n = HEAD; n < STAGES; n++) { spin_until(c_start, ST_T0 + n * ST_DELAY); g1(n, n + 1, 8 * j); }
          g1(STAGES, 16, 8 * j);
          g1(0, XPOS - 16, 8 * j + 64);
          step([&](uint32_t dst, uint32_t fb) { mbar_expect(fb, STAGE_BYTES); tma4d(dst, &mXs, 128 * j, 0, 0, 16 * tc, fb); mbar_arrive(bars + B_XI * 8); });
          g1(XPOS - 16, 16, 8 * j + 64);
#pragma unroll 1
          for (int n = 0; n < 32; n += 2) {
            const int col = kblock(n) * 32;
            if (n == 2 * (slot >> 3)) {
#pragma unroll
              for (int part = 0; part < 2; part++)
                asm volatile("cp.async.bulk.prefetch.tensor.5d.L2.global [%0, {%1, %2, %2, %2, %3}];" ::"l"(part ? &mCim : &mCre), "r"(512 + 32 * n), "r"(0), "r"(8 * j + 4 * rank) : "memory");
            }
#pragma unroll
            for (int part = 0; part < 2; part++)
              step([&](uint32_t dst, uint32_t fb) { mbar_expect(fb, STAGE_BYTES); tma5d_mc(dst + rank * 8192, part ? &mCim : &mCre, col, 0, 0, 0, 8 * j + 4 * rank, fb); });
          }
        } else {
          auto g1 = [&](int n0, int n1, int nb) {
#pragma unroll 1
            for (int n = n0; n < n1; n++) step([&](uint32_t dst, uint32_t fb) { tma4d(dst + 16384, &mX, n * 64, 0, 4 * tc, 0, fb); TSTAMP(1, n + nb); });
          };
          auto g2 = [&](int n0, int n1) {
#pragma unroll 1
            for (int n = n0; n < n1; n++) step([&](uint32_t dst, uint32_t fb) { bulk_load(dst + 16384, g_h + (32 * tc + kblock(n)) * 1024, 16384, fb); TSTAMP(1, n + 32); });
          };
#pragma unroll 1
          for (int n = HEAD; n < STAGES; n++) { spin_until(c_start, ST_T0 + n * ST_DELAY); g1(n, n + 1, 0); }
          g1(STAGES, 16, 0);
          g1(0, XPOS - 16, 16);
          step([&](uint32_t dst, uint32_t fb) { tma4d(dst + 16384, &mXs, 128 * j + 64, 0, 0, 16 * tc, fb); });
          g1(XPOS - 16, 16, 16);
#pragma unroll 1
          for (int v = 0; v < 2; v++) {
            STAMP(4 + v);
            mbar_wait(bars + B_HP * 8, v);
            fence_proxy_async_global();
            STAMP(6 + v);
            g2(16 * v, 16 * v + 2);
            mbar_wait(bars + B_HR * 8, v);
            fence_proxy_async_global();
            g2(16 * v + 2, 16 * v + 16);
          }
        }
      }
    } else if (warp == 15) {
      mbar_wait(bars + B_COEF * 8, 0);
      const unsigned epoch = lds32(bars + B_EPOCH * 8);
#pragma unroll 1
      for (int v = 0; v < 2; v++) {
        unsigned* fp = &g_flagH[(16 * v + tc) * 32];
        bar_sync(4 + v, 160);
        if (elect_one()) {
          asm volatile("red.release.gpu.global.add.u32 [%0], 1;" ::"l"(fp) : "memory");
          mbar_arrive(bars + B_HP * 8);
          STAMP(16 + 10 * v);
          int it = 0;
          while (ld_acquire(fp) != 8 * epoch && ++it < (SPIN_LIMIT << 4)) __nanosleep(POLL_NS);
          STAMP(2 + v);
          mbar_arrive(bars + B_HR * 8);
        }
        __syncwarp();
      }
    } else if (elect_one()) {
      const int ch0 = 16 * slot;
      auto load_k = [&](int s, uint32_t dst) { const uint32_t fb = bars + (B_KF + (s & 1)) * 8; mbar_expect(fb, 4096); tma2d(dst, &mS, 0, 64 * (8 * b + s), fb); };
      prefetch_map(&mS); prefetch_map(&mK); prefetch_map(&mV);
      wait_until(c_start, K_T0);
      load_k(0, sb + OFF_U + (4 * rank + 3) * U_N8); load_k(1, sb + OFF_U + (4 * rank + 3) * U_N8 - 4096);
      {
        uint32_t so = 16, ph = 1;
#pragma unroll 1
        for (int e = 0; e < 9; e++) {
          const uint32_t fb = bars + B_KVF * 8 + so, dst = sb + OFF_KV + (so << 10);
          wait_until(c_start, KV_T0 + (e ? 2 * e - 1 : 0) * KV_DT);
          mbar_wait(bars + B_KVE * 8 + so, ph);
          const uint32_t c1 = clk32();
          mbar_expect(fb, e ? 8192 : 4096);
          if (e > 0) KSTAMP(1, e - 1);
          tma3d(dst, &mK, ch0, 32 * rank - (e == 0), (4 * e - 4) & 31, fb);
          if (e > 0) { wait_until(c1, KV_DV); tma3d(dst + 4096, &mV, ch0, 32 * rank, 4 * e - 4, fb); }
          so += 8;
          if (so == 24) so = 0;
          if (so == 16) ph ^= 1;
        }
      }
      prefetch_map(&mCre); prefetch_map(&mCim); prefetch_map(&mXs); prefetch_map(&mQ); prefetch_map(&mO);
      mbar_wait(bars + B_KVE * 8, 0);
      load_k(2, sb + OFF_K); load_k(3, sb + OFF_K + 4096);
      mbar_wait(bars + (B_UF + 3) * 8, 0);
#pragma unroll 1
      for (int ch = 0; ch < 7; ch++) {
        if (ch > 0) {
          mbar_wait(bars + (B_Y + (ch & 3)) * 8, ch >> 2);
          if (ch > 2) mbar_wait(bars + (B_IN + ch - 3) * 8, 0);
          send_y(ch - 1);
        }
        if (ch < 6) {
          mbar_wait(bars + (B_KE + (ch & 1)) * 8, (ch >> 1) & 1);
          if (ch < 4) load_k(ch + 4, sb + OFF_K + (ch & 1) * 4096);
          if (ch >= 2) load_q(2 * (ch & 1) + (ch < 4), ch < 4 ? OFF_Q : OFF_K, ch < 4 ? B_QF : B_KF);
        }
      }
    }
    return;
  } else if (wg == 2) {
    asm volatile("setmaxnreg.inc.sync.aligned.u32 %0;" ::"n"(488 - 2 * GREG));
    const int t = tid & 127, w = warp & 3, lane = t & 31, g = lane >> 2, c = lane & 3;
    const uint4 s2[2] = {ldg128_nc(P.shift_k + (8 * b + 2 * c) * 4), ldg128_nc(P.shift_k + (8 * (b ^ 1) + 2 * c) * 4)};
    const uint32_t dskip = __bfloat16_as_ushort(P.ssm_D[8 * b + (t & 7)]);
    uint32_t tp[4] = {}, ts[4] = {};
    float d0r, d0i;
    fft_tables(sb + OFF_F1, sb + OFF_F2, w, lane, tp, ts, d0r, d0i);
    if (t == 0) STAMP(19);
    CLUSTER_WAIT();
    if (t < 12) mbar_expect(bars + (B_IN + t) * 8, t < 6 ? 2048 : t < 8 ? 4 * (U_CH + 512) : U_N8);
    if (t < 8) sts32(sb + OFF_D + 4 * t, dskip << 16);
    const uint64_t dF1a = make_desc(sb + OFF_F1, 128, 512, 0), dF1b = make_desc(sb + OFF_F1, 512, 128, 0);
    const uint64_t dF2f = make_desc(sb + OFF_F2, 512, 128, 0), dF2i = make_desc(sb + OFF_F2, 128, 512, 0);
    auto T1k = [&](float* z, uint64_t dk) { wg_fence(); ss_n64<0, 1>(z, dF1a, dk); ss_n64<1, 1>(z, dF1a + 16, dk + 64); wg_commit(); };
    auto T1u = [&](float* z, uint64_t du) { wg_fence(); ss_n64<0, 0>(z, dF1a, du); ss_n64<1, 0>(z, dF1a + 16, du + 16); wg_commit(); };
    auto T2 = [&](float* s, const uint32_t* f) {
      wg_fence();
      rs_n32<0, 1>(s, f, dF2f); rs_n32<0, 1>(s + 16, f + 8, dF2f); rs_n32<1, 1>(s, f + 4, dF2f + 64); rs_n32<1, 1>(s + 16, f + 12, dF2f + 64);
      wg_commit();
    };
    auto product = [&](uint32_t* pr, const uint32_t* kh, const uint32_t* uh) {
      bimac<0>(pr, kh, uh, pr); bimac<2>(pr + 8, kh + 8, uh, pr); bimac<1>(pr + 8, kh, uh + 8, pr + 8);
      fence_u32<16>(pr);
    };
    float zk[32] = {};
    uint32_t pr[16];
    {
      uint32_t kh0[16];
      {
        float z0[32], sk[32];
        uint32_t fk[16];
        const uint64_t dk = make_desc(sb + OFF_U + (4 * rank + 3) * U_N8, 2048, 512, 2);
        fence_proxy_async_smem();
        bar_sync(7, 128);
        mbar_wait(bars + B_KF * 8, 0);
        T1k(z0, dk);
        mbar_wait(bars + (B_KF + 1) * 8, 0);
        T1k(zk, dk - 256);
        wg_wait<0>(); fence_regs<32>(z0); fence_regs<32>(zk);
        const float dd = __uint_as_float(lds32(sb + OFF_D));
        z0[0] = fmaf(d0r, dd, z0[0]); z0[2] = fmaf(d0i, dd, z0[2]);
        pack32(fk, z0); twiddle<0>(fk, tp, ts); fence_u32<16>(fk);
        T2(sk, fk);
        wg_wait<0>(); fence_regs<32>(sk); fence_u32<16>(fk);
        pack32(kh0, sk); fence_u32<16>(kh0);
      }
      {
        uint32_t sk[2][4], kx[2][8];
#pragma unroll
        for (int o = 0; o < 2; o++) {
          sk[o][0] = __byte_perm(s2[o].x, s2[o].z, 0x5410); sk[o][1] = __byte_perm(s2[o].x, s2[o].z, 0x7632);
          sk[o][2] = __byte_perm(s2[o].y, s2[o].w, 0x5410); sk[o][3] = __byte_perm(s2[o].y, s2[o].w, 0x7632);
        }
        const uint32_t la = sb + OFF_KV + (lane >> 3) * 1024 + (8 * w + (lane & 7)) * 32 + ((rank ^ ((lane >> 2) & 1)) << 4);
        const uint32_t uo = (lane & 7) * U_CH + w * 128 + (lane >> 3) * 16;
        mbar_wait(bars + (B_KVF + 2) * 8, 0);
        if (t == 0) STAMP(27);
        ldsm4(kx[0], la + 16384); ldsm4(kx[1], (la ^ 16) + 16384);
        if (lane == 0) mbar_arrive(bars + (B_KVE + 2) * 8 + (kx[0][1] & kx[1][1] & P.zero));
        uint32_t so = 0, ph = 0;
#pragma unroll 1
        for (int n = 0; n < 4; n++) {
          const uint32_t own = sb + OFF_U + (4 * rank + n) * U_N8, box = n < 3 ? sb + OFF_U + (4 * (rank ^ 1) + n + 1) * U_N8 : sb + OFF_IN;
#pragma unroll
          for (int e = 0; e < 2; e++) {
            uint32_t vx[2][4];
            mbar_wait(bars + B_KVF * 8 + so, ph);
            if (t == 0) KSTAMP(2, 2 * n + e);
#pragma unroll
            for (int o = 0; o < 2; o++) { ldsm4(kx[o] + 4, (la ^ (16 * o)) + (so << 10)); ldsm4(vx[o], (la ^ (16 * o)) + (so << 10) + 4096); }
            if (lane == 0) mbar_arrive(bars + B_KVE * 8 + so + (kx[0][4] & kx[1][4] & vx[0][0] & vx[1][0] & P.zero));
#pragma unroll
            for (int o = 0; o < 2; o++) {
#pragma unroll
              for (int i = 0; i < 4; i++) vx[o][i] = bmul2(bfma2(kx[o][i + 4], sk[o][0], bfma2(kx[o][i + 3], sk[o][1], bfma2(kx[o][i + 2], sk[o][2], bmul2(kx[o][i + 1], sk[o][3])))), vx[o][i]);
              stsm4t((o ? box : own) + uo + e * 64, vx[o][0], vx[o][1], vx[o][2], vx[o][3]);
              kx[o][1] = kx[o][5]; kx[o][2] = kx[o][6]; kx[o][3] = kx[o][7];
            }
            if (t == 0) KSTAMP(3, 2 * n + e);
            so += 8;
            if (so == 24) so = 0;
            if (so == 16) ph ^= 1;
          }
          fence_proxy_async_smem();
          bar_sync(7, 128);
          if (w == 0 && elect_one()) {
            if (n > 0) mbar_wait(bars + B_UF * 8 + 8 * (n - 1), 0);
            bulk_send(own, box, U_N8, bars + B_UF * 8 + 8 * n, rank ^ 1);
          }
          __syncwarp();
        }
        if (t == 0) STAMP(28);
      }
      float zu[32], su[32];
      uint32_t fu[16], uh[16];
#pragma unroll
      for (int n = 0; n < 4; n++) mbar_wait(bars + (B_UF + n) * 8, 0);
      T1u(zu, make_desc(sb + OFF_U, 128, U_N8, 0));
      wg_wait<0>(); fence_regs<32>(zu);
      pack32(fu, zu); twiddle<0>(fu, tp, ts); fence_u32<16>(fu);
      T2(su, fu);
      wg_wait<0>(); fence_regs<32>(su); fence_u32<16>(fu);
      pack32(uh, su);
      product(pr, kh0, uh);
      if (t == 0) STAMP(54);
    }
    {
#define CF(i) do { if ((CFM >> (i)) & 1) PMFENCE(); } while (0)
#define CP(i)
      const uint32_t vs = w < 2 ? 512 : U_N8;
      uint32_t va = (w < 2 ? sb + OFF_VP : sb + OFF_U) + ((lane >> 4) & 1) * vs + (w & 1) * 256 + (lane & 15) * 16;
      uint32_t ya = sb + OFF_U + (2 * w + ((lane >> 3) & 1)) * U_N8 + (lane >> 4) * 128 + (lane & 7) * 16;
      uint64_t du = make_desc(sb + OFF_U, 128, U_N8, 0), dk = make_desc(sb + OFF_K, 2048, 512, 2);
      const uint64_t dv = make_desc(sb + OFF_VP, 128, 512, 0);
      uint32_t yp[8] = {};
      uint32_t yq = sb + OFF_Q + lane * 16;
      auto store_y = [&]() { stsm4(yq, yp[0], yp[1], yp[2], yp[3]); stsm4(yq + 256, yp[4], yp[5], yp[6], yp[7]); };
      auto step = [&](int ch, auto fwd) {
        constexpr bool FWD = decltype(fwd)::value;
        float zu[32], sk[32], su[32], v[32], y[16];
        uint32_t kh[16], uh[16], fk[16], fu[16], fv[16];
        CP(16);
        wg_fence();
        rs_n32<0, 0>(v, pr, dF2i); rs_n32<0, 0>(v + 16, pr + 8, dF2i); rs_n32<1, 0>(v, pr + 4, dF2i + 16); rs_n32<1, 0>(v + 16, pr + 12, dF2i + 16);
        wg_commit();
        CF(0);
        store_y();
        if (FWD) {
          const float dd = __uint_as_float(lds32(sb + OFF_D + 4 * (ch + 1)));
          zk[0] = fmaf(d0r, dd, zk[0]); zk[2] = fmaf(d0i, dd, zk[2]);
          pack32(fk, zk); twiddle<0>(fk, tp, ts); fence_u32<16>(fk);
          CP(1);
          T2(sk, fk);
          CF(2);
          mbar_wait(bars + (B_KF + (ch & 1)) * 8, ((ch >> 1) & 1) ^ 1);
          wg_wait<1>();
        } else {
#pragma unroll
          for (int r = 3; r < 6; r++) mbar_wait(bars + (B_IN + r) * 8, 0);
          wg_wait<0>();
        }
        fence_regs<32>(v); fence_u32<16>(pr); CP(3);
        pack32(fv, v); fence_u32<16>(fv);
        CF(4);
        if (FWD) T1u(zu, du + U_CH / 16);
        CF(5);
        if (FWD && (VO & 1)) { wg_wait<1>(); fence_regs<32>(sk); fence_u32<16>(fk); pack32(kh, sk); }
        twiddle<1>(fv, tp, ts);
#pragma unroll
        for (int i = 0; i < 4; i++) stsm4(va + 2 * i * vs, fv[4 * i], fv[4 * i + 1], fv[4 * i + 2], fv[4 * i + 3]);
        if (FWD) {
          if (!(VO & 1)) {
            CF(6);
            wg_wait<1>(); fence_regs<32>(sk); fence_u32<16>(fk);
            pack32(kh, sk);
          }
          fence_u32<16>(kh);
          CF(7);
          T1k(zk, dk);
          CF(8);
          wg_wait<1>(); fence_regs<32>(zu);
          pack32(fu, zu); twiddle<0>(fu, tp, ts); fence_u32<16>(fu);
          CP(9);
          T2(su, fu);
          CF(10);
        }
        fence_proxy_async_smem();
        bar_sync(7, 128);
        wg_fence(); CP(11);
        ss_n32_tt<0>(y, dv, dF1b); ss_n32_tt<1>(y, dv + 16, dF1b + 64); ss_n32_tt<1>(y, du, dF1b + 128); ss_n32_tt<1>(y, du + 16, dF1b + 192);
        wg_commit();
        if (FWD && t == 0) mbar_arrive(bars + (B_Y + (ch & 3)) * 8);
        CF(12);
        if (FWD) {
          wg_wait<1>(); fence_regs<32>(su); fence_u32<16>(fu); fence_regs<32>(zk); CP(13);
          if (t == 0) mbar_arrive(bars + (B_KE + (ch & 1)) * 8);
          pack32(uh, su);
          if (VO & 2) {
            bimac<0>(pr, kh, uh, pr); bimac<2>(pr + 8, kh + 8, uh, pr); fence_u32<16>(pr);
            CF(14);
            wg_wait<0>(); fence_regs<16>(y);
            bimac<1>(pr + 8, kh, uh + 8, pr + 8); fence_u32<8>(pr + 8);
          } else product(pr, kh, uh);
          du += U_CH / 16; dk += (ch & 1) ? -256 : 256;
          if (w >= 2) va += U_CH;
        }
        if (!FWD || !(VO & 2)) { CF(14); wg_wait<0>(); fence_regs<16>(y); CP(15); }
#pragma unroll
        for (int i = 0; i < 8; i++) yp[i] = pack_bf16(y[2 * i], y[2 * i + 1]);
        fence_u32<8>(yp);
        yq = ya;
        ya += U_CH; CP(17);
        if (t == 0) STAMP(55 + ch);
      };
#pragma unroll 1
      for (int ch = 0; ch < 7; ch++) step(ch, std::true_type());
      step(7, std::false_type());
      store_y();
    }
    fence_proxy_async_smem();
    bar_sync(7, 128);
    if (elect_one()) bulk_send(sb + OFF_U + (4 * rank + w) * U_N8 + 4 * U_CH, sb + OFF_U + (4 * (rank ^ 1) + w) * U_N8 + 6 * U_CH, U_CH + 512, bars + (B_IN + 6) * 8, rank ^ 1);
    __syncwarp();
    asm volatile("bar.arrive 9, 256;" ::: "memory");
    if (t == 0) STAMP(29);
  } else {
    asm volatile("setmaxnreg.inc.sync.aligned.u32 %0;" ::"n"(GREG));
    const int t = tid & 127, w = warp & 3, lane = t & 31, g = lane >> 2, c = lane & 3;
    if (wg == 1) {
      wait_until(c_start, COEF_T0);
      const int p = 64 * j + (t & 63) + 8 * (t & 64);
      const float Lr = bf2f(P.lam_re[p]), Li = bf2f(P.lam_im[p]);
      const uint32_t ds = __bfloat16_as_ushort(P.Dskip[128 * j + t]);
      const unsigned epoch = ld_relaxed(&g_epoch[b * 32]) + 1;
      const float dt = bf2f(__float2bfloat16_rn(expf(bf2f(P.log_dt[p]))));
      const float e = expf(dt * Lr);
      float sn, cs;
      {
        const double z = (double)(dt * Li) * 0.15915494309189535;
        sincospif(2.f * (float)(z - rint(z)), &sn, &cs);
      }
      const float lr = e * cs, li = e * sn;
      const float nr = lr - 1.0f, ni = li;
      const bool big = fabsf(Lr) >= fabsf(Li);
      const float la = big ? Lr : Li, lb = big ? Li : Lr, r = __fdiv_rn(lb, la), inv = __frcp_rn(fmaf(lb, r, la));
      const float br = (big ? fmaf(ni, r, nr) : fmaf(nr, r, ni)) * inv, bi = (big ? fmaf(-nr, r, ni) : fmaf(ni, r, -nr)) * inv;
      sts128(sb + OFF_COEF + t * 16, make_uint4(__float_as_uint(lr), __float_as_uint(li), pack_bf16(2.f * br, 2.f * br), pack_bf16(-2.f * bi, -2.f * bi)));
      sts32(sb + OFF_DS + 4 * t, ds << 16);
      if (t == 0) sts32(bars + B_EPOCH * 8, epoch);
      if (t == 0) STAMP(52);
    }
    CLUSTER_WAIT();
    if (wg == 1) mbar_arrive(bars + B_COEF * 8);
    float d[128];
    uint32_t so = 0, ph = 0, po = 0;
    uint32_t ra;
    auto set_ra = [&]() { asm volatile("mapa.shared::cluster.u32 %0, %1, %2;" : "=r"(ra) : "r"(bars + B_EMPTY * 8), "r"((t & 1) ? rank ^ 1 : rank)); };
    set_ra();
    auto release_at = [&](uint32_t off, bool skip) {
      asm volatile("{\n.reg .pred p;\nsetp.lt.u32 p, %1, %2;\n@p mbarrier.arrive.shared::cluster.b64 _, [%0];\n}\n" ::"r"(ra + off), "r"(t), "r"(skip ? 0 : 2) : "memory");
    };
    auto release = [&](bool first) { release_at(po, first); };
    auto block = [&](auto ta, uint64_t da0, uint64_t db0, bool first, bool zero, int nn) {
      constexpr int PH = decltype(ta)::value, TA = PH > 0, KS = TA ? 128 : 2, QD = PH == 0 ? QD1 : PH == 1 ? QD2 : QD3;
      if (t == 0) TSTAMP(2, nn);
      mbar_wait(bars + B_FULL * 8 + so, ph);
      if (t == 0) TSTAMP(3, nn);
      const uint64_t da = da0 + (so << 8), db = db0 + (so << 8);
      wg_fence();
      wgmma_n128<TA>(d, da, db, !zero);
      wgmma_n128<TA>(d + 64, da + 512, db, !zero);
      wg_commit();
      wg_wait<1>();
      if (RELPOS == 0) release(first);
#pragma unroll
      for (int k = 1; k < 4; k++) {
        if (QD == 2 || (QD == 4 && k == 2)) wg_fence();
        wgmma_n128<TA>(d, da + KS * k, db + 2 * k, 1);
        wgmma_n128<TA>(d + 64, da + 512 + KS * k, db + 2 * k, 1);
        if (QD == 2 || (QD == 4 && k == 1)) wg_commit();
        if (RELPOS == 1 && k == 1) release(first);
        if ((QD == 2 && k < 3) || (QD == 4 && k == 1)) wg_wait<1>();
      }
      if (QD != 2) wg_commit();
      if (RELPOS == 2) release(first);
      po = so;
      so += 8;
      if (so == 8 * STAGES) { so = 0; ph ^= 1; }
    };
    {
      so = wg ? 8 * (16 % STAGES) : 0; ph = wg ? (16 / STAGES) & 1 : 0; po = 0;
      const uint64_t da0 = make_desc(sb + OFF_RING, 16, 1024, 1), db0 = make_desc(sb + OFF_RING + 16384, 16, 1024, 1);
      if (wg == 1) bar_sync(1, 256);
#pragma unroll 1
      for (int kb = 0; kb < 16; kb++) {
        if (16 * wg + kb == XPOS) { so += 8; if (so == 8 * STAGES) { so = 0; ph ^= 1; } }
        block(std::integral_constant<int, 0>(), da0, db0, kb == 0, kb == 0, 16 * wg + kb);
      }
      asm volatile("bar.arrive %0, 256;" ::"r"(1 + wg) : "memory");
    }
    mbar_wait(bars + B_COEF * 8, 0);
    const uint32_t ca = sb + OFF_COEF + (64 * wg + 8 * w + g) * 16;
    const uint32_t tag = __shfl_sync(0xffffffffu, lds32(bars + B_EPOCH * 8) & 3, 0);
    constexpr int RE = SWAPB ? 2 : 0, IM = 2 - RE;
    uint2* cp = &g_carry[((16 * wg + 2 * j) * 16 + tc) * 32 + 8 * w];
    const int ct = lane >> 3;
    uint2 cv[4];
    auto load_carry = [&](int i) {
#pragma unroll
      for (int m = 0; m < 4; m++)
        asm volatile("{\n.reg .pred p;\n.reg .b64 v;\nsetp.lt.s32 p, %3, %4;\nmov.b64 v, {%0,%1};\n@p ld.relaxed.gpu.global.b64 v, [%2];\nmov.b64 {%0,%1}, v;\n}\n"
                     : "+r"(cv[m].x), "+r"(cv[m].y) : "l"(cp + 512 * i + (lane & 7) - 32 * (1 + ct) - 128 * m), "r"(ct), "r"(tc - 4 * m) : "memory");
    };
    auto first_load = [&](int i) {
#pragma unroll
      for (int m = 0; m < 4; m++) cv[m] = make_uint2(tag, 0);
      load_carry(i);
    };
    float lr[2], li[2], pr[2], pi[2], wr[2], wi[2], vr[2], vi[2], qr[2], qi[2], er[2], ei[2], gr[2], gi[2];
    auto powers = [&](int i) {
      const uint2 cf = lds64(ca + 512 * i);
      pr[i] = lr[i] = __uint_as_float(cf.x); pi[i] = li[i] = __uint_as_float(cf.y);
#pragma unroll
      for (int s = 0; s < 4; s++) csq(pr[i], pi[i]);
      gr[i] = pr[i]; gi[i] = pi[i];
      csq(pr[i], pi[i]);
      qr[i] = pr[i]; qi[i] = pi[i];
      csq(qr[i], qi[i]);
      er[i] = qr[i]; ei[i] = qi[i];
      wr[i] = (c & 1) ? pr[i] : 1.f; wi[i] = (c & 1) ? pi[i] : 0.f;
      if (c & 2) { float x, y; cmul(wr[i], wi[i], qr[i], qi[i], x, y); wr[i] = x; wi[i] = y; }
      vr[i] = wr[i]; vi[i] = wi[i];
      csq(vr[i], vi[i]); csq(vr[i], vi[i]);
      csq(qr[i], qi[i]); csq(qr[i], qi[i]); csq(qr[i], qi[i]);
      const int src = 4 * (lane & 7) + ct;
      vr[i] = __shfl_sync(0xffffffffu, vr[i], src); vi[i] = __shfl_sync(0xffffffffu, vi[i], src);
      qr[i] = __shfl_sync(0xffffffffu, qr[i], src); qi[i] = __shfl_sync(0xffffffffu, qi[i], src);
      asm volatile("" : "+f"(wr[i]), "+f"(wi[i]), "+f"(pr[i]), "+f"(pi[i]), "+f"(er[i]), "+f"(ei[i]));
    };
    powers(0);
    if (POW2 == 0) powers(1);
    PMFENCE();
    wg_wait<0>();
    fence_regs<128>(d);
    release(false);
    if (t == 0) STAMP(10 + 10 * wg);
#pragma unroll
    for (int i = 0; i < 2; i++) {
      const float* e = d + 64 * i;
      auto chain = [&](int s0, int s1, float& sr, float& si) {
        sr = e[2 * s0 + RE]; si = e[2 * s0 + IM];
#pragma unroll
        for (int s = s0 + 1; s < s1; s++) {
          const int ia = 4 * (s >> 1) + (s & 1);
          const float nr = fmaf(-li[i], si, fmaf(lr[i], sr, e[ia + RE])), ni = fmaf(li[i], sr, fmaf(lr[i], si, e[ia + IM]));
          sr = nr; si = ni;
        }
      };
      float sr, si;
      if (POW2 == 1 && i == 1) powers(1);
      if ((GREEDY >> i) & 1) {
        float ar, ai;
        chain(0, 16, ar, ai); chain(16, 32, sr, si);
        sr = fmaf(gr[i], ar, fmaf(-gi[i], ai, sr)); si = fmaf(gr[i], ai, fmaf(gi[i], ar, si));
      } else chain(0, 32, sr, si);
      if (i == 1 && C_AT == 0) { asm volatile("pmevent 0;" : "+f"(sr), "+f"(si)::"memory"); first_load(0); }
      float ur = __shfl_up_sync(0xffffffffu, sr, 1, 4), ui = __shfl_up_sync(0xffffffffu, si, 1, 4);
      if (c >= 1) { sr = fmaf(pr[i], ur, fmaf(-pi[i], ui, sr)); si = fmaf(pr[i], ui, fmaf(pi[i], ur, si)); }
      ur = __shfl_up_sync(0xffffffffu, sr, 2, 4); ui = __shfl_up_sync(0xffffffffu, si, 2, 4);
      if (c >= 2) { sr = fmaf(er[i], ur, fmaf(-ei[i], ui, sr)); si = fmaf(er[i], ui, fmaf(ei[i], ur, si)); }
      if (c == 3 && tc < 15)
        asm volatile("{\n.reg .b64 v;\nmov.b64 v, {%1,%2};\nst.relaxed.gpu.global.b64 [%0], v;\n}\n" ::"l"(cp + 512 * i + g), "r"((__float_as_uint(sr) & ~3u) | tag), "r"(__float_as_uint(si)) : "memory");
      if (i == 1 && C_AT == 1) first_load(0);
      PMFENCE();
      if (t == 0) STAMP(11 + i + 10 * wg);
      er[i] = __shfl_up_sync(0xffffffffu, sr, 1, 4); ei[i] = __shfl_up_sync(0xffffffffu, si, 1, 4);
      if (c == 0) er[i] = ei[i] = 0.f;
    }
    uint4* hp = g_h + (32 * tc + 16 * wg + 2 * j) * 1024 + 64 * w + 4 * g + (c ^ (g >> 1));
#pragma unroll
    for (int i = 0; i < 2; i++) {
      float* e = d + 64 * i;
      const uint2 cf = lds64(ca + 512 * i + 8);
      const uint32_t gp = cf.x, gms = cf.y;
      PMFENCE();
      int n = 0;
#pragma unroll 1
      while (!__all_sync(0xffffffffu, (((cv[0].x ^ tag) | (cv[1].x ^ tag) | (cv[2].x ^ tag) | (cv[3].x ^ tag)) & 3) == 0) && ++n <= (SPIN_LIMIT << 4)) load_carry(i);
      if (t == 0 && i == 0) STAMP(13 + 10 * wg);
      float hr = __uint_as_float(cv[3].x), hi = __uint_as_float(cv[3].y);
#pragma unroll
      for (int m = 2; m >= 0; m--) {
        const float nr = fmaf(qr[i], hr, fmaf(-qi[i], hi, __uint_as_float(cv[m].x))), ni = fmaf(qr[i], hi, fmaf(qi[i], hr, __uint_as_float(cv[m].y)));
        hr = nr; hi = ni;
      }
      { float x, y; cmul(hr, hi, vr[i], vi[i], x, y); hr = x; hi = y; }
      hr += __shfl_xor_sync(0xffffffffu, hr, 8); hi += __shfl_xor_sync(0xffffffffu, hi, 8);
      hr = __shfl_sync(0xffffffffu, hr, g) + __shfl_sync(0xffffffffu, hr, g + 16); hi = __shfl_sync(0xffffffffu, hi, g) + __shfl_sync(0xffffffffu, hi, g + 16);
      float sr = fmaf(wr[i], hr, fmaf(-wi[i], hi, er[i])), si = fmaf(wr[i], hi, fmaf(wi[i], hr, ei[i]));
      if (t == 0 && i == 0) STAMP(14 + 10 * wg);
#pragma unroll
      for (int i8 = 0; i8 < 4; i8++) {
        asm volatile("pmevent 0;" : "+f"(sr), "+f"(si)::"memory");
        if (i == 0 && i8 == C_AT2) first_load(1);
#pragma unroll
        for (int s = 8 * i8; s < 8 * i8 + 8; s++) {
          const int ia = 4 * (s >> 1) + (s & 1);
          const float nr = fmaf(-li[i], si, fmaf(lr[i], sr, e[ia + RE])), ni = fmaf(li[i], sr, fmaf(lr[i], si, e[ia + IM]));
          sr = nr; si = ni;
          e[ia + RE] = nr; e[ia + IM] = ni;
        }
        if (P2_SPLIT) PMFENCE();
        uint32_t hp0[4], hp1[4];
#pragma unroll
        for (int m = 0; m < 4; m++) {
          const float* f = e + 16 * i8 + 4 * m;
          const uint32_t x = pack_bf16(f[RE], f[RE + 1]), y = pack_bf16(f[IM], f[IM + 1]);
          hp0[m] = bfma2(gp, x, bmul2(gms, y)); hp1[m] = bfnma2(gp, y, bmul2(gms, x));
        }
        uint4* o = hp + 512 * (i8 >> 1) + 256 * i + 32 * (i8 & 1);
        stg128(o, make_uint4(hp0[0], hp0[1], hp0[2], hp0[3]));
        stg128(o + 1024, make_uint4(hp1[0], hp1[1], hp1[2], hp1[3]));
      }
    }
    if (t == 0) STAMP(15 + 10 * wg);
    const int trow = 128 * tc + 64 * (w & 1) + 8 * (w >> 1) + g;
    const int dcol = 128 * j + 4 * c;
    asm volatile("bar.arrive %0, 160;" ::"r"(4 + wg) : "memory");
    if (wg == 0) {
      set_ra();
      uint2 xv[32];
      {
        const int gp = 2 * (g & 3) + (g >> 2);
        const uint32_t xa = sb + OFF_RING + (XPOS % STAGES) * STAGE_BYTES + (64 * (w & 1) + 8 * (w >> 1) + gp) * 128 + (c & 1) * 8;
        mbar_wait(bars + B_XI * 8, 0);
        mbar_wait(bars + (B_FULL + XPOS % STAGES) * 8, (XPOS / STAGES) & 1);
        if (t == 0) STAMP(18);
#pragma unroll
        for (int u = 0; u < 32; u++) {
          const int J = (u >> 1) & 7;
          asm volatile("ld.shared.v2.u32 {%0,%1}, [%2];" : "=r"(xv[u].x), "=r"(xv[u].y) : "r"(xa + (J >> 2) * 16384 + (u >> 4) * 2048 + (u & 1) * 4096 + (((2 * (J & 3) + (c >> 1)) ^ gp) << 4)) : "memory");
        }
        uint32_t dep = P.zero;
#pragma unroll
        for (int u = 0; u < 32; u++) dep &= xv[u].x;
        bar_sync(3 + dep, 128);
        release_at(8 * (XPOS % STAGES), false);
      }
#pragma unroll
      for (int J = 0; J < 8; J++) {
        const uint4 ds = lds128(sb + OFF_DS + 16 * c + 64 * J);
#pragma unroll
        for (int r = 0; r < 4; r++) {
          const int u = 16 * (r >> 1) + 2 * J + (r & 1);
          float* e = d + 8 * (u >> 1) + 2 * (u & 1);
          e[0] = __uint_as_float(bfma2(blo2(xv[u].x), ds.x, 0)); e[1] = __uint_as_float(bfma2(xv[u].x, ds.y, 0));
          e[4] = __uint_as_float(bfma2(blo2(xv[u].y), ds.z, 0)); e[5] = __uint_as_float(bfma2(xv[u].y, ds.w, 0));
        }
      }
      fence_regs<128>(d);
      if (t == 0) STAMP(17);
      so = 8 * (33 % STAGES); ph = (33 / STAGES) & 1;
      const uint64_t da0 = make_desc(sb + OFF_RING + 16384, 512, 1024, 2), db0 = make_desc(sb + OFF_RING, 16, 1024, 1);
      bar_sync(2, 256);
#pragma unroll 1
      for (int kb = 0; kb < QSW; kb++) block(std::integral_constant<int, 1>(), da0, db0, kb == 0, false, 32 + kb);
#pragma unroll 1
      for (int kb = QSW; kb < 32 - TAILB; kb++) block(std::integral_constant<int, 2>(), da0, db0, false, false, 32 + kb);
      float* op = P.out + (size_t)trow * 2048 + 1024 + dcol;
      auto mma = [&](int i, int kb, int k0, int k1) {
        const int s = (33 + kb) % STAGES;
        wg_fence();
#pragma unroll
        for (int k = k0; k < k1; k++) wgmma_n128<1>(d + 64 * i, da0 + s * 2048 + 512 * i + 128 * k, db0 + (i ? 0 : P.zero) + s * 2048 + 2 * k, 1);
        wg_commit();
      };
      auto store = [&](int i, int J0, int J1) {
#pragma unroll
        for (int J = J0; J < J1; J++) {
#pragma unroll
          for (int h = 0; h < 2; h++) {
            const float* e = d + 64 * i + 8 * J + 2 * h;
            stg128(op + (size_t)(16 * i + 32 * h) * 2048 + 16 * J, make_uint4(__float_as_uint(e[0]), __float_as_uint(e[1]), __float_as_uint(e[4]), __float_as_uint(e[5])));
          }
        }
        PMFENCE();
      };
      constexpr int K0 = 32 - TAILB;
#pragma unroll
      for (int kb = K0; kb < 32; kb++) {
        mbar_wait(bars + (B_FULL + (33 + kb) % STAGES) * 8, ((33 + kb) / STAGES) & 1);
        if (TAILB == 5 && kb == K0) { mma(0, kb, 0, 2); wg_wait<1>(); release(false); mma(0, kb, 2, 4); }
        else mma(0, kb, 0, 4);
      }
      mma(1, K0, 0, 4);
      wg_wait<1>();
      fence_regs<64>(d);
      if (t == 0) STAMP(48);
#pragma unroll
      for (int kb = K0 + 1; kb < 32; kb++) {
        mma(1, kb, 0, 4);
        if (T_FENCE) PMFENCE();
        store(0, T_ST * (kb - K0 - 1), kb == 31 ? 8 : T_ST * (kb - K0));
      }
      if (t == 0) STAMP(49);
      wg_wait<0>();
      fence_regs<64>(d + 64);
      if (t == 0) STAMP(50);
      store(1, 0, 8);
      if (t == 0) { STAMP(51); GSTAMP(51); }
      if (t == 0) g_epoch[b * 32] = lds32(bars + B_EPOCH * 8);
      return;
    }
    asm volatile("setmaxnreg.dec.sync.aligned.u32 %0;" ::"n"(488 - 2 * GREG));
  }
  {
    int lane;
    asm volatile("mov.u32 %0, %%laneid;" : "=r"(lane));
    const int w = warp & 3, h = wg & 1;
    const int lc = 2 * (lane & 2) + (lane & 1) + ((lane >> 2) & 2);
    const bool own = ((lane >> 2) & 1) == rank, spare = !own && lc < 2;
    const uint32_t ya = (spare ? sb + OFF_IN + 96 + lc * 2064 : sb + OFF_U + (own ? 4 * rank * U_N8 : 4 * (rank ^ 1) * U_N8 - 2 * U_CH) + lc * U_CH) + w * 128 + (lane >> 4) * 16 + h * 64;
    const uint32_t ys = spare ? 512 : U_N8;
    const uint32_t ob0 = sb + (h ? OFF_F1 : OFF_K) + 1024 * w, ob1 = sb + (h ? OFF_VP : OFF_K + 4096) + 1024 * w;
    uint32_t y[2][8];
    uint2 q[4][4];
    auto get_q = [&](int n, int off, int bar, int ph) {
#pragma unroll
      for (int u = 0; u < 2; u++) {
        mbar_wait(bars + (bar + u) * 8, ph);
#pragma unroll
        for (int r = 0; r < 4; r++) q[n + u][r] = lds64(sb + off + 4096 * u + 1024 * w + 256 * r + 8 * lane);
      }
    };
    auto get_y = [&](int n) { ldsm4t(y[n & 1], ya + n * ys); ldsm4t(y[n & 1] + 4, ya + n * ys + 32); };
    if (h) {
#pragma unroll
      for (int n = 0; n < 4; n += 2) {
        get_q(n, OFF_Q, B_QF, n >> 1);
        uint32_t dep = P.zero;
#pragma unroll
        for (int r = 0; r < 8; r++) dep &= q[n + (r >> 2)][r & 3].x;
        bar_sync(6 + dep, 128);
        if (w < 2 && elect_one()) load_q(5 + 2 * w - (n >> 1), OFF_Q, B_QF + n);
        __syncwarp();
      }
#pragma unroll 1
      for (int r = 0; r < 6; r++) mbar_wait(bars + (B_IN + r) * 8, 0);
      if (warp == 4 && lane == 0) STAMP(52);
      bar_sync(9, 256);
    } else get_q(0, OFF_K, B_KF, 0);
    if (O_WAIT) mbar_wait(bars + (O_WAIT == 1 ? B_HP : B_HR) * 8, 1);
    if (warp == 8 && lane == 0) STAMP(53);
    mbar_wait(bars + (B_IN + 6) * 8, 0);
    if (warp == 8 && lane == 0) STAMP(63);
    get_y(0);
    uint32_t oc = clk32() + (2 * w + h) * (O_PACE / 2);
    if (warp == 8 && lane == 0) STAMP(30);
#pragma unroll
    for (int n = 0; n < 4; n++) {
      uint32_t* o = y[n & 1];
#pragma unroll
      for (int r = 0; r < 4; r++) { o[2 * r] = bmul2(o[2 * r], q[n][r].x); o[2 * r + 1] = bmul2(o[2 * r + 1], q[n][r].y); }
#pragma unroll
      for (int u = 0; u < 2; u++) {
        const uint32_t ob = u ? ob1 : ob0;
        if (n > 0 && lane == 0) asm volatile("cp.async.bulk.wait_group.read 1;" ::: "memory");
        __syncwarp();
#pragma unroll
        for (int r = 2 * u; r < 2 * u + 2; r++)
          sts128(ob + (r & 1) * 512 + lane * 16, make_uint4(o[2 * r] << 16, o[2 * r] & 0xffff0000u, o[2 * r + 1] << 16, o[2 * r + 1] & 0xffff0000u));
        if (O_PACE) { while ((int)(clk32() - oc) < 0) { if (O_SLEEP) __nanosleep(O_SLEEP); } }
        oc += 4 * O_PACE;
        fence_proxy_async_smem();
        __syncwarp();
        if (lane == 0)
          asm volatile("cp.async.bulk.tensor.3d.global.shared::cta.bulk_group [%0, {%2, %3, %4}], [%1];\ncp.async.bulk.commit_group;"
                       ::"l"(&mO), "r"(ob), "r"(32 * slot), "r"(32 * rank + 8 * w), "r"(8 * n + 4 * h + 2 * u) : "memory");
        __syncwarp();
        if (u == 0 && n < 3) get_y(n + 1);
        if (u == 0 && n == 1 && !h) get_q(2, OFF_Q, B_QF + 2, 0);
      }
    }
    if (warp == 8 && lane == 0) mbar_arrive_cta(bars + B_ACK * 8, rank ^ 1);
    if (lane == 0) asm volatile("cp.async.bulk.wait_group 0;" ::: "memory");
    if (warp == 8 && lane == 0) STAMP(31);
    mbar_wait(bars + B_ACK * 8, 0);
  }
}

typedef CUresult (*EncodeFn)(CUtensorMap*, CUtensorMapDataType, cuuint32_t, void*, const cuuint64_t*, const cuuint64_t*, const cuuint32_t*,
                             const cuuint32_t*, CUtensorMapInterleave, CUtensorMapSwizzle, CUtensorMapL2promotion, CUtensorMapFloatOOBfill);

bool encode(EncodeFn fn, CUtensorMap* m, int rank, const void* base, const cuuint64_t* dims, const cuuint64_t* strides, const cuuint32_t* box, CUtensorMapSwizzle swz,
            CUtensorMapL2promotion promo = CU_TENSOR_MAP_L2_PROMOTION_L2_128B) {
  const cuuint32_t es[5] = {1, 1, 1, 1, 1};
  return fn(m, CU_TENSOR_MAP_DATA_TYPE_BFLOAT16, rank, const_cast<void*>(base), dims, strides, box, es, CU_TENSOR_MAP_INTERLEAVE_NONE, swz,
            promo, CU_TENSOR_MAP_FLOAT_OOB_FILL_NONE) == CUDA_SUCCESS;
}

}

extern "C" void kernel_launch(void* const* d_in, const int* in_sizes, int n_in, void* d_out, int out_size) {
  (void)in_sizes; (void)n_in; (void)out_size;
  typedef const __nv_bfloat16* In;
  const In q = (In)d_in[0], k = (In)d_in[1], v = (In)d_in[2], ssm_k = (In)d_in[4], x = (In)d_in[6], B_re = (In)d_in[9], B_im = (In)d_in[10], C_re = (In)d_in[11], C_im = (In)d_in[12];
  Params P = {};
  P.shift_k = (In)d_in[3]; P.ssm_D = (In)d_in[5]; P.lam_re = (In)d_in[7]; P.lam_im = (In)d_in[8]; P.log_dt = (In)d_in[13]; P.Dskip = (In)d_in[14];
  P.out = (float*)d_out;
  for (int cl = 0; cl < 64; cl++) P.slot[cl >> 2] |= (cl < 4 ? 4 + cl : cl < 36 ? 8 * ((cl - 4) & 7) + ((cl - 4) >> 3) : 8 * (1 + (cl - 36) % 7) + 4 + (cl - 36) / 7) << (8 * (cl & 3));
  const bool swapB = (uintptr_t)B_im < (uintptr_t)B_re;

  EncodeFn fn = nullptr;
  cudaDriverEntryPointQueryResult qr;
  cudaGetDriverEntryPoint("cuTensorMapEncodeTiled", (void**)&fn, cudaEnableDefault, &qr);
  if (!fn) return;

  CUtensorMap mX, mB, mCre, mCim, mXs, mK, mV, mQ, mS, mO;
  bool ok = true;
  {
    const cuuint64_t dims[4] = {1024, 2, 64, 16}, str[3] = {2048, 32 * 2048, 2 * 2048};
    const cuuint32_t box[4] = {64, 2, 4, 16};
    ok &= encode(fn, &mX, 4, x, dims, str, box, CU_TENSOR_MAP_SWIZZLE_128B, (CUtensorMapL2promotion)X_PROMO);
  }
  {
    const uintptr_t lo = swapB ? (uintptr_t)B_im : (uintptr_t)B_re, hi = swapB ? (uintptr_t)B_re : (uintptr_t)B_im;
    const cuuint64_t dims[4] = {1024, 8, 2, 128}, str[3] = {2048, (cuuint64_t)(hi - lo), 8 * 2048};
    const cuuint32_t box[4] = {64, 8, 2, 4};
    ok &= encode(fn, &mB, 4, (const void*)lo, dims, str, box, CU_TENSOR_MAP_SWIZZLE_128B, (CUtensorMapL2promotion)B_PROMO);
  }
  {
    const cuuint64_t dims[5] = {1024, 2, 4, 2, 64}, str[4] = {2048, 4 * 2048, 2 * 2048, 16 * 2048};
    const cuuint32_t box[5] = {64, 2, 4, 2, 4};
    ok &= encode(fn, &mCre, 5, C_re, dims, str, box, CU_TENSOR_MAP_SWIZZLE_128B, (CUtensorMapL2promotion)C_PROMO);
    ok &= encode(fn, &mCim, 5, C_im, dims, str, box, CU_TENSOR_MAP_SWIZZLE_128B, (CUtensorMapL2promotion)C_PROMO);
  }
  {
    const cuuint64_t dims[4] = {1024, 2, 4, 256}, str[3] = {4 * 2048, 2048, 8 * 2048};
    const cuuint32_t box[4] = {64, 2, 4, 16};
    ok &= encode(fn, &mXs, 4, x, dims, str, box, CU_TENSOR_MAP_SWIZZLE_128B);
  }
  {
    const cuuint64_t dims[3] = {1024, 64, 32}, str[2] = {32 * 2048, 2048};
    const cuuint32_t box[3] = {16, 32, 4};
    const cuuint64_t dimq[4] = {1024, 8, 32, 8}, strq[3] = {32 * 2048, 2048, 256 * 2048};
    const cuuint32_t boxq[4] = {16, 8, 4, 4};
    ok &= encode(fn, &mQ, 4, q, dimq, strq, boxq, CU_TENSOR_MAP_SWIZZLE_NONE, (CUtensorMapL2promotion)Q_PROMO);
    ok &= encode(fn, &mK, 3, k, dims, str, box, CU_TENSOR_MAP_SWIZZLE_32B, (CUtensorMapL2promotion)KV_PROMO);
    ok &= encode(fn, &mV, 3, v, dims, str, box, CU_TENSOR_MAP_SWIZZLE_32B, (CUtensorMapL2promotion)KV_PROMO);
  }
  {
    const cuuint64_t dims[2] = {32, 65536}, str[1] = {64};
    const cuuint32_t box[2] = {32, 64};
    ok &= encode(fn, &mS, 2, ssm_k, dims, str, box, CU_TENSOR_MAP_SWIZZLE_64B, (CUtensorMapL2promotion)S_PROMO);
  }
  {
    const cuuint64_t dims[3] = {2048, 64, 32}, str[2] = {32 * 8192, 8192};
    const cuuint32_t box[3] = {32, 8, 2};
    ok &= encode(fn, &mO, 3, d_out, dims, str, box, CU_TENSOR_MAP_SWIZZLE_NONE);
  }
  if (!ok) return;
  auto kern = swapB ? fused_kernel<1> : fused_kernel<0>;
  cudaFuncSetAttribute(kern, cudaFuncAttributeMaxDynamicSharedMemorySize, SMEM_BYTES);
  kern<<<NCTA, 512, SMEM_BYTES, cudaStreamPerThread>>>(P, mX, mB, mCre, mCim, mXs, mK, mV, mQ, mS, mO);
}
```

```cpp
#include <cuda_runtime.h>
#include <cuda_bf16.h>
#include <cuda.h>
#include <stdint.h>
#include <type_traits>

#define PROFILE 0

namespace {

constexpr int D_DIM = 1024;
constexpr int NCTA = 128;

constexpr int STAGES = 5, STAGE_BYTES = 32768;
constexpr int OFF_RING = 0;
constexpr int OFF_F1 = STAGES * STAGE_BYTES, OFF_F2 = OFF_F1 + 4096, OFF_K = OFF_F2 + 2048, OFF_VP = OFF_K + 8192, OFF_Q = OFF_VP + 4096, OFF_IN = OFF_Q + 8192;
constexpr int OFF_KV = OFF_K;
constexpr int U_CH = 528, U_N8 = 8 * U_CH, OFF_U = OFF_IN + U_N8;
constexpr int OFF_COEF = OFF_U + 8 * U_N8;
constexpr int OFF_DS = OFF_COEF + 2048, OFF_D = OFF_DS + 512;
constexpr int OFF_BAR = OFF_D + 64;
constexpr int OFF_PROF = OFF_BAR + 512;
constexpr int SMEM_BYTES = OFF_PROF + 512;
static_assert(SMEM_BYTES <= 232448 && OFF_K % 1024 == 0 && (OFF_U + 3 * U_N8) % 512 == 0 && (4 * U_N8) % 512 == 0, "smem map");
constexpr int B_FULL = 0, B_XI = 5, B_HR = 6, B_HP = 7, B_KVF = 8, B_KF = 11, B_KE = 13, B_QF = 15, B_IN = 19, B_UF = 27, B_Y = 31, B_ACK = 36,
              B_EMPTY = 38, B_COEF = 43, B_KVE = 44, B_EPOCH = 48;
#define QD1 8
#define QD2 2
#define QD3 8
#define QSW 16
#define HEAD 3
#define ST_T0 200
#define ST_DELAY 300
#define XPOS 28
#define K_T0 800
#define KV_T0 1500
#define KV_DT 560
#define KV_DV 100
#define O_PACE 0
#define POLL_NS 30
#define GREEDY 1
#define P2_SPLIT 0
#define TAILB 5
#define GREG 176
#define O_WAIT 2
#define COEF_T0 2500
#define RELPOS 0
#define C_AT 1
#define C_AT2 1
#define T_FENCE 0
#define T_ST 2
#define X_PROMO 2
#define B_PROMO 2
#define C_PROMO 2
#define KV_PROMO 2
#define Q_PROMO 2
#define S_PROMO 2
#define POW2 0
#define O_SLEEP 20
#define VO 3
#define PFC 3
#define PFC_T0 13500
#define PFC_T1 1500
#define PFC_DT 400
#define PFQ 4
#define Q_HOLD 0
#define CFM 0x40f1
constexpr int SPIN_LIMIT = 1 << 14;

struct Params {
  unsigned slot[16];
  unsigned zero;
  const __nv_bfloat16 *shift_k, *ssm_D, *lam_re, *lam_im, *log_dt, *Dskip;
  float* out;
};

__device__ __align__(1024) uint4 g_h[16 * 32 * 1024];
__device__ __align__(128) uint2 g_carry[32 * 16 * 32];
__device__ unsigned g_flagH[2 * 16 * 32];
__device__ unsigned g_epoch[NCTA * 32];
#define STAMP(i)
#define GSTAMP(i)
#define TSTAMP(k, n)
#define KSTAMP(k, n)

__device__ __forceinline__ uint64_t make_desc(uint32_t addr, uint32_t lbo, uint32_t sbo, uint32_t swz) {
  return (uint64_t)((addr & 0x3FFFF) >> 4) | ((uint64_t)(lbo >> 4) << 16) | ((uint64_t)(sbo >> 4) << 32) | ((uint64_t)swz << 62);
}
__device__ __forceinline__ void wg_fence() { asm volatile("wgmma.fence.sync.aligned;" ::: "memory"); }
__device__ __forceinline__ void wg_commit() { asm volatile("wgmma.commit_group.sync.aligned;" ::: "memory"); }
template <int N> __device__ __forceinline__ void wg_wait() { asm volatile("wgmma.wait_group.sync.aligned %0;" ::"n"(N) : "memory"); }
__device__ __forceinline__ void mbar_init(uint32_t bar, int cnt) { asm volatile("mbarrier.init.shared::cta.b64 [%0], %1;" ::"r"(bar), "r"(cnt) : "memory"); }
__device__ __forceinline__ void mbar_expect(uint32_t bar, uint32_t bytes) { asm volatile("mbarrier.arrive.expect_tx.shared::cta.b64 _, [%0], %1;" ::"r"(bar), "r"(bytes) : "memory"); }
__device__ __forceinline__ void mbar_wait(uint32_t bar, uint32_t parity) {
  uint32_t ok; int n = 0;
  do {
    asm volatile("{\n.reg .pred p;\nmbarrier.try_wait.parity.shared::cta.b64 p, [%1], %2;\nselp.u32 %0, 1, 0, p;\n}\n" : "=r"(ok) : "r"(bar), "r"(parity) : "memory");
    if (++n > SPIN_LIMIT) break;
  } while (!ok);
}
__device__ __forceinline__ void mbar_arrive(uint32_t bar) { asm volatile("mbarrier.arrive.shared::cta.b64 _, [%0];" ::"r"(bar) : "memory"); }
__device__ __forceinline__ void mbar_arrive_cta(uint32_t bar, uint32_t cta) {
  asm volatile("{\n.reg .b32 ra;\nmapa.shared::cluster.u32 ra, %0, %1;\nmbarrier.arrive.shared::cluster.b64 _, [ra];\n}\n" ::"r"(bar), "r"(cta) : "memory");
}
__device__ __forceinline__ bool elect_one() {
  uint32_t p;
  asm volatile("{\n.reg .pred P;\nelect.sync _|P, 0xffffffff;\nselp.u32 %0, 1, 0, P;\n}\n" : "=r"(p));
  return p != 0;
}
__device__ __forceinline__ void bar_sync(int id, int n) { asm volatile("bar.sync %0, %1;" ::"r"(id), "r"(n) : "memory"); }
#define TMA_LD(dim) "cp.async.bulk.tensor." dim ".shared::cluster.global.mbarrier::complete_tx::bytes"
__device__ __forceinline__ void tma2d(uint32_t dst, const CUtensorMap* m, int c0, int c1, uint32_t bar) {
  asm volatile(TMA_LD("2d") " [%0], [%1, {%3, %4}], [%2];" ::"r"(dst), "l"(m), "r"(bar), "r"(c0), "r"(c1) : "memory");
}
__device__ __forceinline__ void tma3d(uint32_t dst, const CUtensorMap* m, int c0, int c1, int c2, uint32_t bar) {
  asm volatile(TMA_LD("3d") " [%0], [%1, {%3, %4, %5}], [%2];" ::"r"(dst), "l"(m), "r"(bar), "r"(c0), "r"(c1), "r"(c2) : "memory");
}
__device__ __forceinline__ void tma4d(uint32_t dst, const CUtensorMap* m, int c0, int c1, int c2, int c3, uint32_t bar) {
  asm volatile(TMA_LD("4d") " [%0], [%1, {%3, %4, %5, %6}], [%2];" ::"r"(dst), "l"(m), "r"(bar), "r"(c0), "r"(c1), "r"(c2), "r"(c3) : "memory");
}
__device__ __forceinline__ void tma4d_mc(uint32_t dst, const CUtensorMap* m, int c0, int c1, int c2, int c3, uint32_t bar) {
  asm volatile(TMA_LD("4d") ".multicast::cluster [%0], [%1, {%3, %4, %5, %6}], [%2], %7;" ::"r"(dst), "l"(m), "r"(bar), "r"(c0), "r"(c1), "r"(c2), "r"(c3), "h"((uint16_t)3) : "memory");
}
__device__ __forceinline__ void tma5d_mc(uint32_t dst, const CUtensorMap* m, int c0, int c1, int c2, int c3, int c4, uint32_t bar) {
  asm volatile(TMA_LD("5d") ".multicast::cluster [%0], [%1, {%3, %4, %5, %6, %7}], [%2], %8;" ::"r"(dst), "l"(m), "r"(bar), "r"(c0), "r"(c1), "r"(c2), "r"(c3), "r"(c4), "h"((uint16_t)3) : "memory");
}
__device__ __forceinline__ void bulk_load(uint32_t dst, const void* src, uint32_t bytes, uint32_t bar) {
  asm volatile("cp.async.bulk.shared::cluster.global.mbarrier::complete_tx::bytes [%0], [%1], %2, [%3];" ::"r"(dst), "l"(src), "r"(bytes), "r"(bar) : "memory");
}
__device__ __forceinline__ void bulk_send(uint32_t dst, uint32_t src, uint32_t bytes, uint32_t bar, uint32_t cta) {
  asm volatile("{\n.reg .b32 rd, rb;\nmapa.shared::cluster.u32 rd, %0, %3;\nmapa.shared::cluster.u32 rb, %2, %3;\n"
               "cp.async.bulk.shared::cluster.shared::cta.mbarrier::complete_tx::bytes [rd], [%1], %4, [rb];\n}\n"
               ::"r"(dst), "r"(src), "r"(bar), "r"(cta), "r"(bytes) : "memory");
}
__device__ __forceinline__ void fence_proxy_async_smem() { asm volatile("fence.proxy.async.shared::cta;" ::: "memory"); }
__device__ __forceinline__ void fence_proxy_async_global() { asm volatile("fence.proxy.async.global;" ::: "memory"); }
__device__ __forceinline__ uint32_t clk32() { uint32_t c; asm volatile("mov.u32 %0, %%clock;" : "=r"(c)::"memory"); return c; }
__device__ __forceinline__ void wait_until(uint32_t t0, uint32_t dt) { while (clk32() - t0 < dt) __nanosleep(32); }
__device__ __forceinline__ void spin_until(uint32_t t0, uint32_t dt) { while (clk32() - t0 < dt) {} }
__device__ __forceinline__ void prefetch_map(const CUtensorMap* m) { asm volatile("prefetch.tensormap [%0];" ::"l"(m) : "memory"); }
__device__ __forceinline__ void prefetch_line(const void* p) { asm volatile("prefetch.global.L2 [%0];" ::"l"(p) : "memory"); }
__device__ __forceinline__ unsigned ld_acquire(const unsigned* p) { unsigned v; asm volatile("ld.acquire.gpu.global.u32 %0, [%1];" : "=r"(v) : "l"(p) : "memory"); return v; }
__device__ __forceinline__ unsigned ld_relaxed(const unsigned* p) { unsigned v; asm volatile("ld.relaxed.gpu.global.u32 %0, [%1];" : "=r"(v) : "l"(p) : "memory"); return v; }
__device__ __forceinline__ uint32_t lds32(uint32_t a) { uint32_t v; asm volatile("ld.shared.u32 %0, [%1];" : "=r"(v) : "r"(a)); return v; }
__device__ __forceinline__ uint2 lds64(uint32_t a) { uint2 v; asm volatile("ld.shared.v2.u32 {%0,%1}, [%2];" : "=r"(v.x), "=r"(v.y) : "r"(a) : "memory"); return v; }
__device__ __forceinline__ uint4 lds128(uint32_t a) { uint4 v; asm volatile("ld.shared.v4.u32 {%0,%1,%2,%3}, [%4];" : "=r"(v.x), "=r"(v.y), "=r"(v.z), "=r"(v.w) : "r"(a) : "memory"); return v; }
__device__ __forceinline__ void sts32(uint32_t a, uint32_t v) { asm volatile("st.shared.u32 [%0], %1;" ::"r"(a), "r"(v) : "memory"); }
__device__ __forceinline__ void sts128(uint32_t a, uint4 v) { asm volatile("st.shared.v4.u32 [%0], {%1,%2,%3,%4};" ::"r"(a), "r"(v.x), "r"(v.y), "r"(v.z), "r"(v.w) : "memory"); }
__device__ __forceinline__ void ldsm4(uint32_t* r, uint32_t a) { asm volatile("ldmatrix.sync.aligned.m8n8.x4.shared.b16 {%0,%1,%2,%3}, [%4];" : "=r"(r[0]), "=r"(r[1]), "=r"(r[2]), "=r"(r[3]) : "r"(a) : "memory"); }
__device__ __forceinline__ void ldsm4t(uint32_t* r, uint32_t a) { asm volatile("ldmatrix.sync.aligned.m8n8.x4.trans.shared.b16 {%0,%1,%2,%3}, [%4];" : "=r"(r[0]), "=r"(r[1]), "=r"(r[2]), "=r"(r[3]) : "r"(a) : "memory"); }
__device__ __forceinline__ void stsm4t(uint32_t a, uint32_t r0, uint32_t r1, uint32_t r2, uint32_t r3) {
  asm volatile("stmatrix.sync.aligned.m8n8.x4.trans.shared.b16 [%0], {%1,%2,%3,%4};" ::"r"(a), "r"(r0), "r"(r1), "r"(r2), "r"(r3) : "memory");
}
__device__ __forceinline__ uint4 ldg128_nc(const void* p) { uint4 v; asm volatile("ld.global.nc.L1::no_allocate.v4.u32 {%0,%1,%2,%3}, [%4];" : "=r"(v.x), "=r"(v.y), "=r"(v.z), "=r"(v.w) : "l"(p)); return v; }
__device__ __forceinline__ void stg128(void* p, uint4 v) { asm volatile("st.global.L1::no_allocate.v4.u32 [%0], {%1,%2,%3,%4};" ::"l"(p), "r"(v.x), "r"(v.y), "r"(v.z), "r"(v.w) : "memory"); }
__device__ __forceinline__ uint32_t pack_bf16(float lo, float hi) { uint32_t r; asm("cvt.rn.bf16x2.f32 %0, %1, %2;" : "=r"(r) : "f"(hi), "f"(lo)); return r; }
__device__ __forceinline__ uint32_t bmul2(uint32_t a, uint32_t b) { uint32_t r; asm("mul.rn.bf16x2 %0, %1, %2;" : "=r"(r) : "r"(a), "r"(b)); return r; }
__device__ __forceinline__ uint32_t bfma2(uint32_t a, uint32_t b, uint32_t c) { uint32_t r; asm("fma.rn.bf16x2 %0, %1, %2, %3;" : "=r"(r) : "r"(a), "r"(b), "r"(c)); return r; }
__device__ __forceinline__ uint32_t blo2(uint32_t a) { uint32_t r; asm("{\n.reg .b16 l, h;\nmov.b32 {l, h}, %1;\nmov.b32 %0, {l, l};\n}" : "=r"(r) : "r"(a)); return r; }
__device__ __forceinline__ float bf2f(__nv_bfloat16 v) { return __bfloat162float(v); }

#define R8(d, o) "+f"(d[o]), "+f"(d[o + 1]), "+f"(d[o + 2]), "+f"(d[o + 3]), "+f"(d[o + 4]), "+f"(d[o + 5]), "+f"(d[o + 6]), "+f"(d[o + 7])
#define R16(d, o) R8(d, o), R8(d, o + 8)
#define R64(d, o) R16(d, o), R16(d, o + 16), R16(d, o + 32), R16(d, o + 48)
template <int TA> __device__ __forceinline__ void wgmma_n128(float* d, uint64_t da, uint64_t db, int scale_d) {
  asm volatile("{\n.reg .pred p;\nsetp.ne.b32 p, %66, 0;\n"
    "wgmma.mma_async.sync.aligned.m64n128k16.f32.bf16.bf16 {"
    "%0,%1,%2,%3,%4,%5,%6,%7,%8,%9,%10,%11,%12,%13,%14,%15,%16,%17,%18,%19,%20,%21,%22,%23,%24,%25,%26,%27,%28,%29,%30,%31,"
    "%32,%33,%34,%35,%36,%37,%38,%39,%40,%41,%42,%43,%44,%45,%46,%47,%48,%49,%50,%51,%52,%53,%54,%55,%56,%57,%58,%59,%60,%61,%62,%63"
    "}, %64, %65, p, 1, 1, %67, 0;\n}\n"
    : R64(d, 0)
    : "l"(da), "l"(db), "r"(scale_d), "n"(TA));
}
template <int N> __device__ __forceinline__ void fence_regs(float* d) {
#pragma unroll
  for (int i = 0; i < N; i++) asm volatile("" : "+f"(d[i])::"memory");
}
#define PMFENCE() asm volatile("pmevent 0;" ::: "memory")
__device__ __forceinline__ void cmul(float ar, float ai, float br, float bi, float& cr, float& ci) {
  cr = ar * br - ai * bi; ci = ar * bi + ai * br;
}
__device__ __forceinline__ void csq(float& r, float& i) { const float x = fmaf(r, r, -i * i), y = (r + r) * i; r = x; i = y; }

#define W8(d, o) "=f"(d[o]), "=f"(d[o + 1]), "=f"(d[o + 2]), "=f"(d[o + 3]), "=f"(d[o + 4]), "=f"(d[o + 5]), "=f"(d[o + 6]), "=f"(d[o + 7])
#define L16 "{%0,%1,%2,%3,%4,%5,%6,%7,%8,%9,%10,%11,%12,%13,%14,%15}"
#define L32 "{%0,%1,%2,%3,%4,%5,%6,%7,%8,%9,%10,%11,%12,%13,%14,%15,%16,%17,%18,%19,%20,%21,%22,%23,%24,%25,%26,%27,%28,%29,%30,%31}"
template <int ACC, int TB> __device__ __forceinline__ void rs_n32(float* d, const uint32_t* a, uint64_t db) {
  if constexpr (ACC) asm volatile("wgmma.mma_async.sync.aligned.m64n32k16.f32.bf16.bf16 " L16 ", {%16,%17,%18,%19}, %20, 1, 1, 1, %21;" : R16(d, 0) : "r"(a[0]), "r"(a[1]), "r"(a[2]), "r"(a[3]), "l"(db), "n"(TB));
  else asm volatile("wgmma.mma_async.sync.aligned.m64n32k16.f32.bf16.bf16 " L16 ", {%16,%17,%18,%19}, %20, 0, 1, 1, %21;" : W8(d, 0), W8(d, 8) : "r"(a[0]), "r"(a[1]), "r"(a[2]), "r"(a[3]), "l"(db), "n"(TB));
}
template <int ACC, int TB> __device__ __forceinline__ void ss_n64(float* d, uint64_t da, uint64_t db) {
  if constexpr (ACC) asm volatile("wgmma.mma_async.sync.aligned.m64n64k16.f32.bf16.bf16 " L32 ", %32, %33, 1, 1, 1, 0, %34;" : R16(d, 0), R16(d, 16) : "l"(da), "l"(db), "n"(TB));
  else asm volatile("wgmma.mma_async.sync.aligned.m64n64k16.f32.bf16.bf16 " L32 ", %32, %33, 0, 1, 1, 0, %34;" : W8(d, 0), W8(d, 8), W8(d, 16), W8(d, 24) : "l"(da), "l"(db), "n"(TB));
}
template <int ACC> __device__ __forceinline__ void ss_n32_tt(float* d, uint64_t da, uint64_t db) {
  if constexpr (ACC) asm volatile("wgmma.mma_async.sync.aligned.m64n32k16.f32.bf16.bf16 " L16 ", %16, %17, 1, 1, 1, 1, 1;" : R16(d, 0) : "l"(da), "l"(db));
  else asm volatile("wgmma.mma_async.sync.aligned.m64n32k16.f32.bf16.bf16 " L16 ", %16, %17, 0, 1, 1, 1, 1;" : W8(d, 0), W8(d, 8) : "l"(da), "l"(db));
}
__device__ __forceinline__ void stsm4(uint32_t a, uint32_t r0, uint32_t r1, uint32_t r2, uint32_t r3) {
  asm volatile("stmatrix.sync.aligned.m8n8.x4.shared.b16 [%0], {%1,%2,%3,%4};" ::"r"(a), "r"(r0), "r"(r1), "r"(r2), "r"(r3) : "memory");
}
template <int N> __device__ __forceinline__ void fence_u32(uint32_t* d) {
#pragma unroll
  for (int i = 0; i < N; i++) asm volatile("" : "+r"(d[i])::"memory");
}
__device__ __forceinline__ void pack32(uint32_t* f, const float* z) {
#pragma unroll
  for (int i = 0; i < 16; i++) f[i] = pack_bf16(z[2 * i], z[2 * i + 1]);
}
template <int INV> __device__ __forceinline__ void twiddle(uint32_t* f, const uint32_t* tp, const uint32_t* ts) {
#pragma unroll
  for (int i = 0; i < 8; i++) {
    uint32_t x = f[2 * i + INV], y = f[2 * i + 1 - INV];
    x = bfma2(tp[i & 3], y, x); y = bfma2(ts[i & 3], x, y); x = bfma2(tp[i & 3], y, x);
    f[2 * i + INV] = x; f[2 * i + 1 - INV] = y;
  }
}
__device__ __forceinline__ uint32_t bfnma2(uint32_t a, uint32_t b, uint32_t c) { uint32_t r; asm("{\n.reg .b32 t;\nmul.bf16x2 t, %1, %2;\nsub.bf16x2 %0, %3, t;\n}" : "=r"(r) : "r"(a), "r"(b), "r"(c)); return r; }
__device__ __forceinline__ uint32_t bfms2(uint32_t a, uint32_t b, uint32_t c) { uint32_t r; asm("{\n.reg .b32 t;\nmul.bf16x2 t, %1, %2;\nsub.bf16x2 %0, t, %3;\n}" : "=r"(r) : "r"(a), "r"(b), "r"(c)); return r; }
template <int ADD> __device__ __forceinline__ void bimac(uint32_t* o, const uint32_t* a, const uint32_t* b, const uint32_t* c) {
#pragma unroll
  for (int J = 0; J < 2; J++) {
    const uint32_t Pr = a[2 * J], Pi = a[2 * J + 1], Qr = a[2 * J + 4], Qi = a[2 * J + 5], pr = b[2 * J], pi = b[2 * J + 1], qr = b[2 * J + 4], qi = b[2 * J + 5];
    uint32_t x0, x1, x2, x3;
    if (ADD == 0) { x0 = bmul2(Pr, pr); x1 = bmul2(Pr, pi); x2 = bmul2(Pr, qr); x3 = bmul2(Pr, qi); }
    if (ADD == 1) { x0 = bfma2(Pr, pr, c[2 * J]); x1 = bfma2(Pr, pi, c[2 * J + 1]); x2 = bfma2(Pr, qr, c[2 * J + 4]); x3 = bfma2(Pr, qi, c[2 * J + 5]); }
    if (ADD == 2) { x0 = bfma2(Pr, pr, c[2 * J + 1]); x1 = bfms2(Pr, pi, c[2 * J]); x2 = bfma2(Pr, qr, c[2 * J + 5]); x3 = bfms2(Pr, qi, c[2 * J + 4]); }
    x0 = bfnma2(Pi, pi, x0); x1 = bfma2(Pi, pr, x1); x2 = bfnma2(Pi, qi, x2); x3 = bfma2(Pi, qr, x3);
    x0 = bfnma2(Qr, qr, x0); x1 = bfnma2(Qr, qi, x1); x2 = bfma2(Qr, pr, x2); x3 = bfma2(Qr, pi, x3);
    x0 = bfma2(Qi, qi, x0); x1 = bfnma2(Qi, qr, x1); x2 = bfnma2(Qi, pi, x2); x3 = bfma2(Qi, pr, x3);
    o[2 * J] = x0; o[2 * J + 1] = x1; o[2 * J + 4] = x2; o[2 * J + 5] = x3;
  }
}
__device__ __forceinline__ void sincos8k(int n, float& s, float& c) {
  const float x = (float)((n << 19) >> 19) * (6.283185307179586f / 8192.f);
  s = __sinf(x); c = __cosf(x);
}
__device__ __forceinline__ void fft_tables(uint32_t f1a, uint32_t f2a, int w, int lane, uint32_t* tp, uint32_t* ts, float& d0r, float& d0i) {
  const int c = lane & 3, f1 = 8 * w + (lane >> 2);
#pragma unroll 1
  for (int J = 3; J >= 0; J--) {
    const int a = 8 * J + 2 * c;
    float s0, c0, s1, c1;
    sincos8k(64 * (4 * f1 + 1) * a + 31 * (4 * f1 - 63), d0i, d0r); sincos8k(64 * (4 * f1 + 1) * (a + 1) + 31 * (4 * f1 - 63), s1, c1);
    d0r *= 0.125f; d0i *= 0.125f;
    sts32(f1a + w * 1024 + J * 128 + lane * 4, pack_bf16(d0r, 0.125f * c1)); sts32(f1a + w * 1024 + 512 + J * 128 + lane * 4, pack_bf16(d0i, 0.125f * s1));
    sincos8k(128 * (2 * (a & 15) + 1) * f1 - 128 * (a & 16), s0, c0); sincos8k(128 * (2 * (a & 15) + 3) * f1 - 128 * (a & 16), s1, c1);
    sts32(f2a + w * 512 + J * 128 + lane * 4, pack_bf16(c0, c1));
    sincos8k((4 * f1 - 63) * (2 * a - 31), s0, c0); sincos8k((4 * f1 - 63) * (2 * a - 29), s1, c1);
#pragma unroll
    for (int i = 3; i > 0; i--) { ts[i] = ts[i - 1]; tp[i] = tp[i - 1]; }
    ts[0] = pack_bf16(s0, s1); tp[0] = pack_bf16(-__fdividef(s0, 1.f + c0), -__fdividef(s1, 1.f + c1));
  }
  if (c != 0) d0r = d0i = 0.f;
}

template <int SWAPB>
__global__ void __cluster_dims__(2, 1, 1) __launch_bounds__(512, 1)
fused_kernel(const __grid_constant__ Params P, const __grid_constant__ CUtensorMap mX, const __grid_constant__ CUtensorMap mB,
             const __grid_constant__ CUtensorMap mCre, const __grid_constant__ CUtensorMap mCim, const __grid_constant__ CUtensorMap mXs,
             const __grid_constant__ CUtensorMap mK, const __grid_constant__ CUtensorMap mV, const __grid_constant__ CUtensorMap mQ, const __grid_constant__ CUtensorMap mS,
             const __grid_constant__ CUtensorMap mO) {
  extern __shared__ __align__(1024) uint8_t smem_raw[];
  const uint32_t sb = (uint32_t)__cvta_generic_to_shared(smem_raw);
  const uint32_t bars = sb + OFF_BAR;
  const int slot = (P.slot[blockIdx.x >> 3] >> (4 * (blockIdx.x & 6))) & 63, rank = blockIdx.x & 1;
  const int j = slot & 7, tc = 2 * (slot >> 3) + rank, b = 2 * slot + rank;
  const int tid = threadIdx.x;
  const int warp = __shfl_sync(0xffffffffu, tid >> 5, 0);
  const int wg = warp >> 2;
  const uint32_t c_start = clk32();
  auto kblock = [&](int n) { return ((n & 14) == 0 || (n & 14) == 2 * j ? n ^ (2 * j) : n) & 31; };
  auto send_y = [&](int r) {
    const uint32_t src = sb + OFF_U + 4 * (rank ^ 1) * U_N8 + r * U_CH, dst = r >= 2 ? sb + OFF_U + 4 * rank * U_N8 + (r - 2) * U_CH : sb + OFF_IN + 96 + r * 2064;
#pragma unroll 1
    for (int n = 0; n < 4; n++) bulk_send(dst + n * (r >= 2 ? U_N8 : 512), src + n * U_N8, 512, bars + (B_IN + r) * 8, rank ^ 1);
  };
  auto load_q = [&](int i, int off, int bar) {
    const uint32_t fb = bars + bar * 8 + 4 * (i & 2);
    mbar_expect(fb, 4096); tma4d(sb + off + 2048 * (i & 2), &mQ, 16 * slot, 0, 4 * i, 4 * rank, fb);
  };
  auto head = [&](int n) {
    const uint32_t fb = bars + (B_FULL + n) * 8, dst = sb + OFF_RING + n * STAGE_BYTES;
    mbar_expect(fb, STAGE_BYTES);
    tma4d(dst + 16384, &mX, 64 * n, 0, 4 * tc, 0, fb);
    tma4d(dst, &mB, 64 * n, 0, 0, 8 * j, fb);
    tma4d(dst + 8192, &mB, 64 * n, 0, 0, 8 * j + 4, fb);
  };
  if (warp == 0 && elect_one()) {
    STAMP(0); GSTAMP(0);
#pragma unroll
    for (int s = 0; s < STAGES; s++) mbar_init(bars + (B_FULL + s) * 8, 1);
    head(0);
    STAMP(1);
    asm volatile("fence.mbarrier_init.release.cluster;" ::: "memory");
  }
  if (wg == 3 && elect_one()) {
    if (warp < 15) {
#pragma unroll
      for (int s = 0; s < 11; s++) mbar_init(bars + 8 * B_XI + (warp & 3) * 88 + 8 * s, 1);
    } else {
#pragma unroll
      for (int s = B_EMPTY; s < B_KVE + 3; s++) mbar_init(bars + 8 * s, s < B_COEF ? 2 : s == B_COEF ? 128 : 4);
    }
    asm volatile("fence.mbarrier_init.release.cluster;" ::: "memory");
  }
  __syncwarp();
  asm volatile("barrier.cluster.arrive.relaxed.aligned;" ::: "memory");
  if (warp == 0 && elect_one()) {
#pragma unroll 1
    for (int n = 1; n < HEAD; n++) { spin_until(c_start, ST_T0 + n * ST_DELAY); head(n); }
  }
  __syncwarp();
#define CLUSTER_WAIT() asm volatile("barrier.cluster.wait.aligned;" ::: "memory")

  if (wg == 3) {
    asm volatile("setmaxnreg.dec.sync.aligned.u32 24;");
    CLUSTER_WAIT();
    if (warp < 14) {
      if (elect_one()) {
        uint32_t so = 8 * (HEAD % STAGES), ph = HEAD < STAGES;
        auto step = [&](auto issue) {
          mbar_wait(bars + B_EMPTY * 8 + so, ph);
          issue(sb + OFF_RING + (so << 12), bars + B_FULL * 8 + so);
          so += 8;
          if (so == 8 * STAGES) { so = 0; ph ^= 1; }
        };
        if (warp == 12) {
          auto g1 = [&](int n0, int n1, int grp) {
#pragma unroll 1
            for (int n = n0; n < n1; n++) step([&](uint32_t dst, uint32_t fb) { mbar_expect(fb, STAGE_BYTES); tma4d_mc(dst + rank * 8192, &mB, n * 64, 0, 0, grp + 4 * rank, fb); });
          };
#pragma unroll 1
          for (int n = HEAD; n < STAGES; n++) { spin_until(c_start, ST_T0 + n * ST_DELAY); g1(n, n + 1, 8 * j); }
          g1(STAGES, 16, 8 * j);
          g1(0, XPOS - 16, 8 * j + 64);
          step([&](uint32_t dst, uint32_t fb) { mbar_expect(fb, STAGE_BYTES); tma4d(dst, &mXs, 128 * j, 0, 0, 16 * tc, fb); mbar_arrive(bars + B_XI * 8); });
          g1(XPOS - 16, 16, 8 * j + 64);
#pragma unroll 1
          for (int n = 0; n < 32; n += 2) {
            const int col = kblock(n) * 32;
#pragma unroll
            for (int part = 0; part < 2; part++)
              step([&](uint32_t dst, uint32_t fb) { mbar_expect(fb, STAGE_BYTES); tma5d_mc(dst + rank * 8192, part ? &mCim : &mCre, col, 0, 0, 0, 8 * j + 4 * rank, fb); });
          }
        } else {
          auto g1 = [&](int n0, int n1, int nb) {
#pragma unroll 1
            for (int n = n0; n < n1; n++) step([&](uint32_t dst, uint32_t fb) { tma4d(dst + 16384, &mX, n * 64, 0, 4 * tc, 0, fb); TSTAMP(1, n + nb); });
          };
          auto g2 = [&](int n0, int n1) {
#pragma unroll 1
            for (int n = n0; n < n1; n++) step([&](uint32_t dst, uint32_t fb) { bulk_load(dst + 16384, g_h + (32 * tc + kblock(n)) * 1024, 16384, fb); TSTAMP(1, n + 32); });
          };
#pragma unroll 1
          for (int n = HEAD; n < STAGES; n++) { spin_until(c_start, ST_T0 + n * ST_DELAY); g1(n, n + 1, 0); }
          g1(STAGES, 16, 0);
          g1(0, XPOS - 16, 16);
          step([&](uint32_t dst, uint32_t fb) { tma4d(dst + 16384, &mXs, 128 * j + 64, 0, 0, 16 * tc, fb); });
          g1(XPOS - 16, 16, 16);
#pragma unroll 1
          for (int v = 0; v < 2; v++) {
            STAMP(4 + v);
            mbar_wait(bars + B_HP * 8, v);
            fence_proxy_async_global();
            STAMP(6 + v);
            g2(16 * v, 16 * v + 2);
            mbar_wait(bars + B_HR * 8, v);
            fence_proxy_async_global();
            g2(16 * v + 2, 16 * v + 16);
          }
        }
      }
    } else if (warp == 15) {
      mbar_wait(bars + B_COEF * 8, 0);
      const unsigned epoch = lds32(bars + B_EPOCH * 8);
#pragma unroll 1
      for (int v = 0; v < 2; v++) {
        unsigned* fp = &g_flagH[(16 * v + tc) * 32];
        if (((PFC >> v) & 1) && elect_one()) {
          wait_until(v ? clk32() : c_start, (v ? PFC_T1 : PFC_T0) + (slot >> 3) * PFC_DT);
#pragma unroll
          for (int part = 0; part < 2; part++)
            asm volatile("cp.async.bulk.prefetch.tensor.5d.L2.global [%0, {%1, %2, %2, %2, %3}];" ::"l"(part ? &mCim : &mCre), "r"(512 * v + 8 * (slot & 56)), "r"(0), "r"(8 * j + 4 * rank) : "memory");
        }
        __syncwarp();
        bar_sync(4 + v, 160);
        if (elect_one()) {
          asm volatile("red.release.gpu.global.add.u32 [%0], 1;" ::"l"(fp) : "memory");
          mbar_arrive(bars + B_HP * 8);
          STAMP(16 + 10 * v);
          int it = 0;
          while (ld_acquire(fp) != 8 * epoch && ++it < (SPIN_LIMIT << 4)) __nanosleep(POLL_NS);
          STAMP(2 + v);
          mbar_arrive(bars + B_HR * 8);
        }
        __syncwarp();
      }
    } else if (elect_one()) {
      const int ch0 = 16 * slot;
      auto load_k = [&](int s, uint32_t dst) { const uint32_t fb = bars + (B_KF + (s & 1)) * 8; mbar_expect(fb, 4096); tma2d(dst, &mS, 0, 64 * (8 * b + s), fb); };
      prefetch_map(&mS); prefetch_map(&mK); prefetch_map(&mV);
      wait_until(c_start, K_T0);
      load_k(0, sb + OFF_U + (4 * rank + 3) * U_N8); load_k(1, sb + OFF_U + (4 * rank + 3) * U_N8 - 4096);
      {
        uint32_t so = 16, ph = 1;
#pragma unroll 1
        for (int e = 0; e < 9; e++) {
          const uint32_t fb = bars + B_KVF * 8 + so, dst = sb + OFF_KV + (so << 10);
          wait_until(c_start, KV_T0 + (e ? 2 * e - 1 : 0) * KV_DT);
          mbar_wait(bars + B_KVE * 8 + so, ph);
          const uint32_t c1 = clk32();
          mbar_expect(fb, e ? 8192 : 4096);
          if (e > 0) KSTAMP(1, e - 1);
          tma3d(dst, &mK, ch0, 32 * rank - (e == 0), (4 * e - 4) & 31, fb);
          if (e > 0) { wait_until(c1, KV_DV); tma3d(dst + 4096, &mV, ch0, 32 * rank, 4 * e - 4, fb); }
          so += 8;
          if (so == 24) so = 0;
          if (so == 16) ph ^= 1;
        }
      }
      prefetch_map(&mCre); prefetch_map(&mCim); prefetch_map(&mXs); prefetch_map(&mQ); prefetch_map(&mO);
      mbar_wait(bars + B_KVE * 8, 0);
      load_k(2, sb + OFF_K); load_k(3, sb + OFF_K + 4096);
      mbar_wait(bars + (B_UF + 3) * 8, 0);
#pragma unroll 1
      for (int ch = 0; ch < 7; ch++) {
        if (ch > 0) {
          mbar_wait(bars + (B_Y + (ch & 3)) * 8, ch >> 2);
          if (ch > 2) mbar_wait(bars + (B_IN + ch - 3) * 8, 0);
          send_y(ch - 1);
        }
        if (ch < 6) {
          mbar_wait(bars + (B_KE + (ch & 1)) * 8, (ch >> 1) & 1);
          if (ch < 4) load_k(ch + 4, sb + OFF_K + (ch & 1) * 4096);
          if (PFQ && ch == PFQ - 1) asm volatile("cp.async.bulk.prefetch.tensor.4d.L2.global [%0, {%1, %2, %3, %4}];" ::"l"(&mQ), "r"(16 * (slot & ~3)), "r"(0), "r"(16 + 4 * (slot & 3)), "r"(4 * rank) : "memory");
          if (ch >= 2) load_q(2 * (ch & 1) + (ch < 4), ch < 4 ? OFF_Q : OFF_K, ch < 4 ? B_QF : B_KF);
        }
      }
    }
    return;
  } else if (wg == 2) {
    asm volatile("setmaxnreg.inc.sync.aligned.u32 %0;" ::"n"(488 - 2 * GREG));
    const int t = tid & 127, w = warp & 3, lane = t & 31, g = lane >> 2, c = lane & 3;
    const uint4 s2[2] = {ldg128_nc(P.shift_k + (8 * b + 2 * c) * 4), ldg128_nc(P.shift_k + (8 * (b ^ 1) + 2 * c) * 4)};
    const uint32_t dskip = __bfloat16_as_ushort(P.ssm_D[8 * b + (t & 7)]);
    uint32_t tp[4] = {}, ts[4] = {};
    float d0r, d0i;
    fft_tables(sb + OFF_F1, sb + OFF_F2, w, lane, tp, ts, d0r, d0i);
    if (t == 0) STAMP(19);
    CLUSTER_WAIT();
    if (t < 12) mbar_expect(bars + (B_IN + t) * 8, t < 6 ? 2048 : t < 8 ? 4 * (U_CH + 512) : U_N8);
    if (t < 8) sts32(sb + OFF_D + 4 * t, dskip << 16);
    const uint64_t dF1a = make_desc(sb + OFF_F1, 128, 512, 0), dF1b = make_desc(sb + OFF_F1, 512, 128, 0);
    const uint64_t dF2f = make_desc(sb + OFF_F2, 512, 128, 0), dF2i = make_desc(sb + OFF_F2, 128, 512, 0);
    auto T1k = [&](float* z, uint64_t dk) { wg_fence(); ss_n64<0, 1>(z, dF1a, dk); ss_n64<1, 1>(z, dF1a + 16, dk + 64); wg_commit(); };
    auto T1u = [&](float* z, uint64_t du) { wg_fence(); ss_n64<0, 0>(z, dF1a, du); ss_n64<1, 0>(z, dF1a + 16, du + 16); wg_commit(); };
    auto T2 = [&](float* s, const uint32_t* f) {
      wg_fence();
      rs_n32<0, 1>(s, f, dF2f); rs_n32<0, 1>(s + 16, f + 8, dF2f); rs_n32<1, 1>(s, f + 4, dF2f + 64); rs_n32<1, 1>(s + 16, f + 12, dF2f + 64);
      wg_commit();
    };
    auto product = [&](uint32_t* pr, const uint32_t* kh, const uint32_t* uh) {
      bimac<0>(pr, kh, uh, pr); bimac<2>(pr + 8, kh + 8, uh, pr); bimac<1>(pr + 8, kh, uh + 8, pr + 8);
      fence_u32<16>(pr);
    };
    float zk[32] = {};
    uint32_t pr[16];
    {
      uint32_t kh0[16];
      {
        float z0[32], sk[32];
        uint32_t fk[16];
        const uint64_t dk = make_desc(sb + OFF_U + (4 * rank + 3) * U_N8, 2048, 512, 2);
        fence_proxy_async_smem();
        bar_sync(7, 128);
        mbar_wait(bars + B_KF * 8, 0);
        T1k(z0, dk);
        mbar_wait(bars + (B_KF + 1) * 8, 0);
        T1k(zk, dk - 256);
        wg_wait<0>(); fence_regs<32>(z0); fence_regs<32>(zk);
        const float dd = __uint_as_float(lds32(sb + OFF_D));
        z0[0] = fmaf(d0r, dd, z0[0]); z0[2] = fmaf(d0i, dd, z0[2]);
        pack32(fk, z0); twiddle<0>(fk, tp, ts); fence_u32<16>(fk);
        T2(sk, fk);
        wg_wait<0>(); fence_regs<32>(sk); fence_u32<16>(fk);
        pack32(kh0, sk); fence_u32<16>(kh0);
      }
      {
        uint32_t sk[2][4], kx[2][8];
#pragma unroll
        for (int o = 0; o < 2; o++) {
          sk[o][0] = __byte_perm(s2[o].x, s2[o].z, 0x5410); sk[o][1] = __byte_perm(s2[o].x, s2[o].z, 0x7632);
          sk[o][2] = __byte_perm(s2[o].y, s2[o].w, 0x5410); sk[o][3] = __byte_perm(s2[o].y, s2[o].w, 0x7632);
        }
        const uint32_t la = sb + OFF_KV + (lane >> 3) * 1024 + (8 * w + (lane & 7)) * 32 + ((rank ^ ((lane >> 2) & 1)) << 4);
        const uint32_t uo = (lane & 7) * U_CH + w * 128 + (lane >> 3) * 16;
        mbar_wait(bars + (B_KVF + 2) * 8, 0);
        if (t == 0) STAMP(27);
        ldsm4(kx[0], la + 16384); ldsm4(kx[1], (la ^ 16) + 16384);
        if (lane == 0) mbar_arrive(bars + (B_KVE + 2) * 8 + (kx[0][1] & kx[1][1] & P.zero));
        uint32_t so = 0, ph = 0;
#pragma unroll 1
        for (int n = 0; n < 4; n++) {
          const uint32_t own = sb + OFF_U + (4 * rank + n) * U_N8, box = n < 3 ? sb + OFF_U + (4 * (rank ^ 1) + n + 1) * U_N8 : sb + OFF_IN;
#pragma unroll
          for (int e = 0; e < 2; e++) {
            uint32_t vx[2][4];
            mbar_wait(bars + B_KVF * 8 + so, ph);
            if (t == 0) KSTAMP(2, 2 * n + e);
#pragma unroll
            for (int o = 0; o < 2; o++) { ldsm4(kx[o] + 4, (la ^ (16 * o)) + (so << 10)); ldsm4(vx[o], (la ^ (16 * o)) + (so << 10) + 4096); }
            if (lane == 0) mbar_arrive(bars + B_KVE * 8 + so + (kx[0][4] & kx[1][4] & vx[0][0] & vx[1][0] & P.zero));
#pragma unroll
            for (int o = 0; o < 2; o++) {
#pragma unroll
              for (int i = 0; i < 4; i++) vx[o][i] = bmul2(bfma2(kx[o][i + 4], sk[o][0], bfma2(kx[o][i + 3], sk[o][1], bfma2(kx[o][i + 2], sk[o][2], bmul2(kx[o][i + 1], sk[o][3])))), vx[o][i]);
              stsm4t((o ? box : own) + uo + e * 64, vx[o][0], vx[o][1], vx[o][2], vx[o][3]);
              kx[o][1] = kx[o][5]; kx[o][2] = kx[o][6]; kx[o][3] = kx[o][7];
            }
            if (t == 0) KSTAMP(3, 2 * n + e);
            so += 8;
            if (so == 24) so = 0;
            if (so == 16) ph ^= 1;
          }
          fence_proxy_async_smem();
          bar_sync(7, 128);
          if (w == 0 && elect_one()) {
            if (n > 0) mbar_wait(bars + B_UF * 8 + 8 * (n - 1), 0);
            bulk_send(own, box, U_N8, bars + B_UF * 8 + 8 * n, rank ^ 1);
          }
          __syncwarp();
        }
        if (t == 0) STAMP(28);
      }
      float zu[32], su[32];
      uint32_t fu[16], uh[16];
#pragma unroll
      for (int n = 0; n < 4; n++) mbar_wait(bars + (B_UF + n) * 8, 0);
      T1u(zu, make_desc(sb + OFF_U, 128, U_N8, 0));
      wg_wait<0>(); fence_regs<32>(zu);
      pack32(fu, zu); twiddle<0>(fu, tp, ts); fence_u32<16>(fu);
      T2(su, fu);
      wg_wait<0>(); fence_regs<32>(su); fence_u32<16>(fu);
      pack32(uh, su);
      product(pr, kh0, uh);
      if (t == 0) STAMP(54);
    }
    {
#define CF(i) do { if ((CFM >> (i)) & 1) PMFENCE(); } while (0)
#define CP(i)
      const uint32_t vs = w < 2 ? 512 : U_N8;
      uint32_t va = (w < 2 ? sb + OFF_VP : sb + OFF_U) + ((lane >> 4) & 1) * vs + (w & 1) * 256 + (lane & 15) * 16;
      uint32_t ya = sb + OFF_U + (2 * w + ((lane >> 3) & 1)) * U_N8 + (lane >> 4) * 128 + (lane & 7) * 16;
      uint64_t du = make_desc(sb + OFF_U, 128, U_N8, 0), dk = make_desc(sb + OFF_K, 2048, 512, 2);
      const uint64_t dv = make_desc(sb + OFF_VP, 128, 512, 0);
      uint32_t yp[8] = {};
      uint32_t yq = sb + OFF_Q + lane * 16;
      auto store_y = [&]() { stsm4(yq, yp[0], yp[1], yp[2], yp[3]); stsm4(yq + 256, yp[4], yp[5], yp[6], yp[7]); };
      auto step = [&](int ch, auto fwd) {
        constexpr bool FWD = decltype(fwd)::value;
        float zu[32], sk[32], su[32], v[32], y[16];
        uint32_t kh[16], uh[16], fk[16], fu[16], fv[16];
        CP(16);
        wg_fence();
        rs_n32<0, 0>(v, pr, dF2i); rs_n32<0, 0>(v + 16, pr + 8, dF2i); rs_n32<1, 0>(v, pr + 4, dF2i + 16); rs_n32<1, 0>(v + 16, pr + 12, dF2i + 16);
        wg_commit();
        CF(0);
        store_y();
        if (FWD) {
          const float dd = __uint_as_float(lds32(sb + OFF_D + 4 * (ch + 1)));
          zk[0] = fmaf(d0r, dd, zk[0]); zk[2] = fmaf(d0i, dd, zk[2]);
          pack32(fk, zk); twiddle<0>(fk, tp, ts); fence_u32<16>(fk);
          CP(1);
          T2(sk, fk);
          CF(2);
          mbar_wait(bars + (B_KF + (ch & 1)) * 8, ((ch >> 1) & 1) ^ 1);
          wg_wait<1>();
        } else {
#pragma unroll
          for (int r = 3; r < 6; r++) mbar_wait(bars + (B_IN + r) * 8, 0);
          wg_wait<0>();
        }
        fence_regs<32>(v); fence_u32<16>(pr); CP(3);
        pack32(fv, v); fence_u32<16>(fv);
        CF(4);
        if (FWD) T1u(zu, du + U_CH / 16);
        CF(5);
        if (FWD && (VO & 1)) { wg_wait<1>(); fence_regs<32>(sk); fence_u32<16>(fk); pack32(kh, sk); }
        twiddle<1>(fv, tp, ts);
#pragma unroll
        for (int i = 0; i < 4; i++) stsm4(va + 2 * i * vs, fv[4 * i], fv[4 * i + 1], fv[4 * i + 2], fv[4 * i + 3]);
        if (FWD) {
          if (!(VO & 1)) {
            CF(6);
            wg_wait<1>(); fence_regs<32>(sk); fence_u32<16>(fk);
            pack32(kh, sk);
          }
          fence_u32<16>(kh);
          CF(7);
          T1k(zk, dk);
          CF(8);
          wg_wait<1>(); fence_regs<32>(zu);
          pack32(fu, zu); twiddle<0>(fu, tp, ts); fence_u32<16>(fu);
          CP(9);
          T2(su, fu);
          CF(10);
        }
        fence_proxy_async_smem();
        bar_sync(7, 128);
        wg_fence(); CP(11);
        ss_n32_tt<0>(y, dv, dF1b); ss_n32_tt<1>(y, dv + 16, dF1b + 64); ss_n32_tt<1>(y, du, dF1b + 128); ss_n32_tt<1>(y, du + 16, dF1b + 192);
        wg_commit();
        if (FWD && t == 0) mbar_arrive(bars + (B_Y + (ch & 3)) * 8);
        CF(12);
        if (FWD) {
          wg_wait<1>(); fence_regs<32>(su); fence_u32<16>(fu); fence_regs<32>(zk); CP(13);
          if (t == 0) mbar_arrive(bars + (B_KE + (ch & 1)) * 8);
          pack32(uh, su);
          if (VO & 2) {
            bimac<0>(pr, kh, uh, pr); bimac<2>(pr + 8, kh + 8, uh, pr); fence_u32<16>(pr);
            CF(14);
            wg_wait<0>(); fence_regs<16>(y);
            bimac<1>(pr + 8, kh, uh + 8, pr + 8); fence_u32<8>(pr + 8);
          } else product(pr, kh, uh);
          du += U_CH / 16; dk += (ch & 1) ? -256 : 256;
          if (w >= 2) va += U_CH;
        }
        if (!FWD || !(VO & 2)) { CF(14); wg_wait<0>(); fence_regs<16>(y); CP(15); }
#pragma unroll
        for (int i = 0; i < 8; i++) yp[i] = pack_bf16(y[2 * i], y[2 * i + 1]);
        fence_u32<8>(yp);
        yq = ya;
        ya += U_CH; CP(17);
        if (t == 0) STAMP(55 + ch);
      };
#pragma unroll 1
      for (int ch = 0; ch < 7; ch++) step(ch, std::true_type());
      step(7, std::false_type());
      store_y();
    }
    fence_proxy_async_smem();
    bar_sync(7, 128);
    if (elect_one()) bulk_send(sb + OFF_U + (4 * rank + w) * U_N8 + 4 * U_CH, sb + OFF_U + (4 * (rank ^ 1) + w) * U_N8 + 6 * U_CH, U_CH + 512, bars + (B_IN + 6) * 8, rank ^ 1);
    __syncwarp();
    asm volatile("bar.arrive 9, 256;" ::: "memory");
    if (t == 0) STAMP(29);
  } else {
    asm volatile("setmaxnreg.inc.sync.aligned.u32 %0;" ::"n"(GREG));
    const int t = tid & 127, w = warp & 3, lane = t & 31, g = lane >> 2, c = lane & 3;
    if (wg == 1) {
      wait_until(c_start, COEF_T0);
      const int p = 64 * j + (t & 63) + 8 * (t & 64);
      const float Lr = bf2f(P.lam_re[p]), Li = bf2f(P.lam_im[p]);
      const uint32_t ds = __bfloat16_as_ushort(P.Dskip[128 * j + t]);
      const unsigned epoch = ld_relaxed(&g_epoch[b * 32]) + 1;
      const float dt = bf2f(__float2bfloat16_rn(expf(bf2f(P.log_dt[p]))));
      const float e = expf(dt * Lr);
      float sn, cs;
      {
        const double z = (double)(dt * Li) * 0.15915494309189535;
        sincospif(2.f * (float)(z - rint(z)), &sn, &cs);
      }
      const float lr = e * cs, li = e * sn;
      const float nr = lr - 1.0f, ni = li;
      const bool big = fabsf(Lr) >= fabsf(Li);
      const float la = big ? Lr : Li, lb = big ? Li : Lr, r = __fdiv_rn(lb, la), inv = __frcp_rn(fmaf(lb, r, la));
      const float br = (big ? fmaf(ni, r, nr) : fmaf(nr, r, ni)) * inv, bi = (big ? fmaf(-nr, r, ni) : fmaf(ni, r, -nr)) * inv;
      sts128(sb + OFF_COEF + t * 16, make_uint4(__float_as_uint(lr), __float_as_uint(li), pack_bf16(2.f * br, 2.f * br), pack_bf16(-2.f * bi, -2.f * bi)));
      sts32(sb + OFF_DS + 4 * t, ds << 16);
      if (t == 0) sts32(bars + B_EPOCH * 8, epoch);
      if (t == 0) STAMP(52);
    }
    CLUSTER_WAIT();
    if (wg == 1) mbar_arrive(bars + B_COEF * 8);
    float d[128];
    uint32_t so = 0, ph = 0, po = 0;
    uint32_t ra;
    auto set_ra = [&]() { asm volatile("mapa.shared::cluster.u32 %0, %1, %2;" : "=r"(ra) : "r"(bars + B_EMPTY * 8), "r"((t & 1) ? rank ^ 1 : rank)); };
    set_ra();
    auto release_at = [&](uint32_t off, bool skip) {
      asm volatile("{\n.reg .pred p;\nsetp.lt.u32 p, %1, %2;\n@p mbarrier.arrive.shared::cluster.b64 _, [%0];\n}\n" ::"r"(ra + off), "r"(t), "r"(skip ? 0 : 2) : "memory");
    };
    auto release = [&](bool first) { release_at(po, first); };
    auto block = [&](auto ta, uint64_t da0, uint64_t db0, bool first, bool zero, int nn) {
      constexpr int PH = decltype(ta)::value, TA = PH > 0, KS = TA ? 128 : 2, QD = PH == 0 ? QD1 : PH == 1 ? QD2 : QD3;
      if (t == 0) TSTAMP(2, nn);
      mbar_wait(bars + B_FULL * 8 + so, ph);
      if (t == 0) TSTAMP(3, nn);
      const uint64_t da = da0 + (so << 8), db = db0 + (so << 8);
      wg_fence();
      wgmma_n128<TA>(d, da, db, !zero);
      wgmma_n128<TA>(d + 64, da + 512, db, !zero);
      wg_commit();
      wg_wait<1>();
      if (RELPOS == 0) release(first);
#pragma unroll
      for (int k = 1; k < 4; k++) {
        if (QD == 2 || (QD == 4 && k == 2)) wg_fence();
        wgmma_n128<TA>(d, da + KS * k, db + 2 * k, 1);
        wgmma_n128<TA>(d + 64, da + 512 + KS * k, db + 2 * k, 1);
        if (QD == 2 || (QD == 4 && k == 1)) wg_commit();
        if (RELPOS == 1 && k == 1) release(first);
        if ((QD == 2 && k < 3) || (QD == 4 && k == 1)) wg_wait<1>();
      }
      if (QD != 2) wg_commit();
      if (RELPOS == 2) release(first);
      po = so;
      so += 8;
      if (so == 8 * STAGES) { so = 0; ph ^= 1; }
    };
    {
      so = wg ? 8 * (16 % STAGES) : 0; ph = wg ? (16 / STAGES) & 1 : 0; po = 0;
      const uint64_t da0 = make_desc(sb + OFF_RING, 16, 1024, 1), db0 = make_desc(sb + OFF_RING + 16384, 16, 1024, 1);
      if (wg == 1) bar_sync(1, 256);
#pragma unroll 1
      for (int kb = 0; kb < 16; kb++) {
        if (16 * wg + kb == XPOS) { so += 8; if (so == 8 * STAGES) { so = 0; ph ^= 1; } }
        block(std::integral_constant<int, 0>(), da0, db0, kb == 0, kb == 0, 16 * wg + kb);
      }
      asm volatile("bar.arrive %0, 256;" ::"r"(1 + wg) : "memory");
    }
    mbar_wait(bars + B_COEF * 8, 0);
    const uint32_t ca = sb + OFF_COEF + (64 * wg + 8 * w + g) * 16;
    const uint32_t tag = __shfl_sync(0xffffffffu, lds32(bars + B_EPOCH * 8) & 3, 0);
    constexpr int RE = SWAPB ? 2 : 0, IM = 2 - RE;
    uint2* cp = &g_carry[((16 * wg + 2 * j) * 16 + tc) * 32 + 8 * w];
    const int ct = lane >> 3;
    uint2 cv[4];
    auto load_carry = [&](int i) {
#pragma unroll
      for (int m = 0; m < 4; m++)
        asm volatile("{\n.reg .pred p;\n.reg .b64 v;\nsetp.lt.s32 p, %3, %4;\nmov.b64 v, {%0,%1};\n@p ld.relaxed.gpu.global.b64 v, [%2];\nmov.b64 {%0,%1}, v;\n}\n"
                     : "+r"(cv[m].x), "+r"(cv[m].y) : "l"(cp + 512 * i + (lane & 7) - 32 * (1 + ct) - 128 * m), "r"(ct), "r"(tc - 4 * m) : "memory");
    };
    auto first_load = [&](int i) {
#pragma unroll
      for (int m = 0; m < 4; m++) cv[m] = make_uint2(tag, 0);
      load_carry(i);
    };
    float lr[2], li[2], pr[2], pi[2], wr[2], wi[2], vr[2], vi[2], qr[2], qi[2], er[2], ei[2], gr[2], gi[2];
    auto powers = [&](int i) {
      const uint2 cf = lds64(ca + 512 * i);
      pr[i] = lr[i] = __uint_as_float(cf.x); pi[i] = li[i] = __uint_as_float(cf.y);
#pragma unroll
      for (int s = 0; s < 4; s++) csq(pr[i], pi[i]);
      gr[i] = pr[i]; gi[i] = pi[i];
      csq(pr[i], pi[i]);
      qr[i] = pr[i]; qi[i] = pi[i];
      csq(qr[i], qi[i]);
      er[i] = qr[i]; ei[i] = qi[i];
      wr[i] = (c & 1) ? pr[i] : 1.f; wi[i] = (c & 1) ? pi[i] : 0.f;
      if (c & 2) { float x, y; cmul(wr[i], wi[i], qr[i], qi[i], x, y); wr[i] = x; wi[i] = y; }
      vr[i] = wr[i]; vi[i] = wi[i];
      csq(vr[i], vi[i]); csq(vr[i], vi[i]);
      csq(qr[i], qi[i]); csq(qr[i], qi[i]); csq(qr[i], qi[i]);
      const int src = 4 * (lane & 7) + ct;
      vr[i] = __shfl_sync(0xffffffffu, vr[i], src); vi[i] = __shfl_sync(0xffffffffu, vi[i], src);
      qr[i] = __shfl_sync(0xffffffffu, qr[i], src); qi[i] = __shfl_sync(0xffffffffu, qi[i], src);
      asm volatile("" : "+f"(wr[i]), "+f"(wi[i]), "+f"(pr[i]), "+f"(pi[i]), "+f"(er[i]), "+f"(ei[i]));
    };
    powers(0);
    if (POW2 == 0) powers(1);
    PMFENCE();
    wg_wait<0>();
    fence_regs<128>(d);
    release(false);
    if (t == 0) STAMP(10 + 10 * wg);
#pragma unroll
    for (int i = 0; i < 2; i++) {
      const float* e = d + 64 * i;
      auto chain = [&](int s0, int s1, float& sr, float& si) {
        sr = e[2 * s0 + RE]; si = e[2 * s0 + IM];
#pragma unroll
        for (int s = s0 + 1; s < s1; s++) {
          const int ia = 4 * (s >> 1) + (s & 1);
          const float nr = fmaf(-li[i], si, fmaf(lr[i], sr, e[ia + RE])), ni = fmaf(li[i], sr, fmaf(lr[i], si, e[ia + IM]));
          sr = nr; si = ni;
          if (i == 1 && C_AT > 1 && s == C_AT) { asm volatile("pmevent 0;" : "+f"(sr), "+f"(si)::"memory"); first_load(0); }
        }
      };
      float sr, si;
      if (POW2 == 1 && i == 1) powers(1);
      if ((GREEDY >> i) & 1) {
        float ar, ai;
        chain(0, 16, ar, ai); chain(16, 32, sr, si);
        sr = fmaf(gr[i], ar, fmaf(-gi[i], ai, sr)); si = fmaf(gr[i], ai, fmaf(gi[i], ar, si));
      } else chain(0, 32, sr, si);
      if (i == 1 && C_AT == 0) { asm volatile("pmevent 0;" : "+f"(sr), "+f"(si)::"memory"); first_load(0); }
      float ur = __shfl_up_sync(0xffffffffu, sr, 1, 4), ui = __shfl_up_sync(0xffffffffu, si, 1, 4);
      if (c >= 1) { sr = fmaf(pr[i], ur, fmaf(-pi[i], ui, sr)); si = fmaf(pr[i], ui, fmaf(pi[i], ur, si)); }
      ur = __shfl_up_sync(0xffffffffu, sr, 2, 4); ui = __shfl_up_sync(0xffffffffu, si, 2, 4);
      if (c >= 2) { sr = fmaf(er[i], ur, fmaf(-ei[i], ui, sr)); si = fmaf(er[i], ui, fmaf(ei[i], ur, si)); }
      if (c == 3 && tc < 15)
        asm volatile("{\n.reg .b64 v;\nmov.b64 v, {%1,%2};\nst.relaxed.gpu.global.b64 [%0], v;\n}\n" ::"l"(cp + 512 * i + g), "r"((__float_as_uint(sr) & ~3u) | tag), "r"(__float_as_uint(si)) : "memory");
      if (i == 1 && C_AT == 1) first_load(0);
      PMFENCE();
      if (t == 0) STAMP(11 + i + 10 * wg);
      er[i] = __shfl_up_sync(0xffffffffu, sr, 1, 4); ei[i] = __shfl_up_sync(0xffffffffu, si, 1, 4);
      if (c == 0) er[i] = ei[i] = 0.f;
    }
    uint4* hp = g_h + (32 * tc + 16 * wg + 2 * j) * 1024 + 64 * w + 4 * g + (c ^ (g >> 1));
#pragma unroll
    for (int i = 0; i < 2; i++) {
      float* e = d + 64 * i;
      const uint2 cf = lds64(ca + 512 * i + 8);
      const uint32_t gp = cf.x, gms = cf.y;
      PMFENCE();
      int n = 0;
#pragma unroll 1
      while (!__all_sync(0xffffffffu, (((cv[0].x ^ tag) | (cv[1].x ^ tag) | (cv[2].x ^ tag) | (cv[3].x ^ tag)) & 3) == 0) && ++n <= (SPIN_LIMIT << 4)) load_carry(i);
      if (t == 0 && i == 0) STAMP(13 + 10 * wg);
      float hr = __uint_as_float(cv[3].x), hi = __uint_as_float(cv[3].y);
#pragma unroll
      for (int m = 2; m >= 0; m--) {
        const float nr = fmaf(qr[i], hr, fmaf(-qi[i], hi, __uint_as_float(cv[m].x))), ni = fmaf(qr[i], hi, fmaf(qi[i], hr, __uint_as_float(cv[m].y)));
        hr = nr; hi = ni;
      }
      { float x, y; cmul(hr, hi, vr[i], vi[i], x, y); hr = x; hi = y; }
      hr += __shfl_xor_sync(0xffffffffu, hr, 8); hi += __shfl_xor_sync(0xffffffffu, hi, 8);
      hr = __shfl_sync(0xffffffffu, hr, g) + __shfl_sync(0xffffffffu, hr, g + 16); hi = __shfl_sync(0xffffffffu, hi, g) + __shfl_sync(0xffffffffu, hi, g + 16);
      float sr = fmaf(wr[i], hr, fmaf(-wi[i], hi, er[i])), si = fmaf(wr[i], hi, fmaf(wi[i], hr, ei[i]));
      if (t == 0 && i == 0) STAMP(14 + 10 * wg);
#pragma unroll
      for (int i8 = 0; i8 < 4; i8++) {
        asm volatile("pmevent 0;" : "+f"(sr), "+f"(si)::"memory");
        if (i == 0 && i8 == C_AT2) first_load(1);
#pragma unroll
        for (int s = 8 * i8; s < 8 * i8 + 8; s++) {
          const int ia = 4 * (s >> 1) + (s & 1);
          const float nr = fmaf(-li[i], si, fmaf(lr[i], sr, e[ia + RE])), ni = fmaf(li[i], sr, fmaf(lr[i], si, e[ia + IM]));
          sr = nr; si = ni;
          e[ia + RE] = nr; e[ia + IM] = ni;
        }
        if (P2_SPLIT) PMFENCE();
        uint32_t hp0[4], hp1[4];
#pragma unroll
        for (int m = 0; m < 4; m++) {
          const float* f = e + 16 * i8 + 4 * m;
          const uint32_t x = pack_bf16(f[RE], f[RE + 1]), y = pack_bf16(f[IM], f[IM + 1]);
          hp0[m] = bfma2(gp, x, bmul2(gms, y)); hp1[m] = bfnma2(gp, y, bmul2(gms, x));
        }
        uint4* o = hp + 512 * (i8 >> 1) + 256 * i + 32 * (i8 & 1);
        stg128(o, make_uint4(hp0[0], hp0[1], hp0[2], hp0[3]));
        stg128(o + 1024, make_uint4(hp1[0], hp1[1], hp1[2], hp1[3]));
      }
    }
    if (t == 0) STAMP(15 + 10 * wg);
    const int trow = 128 * tc + 64 * (w & 1) + 8 * (w >> 1) + g;
    const int dcol = 128 * j + 4 * c;
    asm volatile("bar.arrive %0, 160;" ::"r"(4 + wg) : "memory");
    if (wg == 0) {
      set_ra();
      uint2 xv[32];
      {
        const int gp = 2 * (g & 3) + (g >> 2);
        const uint32_t xa = sb + OFF_RING + (XPOS % STAGES) * STAGE_BYTES + (64 * (w & 1) + 8 * (w >> 1) + gp) * 128 + (c & 1) * 8;
        mbar_wait(bars + B_XI * 8, 0);
        mbar_wait(bars + (B_FULL + XPOS % STAGES) * 8, (XPOS / STAGES) & 1);
        if (t == 0) STAMP(18);
#pragma unroll
        for (int u = 0; u < 32; u++) {
          const int J = (u >> 1) & 7;
          asm volatile("ld.shared.v2.u32 {%0,%1}, [%2];" : "=r"(xv[u].x), "=r"(xv[u].y) : "r"(xa + (J >> 2) * 16384 + (u >> 4) * 2048 + (u & 1) * 4096 + (((2 * (J & 3) + (c >> 1)) ^ gp) << 4)) : "memory");
        }
        uint32_t dep = P.zero;
#pragma unroll
        for (int u = 0; u < 32; u++) dep &= xv[u].x;
        bar_sync(3 + dep, 128);
        release_at(8 * (XPOS % STAGES), false);
      }
#pragma unroll
      for (int J = 0; J < 8; J++) {
        const uint4 ds = lds128(sb + OFF_DS + 16 * c + 64 * J);
#pragma unroll
        for (int r = 0; r < 4; r++) {
          const int u = 16 * (r >> 1) + 2 * J + (r & 1);
          float* e = d + 8 * (u >> 1) + 2 * (u & 1);
          e[0] = __uint_as_float(bfma2(blo2(xv[u].x), ds.x, 0)); e[1] = __uint_as_float(bfma2(xv[u].x, ds.y, 0));
          e[4] = __uint_as_float(bfma2(blo2(xv[u].y), ds.z, 0)); e[5] = __uint_as_float(bfma2(xv[u].y, ds.w, 0));
        }
      }
      fence_regs<128>(d);
      if (t == 0) STAMP(17);
      so = 8 * (33 % STAGES); ph = (33 / STAGES) & 1;
      const uint64_t da0 = make_desc(sb + OFF_RING + 16384, 512, 1024, 2), db0 = make_desc(sb + OFF_RING, 16, 1024, 1);
      bar_sync(2, 256);
#pragma unroll 1
      for (int kb = 0; kb < QSW; kb++) block(std::integral_constant<int, 1>(), da0, db0, kb == 0, false, 32 + kb);
#pragma unroll 1
      for (int kb = QSW; kb < 32 - TAILB; kb++) block(std::integral_constant<int, 2>(), da0, db0, false, false, 32 + kb);
      float* op = P.out + (size_t)trow * 2048 + 1024 + dcol;
      auto mma = [&](int i, int kb, int k0, int k1) {
        const int s = (33 + kb) % STAGES;
        wg_fence();
#pragma unroll
        for (int k = k0; k < k1; k++) wgmma_n128<1>(d + 64 * i, da0 + s * 2048 + 512 * i + 128 * k, db0 + (i ? 0 : P.zero) + s * 2048 + 2 * k, 1);
        wg_commit();
      };
      auto store = [&](int i, int J0, int J1) {
#pragma unroll
        for (int J = J0; J < J1; J++) {
#pragma unroll
          for (int h = 0; h < 2; h++) {
            const float* e = d + 64 * i + 8 * J + 2 * h;
            stg128(op + (size_t)(16 * i + 32 * h) * 2048 + 16 * J, make_uint4(__float_as_uint(e[0]), __float_as_uint(e[1]), __float_as_uint(e[4]), __float_as_uint(e[5])));
          }
        }
        PMFENCE();
      };
      constexpr int K0 = 32 - TAILB;
#pragma unroll
      for (int kb = K0; kb < 32; kb++) {
        mbar_wait(bars + (B_FULL + (33 + kb) % STAGES) * 8, ((33 + kb) / STAGES) & 1);
        if (TAILB == 5 && kb == K0) { mma(0, kb, 0, 2); wg_wait<1>(); release(false); mma(0, kb, 2, 4); }
        else mma(0, kb, 0, 4);
      }
      mma(1, K0, 0, 4);
      wg_wait<1>();
      fence_regs<64>(d);
      if (t == 0) STAMP(48);
#pragma unroll
      for (int kb = K0 + 1; kb < 32; kb++) {
        mma(1, kb, 0, 4);
        if (T_FENCE) PMFENCE();
        store(0, T_ST * (kb - K0 - 1), kb == 31 ? 8 : T_ST * (kb - K0));
      }
      if (t == 0) STAMP(49);
      wg_wait<0>();
      fence_regs<64>(d + 64);
      if (t == 0) STAMP(50);
      store(1, 0, 8);
      if (t == 0) { STAMP(51); GSTAMP(51); }
      if (t == 0) g_epoch[b * 32] = lds32(bars + B_EPOCH * 8);
      return;
    }
    asm volatile("setmaxnreg.dec.sync.aligned.u32 %0;" ::"n"(488 - 2 * GREG));
  }
  {
    int lane;
    asm volatile("mov.u32 %0, %%laneid;" : "=r"(lane));
    const int w = warp & 3, h = wg & 1;
    const int lc = 2 * (lane & 2) + (lane & 1) + ((lane >> 2) & 2);
    const bool own = ((lane >> 2) & 1) == rank, spare = !own && lc < 2;
    const uint32_t ya = (spare ? sb + OFF_IN + 96 + lc * 2064 : sb + OFF_U + (own ? 4 * rank * U_N8 : 4 * (rank ^ 1) * U_N8 - 2 * U_CH) + lc * U_CH) + w * 128 + (lane >> 4) * 16 + h * 64;
    const uint32_t ys = spare ? 512 : U_N8;
    const uint32_t ob0 = sb + (h ? OFF_F1 : OFF_K) + 1024 * w, ob1 = sb + (h ? OFF_VP : OFF_K + 4096) + 1024 * w;
    uint32_t y[2][8];
    uint2 q[4][4];
    auto get_q = [&](int n, int off, int bar, int ph) {
#pragma unroll
      for (int u = 0; u < 2; u++) {
        mbar_wait(bars + (bar + u) * 8, ph);
#pragma unroll
        for (int r = 0; r < 4; r++) q[n + u][r] = lds64(sb + off + 4096 * u + 1024 * w + 256 * r + 8 * lane);
      }
    };
    auto get_y = [&](int n) { ldsm4t(y[n & 1], ya + n * ys); ldsm4t(y[n & 1] + 4, ya + n * ys + 32); };
    if (h) {
#pragma unroll
      for (int n = 0; n < 4; n += 2) {
        get_q(n, OFF_Q, B_QF, n >> 1);
        uint32_t dep = P.zero;
#pragma unroll
        for (int r = 0; r < 8; r++) dep &= q[n + (r >> 2)][r & 3].x;
        bar_sync(6 + dep, 128);
        if (Q_HOLD && n == 0) mbar_wait(bars + B_HP * 8, 1);
        if (w < 2 && elect_one()) load_q(5 + 2 * w - (n >> 1), OFF_Q, B_QF + n);
        __syncwarp();
      }
#pragma unroll 1
      for (int r = 0; r < 6; r++) mbar_wait(bars + (B_IN + r) * 8, 0);
      if (warp == 4 && lane == 0) STAMP(52);
      bar_sync(9, 256);
    } else get_q(0, OFF_K, B_KF, 0);
    if (O_WAIT) mbar_wait(bars + (O_WAIT == 1 ? B_HP : B_HR) * 8, 1);
    if (warp == 8 && lane == 0) STAMP(53);
    mbar_wait(bars + (B_IN + 6) * 8, 0);
    if (warp == 8 && lane == 0) STAMP(63);
    get_y(0);
    uint32_t oc = clk32() + (2 * w + h) * (O_PACE / 2);
    if (warp == 8 && lane == 0) STAMP(30);
#pragma unroll
    for (int n = 0; n < 4; n++) {
      uint32_t* o = y[n & 1];
#pragma unroll
      for (int r = 0; r < 4; r++) { o[2 * r] = bmul2(o[2 * r], q[n][r].x); o[2 * r + 1] = bmul2(o[2 * r + 1], q[n][r].y); }
#pragma unroll
      for (int u = 0; u < 2; u++) {
        const uint32_t ob = u ? ob1 : ob0;
        if (n > 0 && lane == 0) asm volatile("cp.async.bulk.wait_group.read 1;" ::: "memory");
        __syncwarp();
#pragma unroll
        for (int r = 2 * u; r < 2 * u + 2; r++)
          sts128(ob + (r & 1) * 512 + lane * 16, make_uint4(o[2 * r] << 16, o[2 * r] & 0xffff0000u, o[2 * r + 1] << 16, o[2 * r + 1] & 0xffff0000u));
        if (O_PACE) { while ((int)(clk32() - oc) < 0) { if (O_SLEEP) __nanosleep(O_SLEEP); } }
        oc += 4 * O_PACE;
        fence_proxy_async_smem();
        __syncwarp();
        if (lane == 0)
          asm volatile("cp.async.bulk.tensor.3d.global.shared::cta.bulk_group [%0, {%2, %3, %4}], [%1];\ncp.async.bulk.commit_group;"
                       ::"l"(&mO), "r"(ob), "r"(32 * slot), "r"(32 * rank + 8 * w), "r"(8 * n + 4 * h + 2 * u) : "memory");
        __syncwarp();
        if (u == 0 && n < 3) get_y(n + 1);
        if (u == 0 && n == 1 && !h) get_q(2, OFF_Q, B_QF + 2, 0);
      }
    }
    if (warp == 8 && lane == 0) mbar_arrive_cta(bars + B_ACK * 8, rank ^ 1);
    if (lane == 0) asm volatile("cp.async.bulk.wait_group 0;" ::: "memory");
    if (warp == 8 && lane == 0) STAMP(31);
    mbar_wait(bars + B_ACK * 8, 0);
  }
}

typedef CUresult (*EncodeFn)(CUtensorMap*, CUtensorMapDataType, cuuint32_t, void*, const cuuint64_t*, const cuuint64_t*, const cuuint32_t*,
                             const cuuint32_t*, CUtensorMapInterleave, CUtensorMapSwizzle, CUtensorMapL2promotion, CUtensorMapFloatOOBfill);

bool encode(EncodeFn fn, CUtensorMap* m, int rank, const void* base, const cuuint64_t* dims, const cuuint64_t* strides, const cuuint32_t* box, CUtensorMapSwizzle swz,
            CUtensorMapL2promotion promo = CU_TENSOR_MAP_L2_PROMOTION_L2_128B) {
  const cuuint32_t es[5] = {1, 1, 1, 1, 1};
  return fn(m, CU_TENSOR_MAP_DATA_TYPE_BFLOAT16, rank, const_cast<void*>(base), dims, strides, box, es, CU_TENSOR_MAP_INTERLEAVE_NONE, swz,
            promo, CU_TENSOR_MAP_FLOAT_OOB_FILL_NONE) == CUDA_SUCCESS;
}

}

extern "C" void kernel_launch(void* const* d_in, const int* in_sizes, int n_in, void* d_out, int out_size) {
  (void)in_sizes; (void)n_in; (void)out_size;
  typedef const __nv_bfloat16* In;
  const In q = (In)d_in[0], k = (In)d_in[1], v = (In)d_in[2], ssm_k = (In)d_in[4], x = (In)d_in[6], B_re = (In)d_in[9], B_im = (In)d_in[10], C_re = (In)d_in[11], C_im = (In)d_in[12];
  Params P = {};
  P.shift_k = (In)d_in[3]; P.ssm_D = (In)d_in[5]; P.lam_re = (In)d_in[7]; P.lam_im = (In)d_in[8]; P.log_dt = (In)d_in[13]; P.Dskip = (In)d_in[14];
  P.out = (float*)d_out;
  for (int cl = 0; cl < 64; cl++) P.slot[cl >> 2] |= (cl < 4 ? 4 + cl : cl < 36 ? 8 * ((cl - 4) & 7) + ((cl - 4) >> 3) : 8 * (1 + (cl - 36) % 7) + 4 + (cl - 36) / 7) << (8 * (cl & 3));
  const bool swapB = (uintptr_t)B_im < (uintptr_t)B_re;

  EncodeFn fn = nullptr;
  cudaDriverEntryPointQueryResult qr;
  cudaGetDriverEntryPoint("cuTensorMapEncodeTiled", (void**)&fn, cudaEnableDefault, &qr);
  if (!fn) return;

  CUtensorMap mX, mB, mCre, mCim, mXs, mK, mV, mQ, mS, mO;
  bool ok = true;
  {
    const cuuint64_t dims[4] = {1024, 2, 64, 16}, str[3] = {2048, 32 * 2048, 2 * 2048};
    const cuuint32_t box[4] = {64, 2, 4, 16};
    ok &= encode(fn, &mX, 4, x, dims, str, box, CU_TENSOR_MAP_SWIZZLE_128B, (CUtensorMapL2promotion)X_PROMO);
  }
  {
    const uintptr_t lo = swapB ? (uintptr_t)B_im : (uintptr_t)B_re, hi = swapB ? (uintptr_t)B_re : (uintptr_t)B_im;
    const cuuint64_t dims[4] = {1024, 8, 2, 128}, str[3] = {2048, (cuuint64_t)(hi - lo), 8 * 2048};
    const cuuint32_t box[4] = {64, 8, 2, 4};
    ok &= encode(fn, &mB, 4, (const void*)lo, dims, str, box, CU_TENSOR_MAP_SWIZZLE_128B, (CUtensorMapL2promotion)B_PROMO);
  }
  {
    const cuuint64_t dims[5] = {1024, 2, 4, 2, 64}, str[4] = {2048, 4 * 2048, 2 * 2048, 16 * 2048};
    const cuuint32_t box[5] = {64, 2, 4, 2, 4};
    ok &= encode(fn, &mCre, 5, C_re, dims, str, box, CU_TENSOR_MAP_SWIZZLE_128B, (CUtensorMapL2promotion)C_PROMO);
    ok &= encode(fn, &mCim, 5, C_im, dims, str, box, CU_TENSOR_MAP_SWIZZLE_128B, (CUtensorMapL2promotion)C_PROMO);
  }
  {
    const cuuint64_t dims[4] = {1024, 2, 4, 256}, str[3] = {4 * 2048, 2048, 8 * 2048};
    const cuuint32_t box[4] = {64, 2, 4, 16};
    ok &= encode(fn, &mXs, 4, x, dims, str, box, CU_TENSOR_MAP_SWIZZLE_128B);
  }
  {
    const cuuint64_t dims[3] = {1024, 64, 32}, str[2] = {32 * 2048, 2048};
    const cuuint32_t box[3] = {16, 32, 4};
    const cuuint64_t dimq[4] = {1024, 8, 32, 8}, strq[3] = {32 * 2048, 2048, 256 * 2048};
    const cuuint32_t boxq[4] = {16, 8, 4, 4};
    ok &= encode(fn, &mQ, 4, q, dimq, strq, boxq, CU_TENSOR_MAP_SWIZZLE_NONE, (CUtensorMapL2promotion)Q_PROMO);
    ok &= encode(fn, &mK, 3, k, dims, str, box, CU_TENSOR_MAP_SWIZZLE_32B, (CUtensorMapL2promotion)KV_PROMO);
    ok &= encode(fn, &mV, 3, v, dims, str, box, CU_TENSOR_MAP_SWIZZLE_32B, (CUtensorMapL2promotion)KV_PROMO);
  }
  {
    const cuuint64_t dims[2] = {32, 65536}, str[1] = {64};
    const cuuint32_t box[2] = {32, 64};
    ok &= encode(fn, &mS, 2, ssm_k, dims, str, box, CU_TENSOR_MAP_SWIZZLE_64B, (CUtensorMapL2promotion)S_PROMO);
  }
  {
    const cuuint64_t dims[3] = {2048, 64, 32}, str[2] = {32 * 8192, 8192};
    const cuuint32_t box[3] = {32, 8, 2};
    ok &= encode(fn, &mO, 3, d_out, dims, str, box, CU_TENSOR_MAP_SWIZZLE_NONE);
  }
  if (!ok) return;
  auto kern = swapB ? fused_kernel<1> : fused_kernel<0>;
  cudaFuncSetAttribute(kern, cudaFuncAttributeMaxDynamicSharedMemorySize, SMEM_BYTES);
  kern<<<NCTA, 512, SMEM_BYTES, cudaStreamPerThread>>>(P, mX, mB, mCre, mCim, mXs, mK, mV, mQ, mS, mO);
}
```

```cpp
#include <cuda_runtime.h>
#include <cuda_bf16.h>
#include <cuda.h>
#include <stdint.h>
#include <type_traits>

namespace {

constexpr int D_DIM = 1024;
constexpr int NCTA = 128;

constexpr int STAGES = 5, STAGE_BYTES = 32768;
constexpr int OFF_RING = 0;
constexpr int OFF_F1 = STAGES * STAGE_BYTES, OFF_F2 = OFF_F1 + 4096, OFF_K = OFF_F2 + 2048, OFF_VP = OFF_K + 8192, OFF_Q = OFF_VP + 4096, OFF_IN = OFF_Q + 8192;
constexpr int OFF_KV = OFF_K;
constexpr int U_CH = 528, U_N8 = 8 * U_CH, OFF_U = OFF_IN + U_N8;
constexpr int OFF_COEF = OFF_U + 8 * U_N8;
constexpr int OFF_DS = OFF_COEF + 2048, OFF_D = OFF_DS + 512;
constexpr int OFF_BAR = OFF_D + 64;
constexpr int SMEM_BYTES = OFF_BAR + 512;
static_assert(SMEM_BYTES <= 232448 && OFF_K % 1024 == 0 && (OFF_U + 3 * U_N8) % 512 == 0 && (4 * U_N8) % 512 == 0, "smem map");
constexpr int B_FULL = 0, B_XI = 5, B_HR = 6, B_HP = 7, B_KVF = 8, B_KF = 11, B_KE = 13, B_QF = 15, B_IN = 19, B_UF = 27, B_Y = 31, B_ACK = 36,
              B_EMPTY = 38, B_COEF = 43, B_KVE = 44, B_EPOCH = 48;
constexpr int QD1 = 8;
constexpr int QD2 = 2;
constexpr int QD3 = 8;
constexpr int QSW = 16;
constexpr int HEAD = 3;
constexpr int ST_T0 = 200;
constexpr int ST_DELAY = 300;
constexpr int XPOS = 28;
constexpr int K_T0 = 800;
constexpr int KV_T0 = 1500;
constexpr int KV_DT = 560;
constexpr int KV_DV = 100;
constexpr int O_PACE = 0;
constexpr int POLL_NS = 30;
constexpr int GREEDY = 1;
constexpr int P2_SPLIT = 0;
constexpr int TAILB = 5;
constexpr int GREG = 176;
constexpr int O_WAIT = 2;
constexpr int COEF_T0 = 2500;
constexpr int RELPOS = 0;
constexpr int C_AT = 1;
constexpr int C_AT2 = 1;
constexpr int T_FENCE = 0;
constexpr int T_ST = 2;
constexpr int X_PROMO = 2;
constexpr int B_PROMO = 2;
constexpr int C_PROMO = 2;
constexpr int KV_PROMO = 2;
constexpr int Q_PROMO = 2;
constexpr int S_PROMO = 2;
constexpr int POW2 = 0;
constexpr int O_SLEEP = 20;
constexpr int VO = 3;
constexpr int PFC = 3;
constexpr int PFC_T0 = 13500;
constexpr int PFC_T1 = 1500;
constexpr int PFC_DT = 400;
constexpr int PFQ = 4;
constexpr int Q_HOLD = 0;
constexpr int CFM = 0x40f1;
constexpr int SPIN_LIMIT = 1 << 14;

struct Params {
  unsigned slot[16];
  unsigned zero;
  const __nv_bfloat16 *shift_k, *ssm_D, *lam_re, *lam_im, *log_dt, *Dskip;
  float* out;
};

__device__ __align__(1024) uint4 g_h[16 * 32 * 1024];
__device__ __align__(128) uint2 g_carry[32 * 16 * 32];
__device__ unsigned g_flagH[2 * 16 * 32];
__device__ unsigned g_epoch[NCTA * 32];

__device__ __forceinline__ uint64_t make_desc(uint32_t addr, uint32_t lbo, uint32_t sbo, uint32_t swz) {
  return (uint64_t)((addr & 0x3FFFF) >> 4) | ((uint64_t)(lbo >> 4) << 16) | ((uint64_t)(sbo >> 4) << 32) | ((uint64_t)swz << 62);
}
__device__ __forceinline__ void wg_fence() { asm volatile("wgmma.fence.sync.aligned;" ::: "memory"); }
__device__ __forceinline__ void wg_commit() { asm volatile("wgmma.commit_group.sync.aligned;" ::: "memory"); }
template <int N> __device__ __forceinline__ void wg_wait() { asm volatile("wgmma.wait_group.sync.aligned %0;" ::"n"(N) : "memory"); }
__device__ __forceinline__ void mbar_init(uint32_t bar, int cnt) { asm volatile("mbarrier.init.shared::cta.b64 [%0], %1;" ::"r"(bar), "r"(cnt) : "memory"); }
__device__ __forceinline__ void mbar_expect(uint32_t bar, uint32_t bytes) { asm volatile("mbarrier.arrive.expect_tx.shared::cta.b64 _, [%0], %1;" ::"r"(bar), "r"(bytes) : "memory"); }
__device__ __forceinline__ void mbar_wait(uint32_t bar, uint32_t parity) {
  uint32_t ok; int n = 0;
  do {
    asm volatile("{\n.reg .pred p;\nmbarrier.try_wait.parity.shared::cta.b64 p, [%1], %2;\nselp.u32 %0, 1, 0, p;\n}\n" : "=r"(ok) : "r"(bar), "r"(parity) : "memory");
    if (++n > SPIN_LIMIT) break;
  } while (!ok);
}
__device__ __forceinline__ void mbar_arrive(uint32_t bar) { asm volatile("mbarrier.arrive.shared::cta.b64 _, [%0];" ::"r"(bar) : "memory"); }
__device__ __forceinline__ void mbar_arrive_cta(uint32_t bar, uint32_t cta) {
  asm volatile("{\n.reg .b32 ra;\nmapa.shared::cluster.u32 ra, %0, %1;\nmbarrier.arrive.shared::cluster.b64 _, [ra];\n}\n" ::"r"(bar), "r"(cta) : "memory");
}
__device__ __forceinline__ bool elect_one() {
  uint32_t p;
  asm volatile("{\n.reg .pred P;\nelect.sync _|P, 0xffffffff;\nselp.u32 %0, 1, 0, P;\n}\n" : "=r"(p));
  return p != 0;
}
__device__ __forceinline__ void bar_sync(int id, int n) { asm volatile("bar.sync %0, %1;" ::"r"(id), "r"(n) : "memory"); }
#define TMA_LD(dim) "cp.async.bulk.tensor." dim ".shared::cluster.global.mbarrier::complete_tx::bytes"
__device__ __forceinline__ void tma2d(uint32_t dst, const CUtensorMap* m, int c0, int c1, uint32_t bar) {
  asm volatile(TMA_LD("2d") " [%0], [%1, {%3, %4}], [%2];" ::"r"(dst), "l"(m), "r"(bar), "r"(c0), "r"(c1) : "memory");
}
__device__ __forceinline__ void tma3d(uint32_t dst, const CUtensorMap* m, int c0, int c1, int c2, uint32_t bar) {
  asm volatile(TMA_LD("3d") " [%0], [%1, {%3, %4, %5}], [%2];" ::"r"(dst), "l"(m), "r"(bar), "r"(c0), "r"(c1), "r"(c2) : "memory");
}
__device__ __forceinline__ void tma4d(uint32_t dst, const CUtensorMap* m, int c0, int c1, int c2, int c3, uint32_t bar) {
  asm volatile(TMA_LD("4d") " [%0], [%1, {%3, %4, %5, %6}], [%2];" ::"r"(dst), "l"(m), "r"(bar), "r"(c0), "r"(c1), "r"(c2), "r"(c3) : "memory");
}
__device__ __forceinline__ void tma4d_mc(uint32_t dst, const CUtensorMap* m, int c0, int c1, int c2, int c3, uint32_t bar) {
  asm volatile(TMA_LD("4d") ".multicast::cluster [%0], [%1, {%3, %4, %5, %6}], [%2], %7;" ::"r"(dst), "l"(m), "r"(bar), "r"(c0), "r"(c1), "r"(c2), "r"(c3), "h"((uint16_t)3) : "memory");
}
__device__ __forceinline__ void tma5d_mc(uint32_t dst, const CUtensorMap* m, int c0, int c1, int c2, int c3, int c4, uint32_t bar) {
  asm volatile(TMA_LD("5d") ".multicast::cluster [%0], [%1, {%3, %4, %5, %6, %7}], [%2], %8;" ::"r"(dst), "l"(m), "r"(bar), "r"(c0), "r"(c1), "r"(c2), "r"(c3), "r"(c4), "h"((uint16_t)3) : "memory");
}
__device__ __forceinline__ void bulk_load(uint32_t dst, const void* src, uint32_t bytes, uint32_t bar) {
  asm volatile("cp.async.bulk.shared::cluster.global.mbarrier::complete_tx::bytes [%0], [%1], %2, [%3];" ::"r"(dst), "l"(src), "r"(bytes), "r"(bar) : "memory");
}
__device__ __forceinline__ void bulk_send(uint32_t dst, uint32_t src, uint32_t bytes, uint32_t bar, uint32_t cta) {
  asm volatile("{\n.reg .b32 rd, rb;\nmapa.shared::cluster.u32 rd, %0, %3;\nmapa.shared::cluster.u32 rb, %2, %3;\n"
               "cp.async.bulk.shared::cluster.shared::cta.mbarrier::complete_tx::bytes [rd], [%1], %4, [rb];\n}\n"
               ::"r"(dst), "r"(src), "r"(bar), "r"(cta), "r"(bytes) : "memory");
}
__device__ __forceinline__ void fence_proxy_async_smem() { asm volatile("fence.proxy.async.shared::cta;" ::: "memory"); }
__device__ __forceinline__ void fence_proxy_async_global() { asm volatile("fence.proxy.async.global;" ::: "memory"); }
__device__ __forceinline__ uint32_t clk32() { uint32_t c; asm volatile("mov.u32 %0, %%clock;" : "=r"(c)::"memory"); return c; }
__device__ __forceinline__ void wait_until(uint32_t t0, uint32_t dt) { while (clk32() - t0 < dt) __nanosleep(32); }
__device__ __forceinline__ void spin_until(uint32_t t0, uint32_t dt) { while (clk32() - t0 < dt) {} }
__device__ __forceinline__ void prefetch_map(const CUtensorMap* m) { asm volatile("prefetch.tensormap [%0];" ::"l"(m) : "memory"); }
__device__ __forceinline__ void prefetch_line(const void* p) { asm volatile("prefetch.global.L2 [%0];" ::"l"(p) : "memory"); }
__device__ __forceinline__ unsigned ld_acquire(const unsigned* p) { unsigned v; asm volatile("ld.acquire.gpu.global.u32 %0, [%1];" : "=r"(v) : "l"(p) : "memory"); return v; }
__device__ __forceinline__ unsigned ld_relaxed(const unsigned* p) { unsigned v; asm volatile("ld.relaxed.gpu.global.u32 %0, [%1];" : "=r"(v) : "l"(p) : "memory"); return v; }
__device__ __forceinline__ uint32_t lds32(uint32_t a) { uint32_t v; asm volatile("ld.shared.u32 %0, [%1];" : "=r"(v) : "r"(a)); return v; }
__device__ __forceinline__ uint2 lds64(uint32_t a) { uint2 v; asm volatile("ld.shared.v2.u32 {%0,%1}, [%2];" : "=r"(v.x), "=r"(v.y) : "r"(a) : "memory"); return v; }
__device__ __forceinline__ uint4 lds128(uint32_t a) { uint4 v; asm volatile("ld.shared.v4.u32 {%0,%1,%2,%3}, [%4];" : "=r"(v.x), "=r"(v.y), "=r"(v.z), "=r"(v.w) : "r"(a) : "memory"); return v; }
__device__ __forceinline__ void sts32(uint32_t a, uint32_t v) { asm volatile("st.shared.u32 [%0], %1;" ::"r"(a), "r"(v) : "memory"); }
__device__ __forceinline__ void sts128(uint32_t a, uint4 v) { asm volatile("st.shared.v4.u32 [%0], {%1,%2,%3,%4};" ::"r"(a), "r"(v.x), "r"(v.y), "r"(v.z), "r"(v.w) : "memory"); }
__device__ __forceinline__ void ldsm4(uint32_t* r, uint32_t a) { asm volatile("ldmatrix.sync.aligned.m8n8.x4.shared.b16 {%0,%1,%2,%3}, [%4];" : "=r"(r[0]), "=r"(r[1]), "=r"(r[2]), "=r"(r[3]) : "r"(a) : "memory"); }
__device__ __forceinline__ void ldsm4t(uint32_t* r, uint32_t a) { asm volatile("ldmatrix.sync.aligned.m8n8.x4.trans.shared.b16 {%0,%1,%2,%3}, [%4];" : "=r"(r[0]), "=r"(r[1]), "=r"(r[2]), "=r"(r[3]) : "r"(a) : "memory"); }
__device__ __forceinline__ void stsm4t(uint32_t a, uint32_t r0, uint32_t r1, uint32_t r2, uint32_t r3) {
  asm volatile("stmatrix.sync.aligned.m8n8.x4.trans.shared.b16 [%0], {%1,%2,%3,%4};" ::"r"(a), "r"(r0), "r"(r1), "r"(r2), "r"(r3) : "memory");
}
__device__ __forceinline__ uint4 ldg128_nc(const void* p) { uint4 v; asm volatile("ld.global.nc.L1::no_allocate.v4.u32 {%0,%1,%2,%3}, [%4];" : "=r"(v.x), "=r"(v.y), "=r"(v.z), "=r"(v.w) : "l"(p)); return v; }
__device__ __forceinline__ void stg128(void* p, uint4 v) { asm volatile("st.global.L1::no_allocate.v4.u32 [%0], {%1,%2,%3,%4};" ::"l"(p), "r"(v.x), "r"(v.y), "r"(v.z), "r"(v.w) : "memory"); }
__device__ __forceinline__ uint32_t pack_bf16(float lo, float hi) { uint32_t r; asm("cvt.rn.bf16x2.f32 %0, %1, %2;" : "=r"(r) : "f"(hi), "f"(lo)); return r; }
__device__ __forceinline__ uint32_t bmul2(uint32_t a, uint32_t b) { uint32_t r; asm("mul.rn.bf16x2 %0, %1, %2;" : "=r"(r) : "r"(a), "r"(b)); return r; }
__device__ __forceinline__ uint32_t bfma2(uint32_t a, uint32_t b, uint32_t c) { uint32_t r; asm("fma.rn.bf16x2 %0, %1, %2, %3;" : "=r"(r) : "r"(a), "r"(b), "r"(c)); return r; }
__device__ __forceinline__ uint32_t blo2(uint32_t a) { uint32_t r; asm("{\n.reg .b16 l, h;\nmov.b32 {l, h}, %1;\nmov.b32 %0, {l, l};\n}" : "=r"(r) : "r"(a)); return r; }
__device__ __forceinline__ float bf2f(__nv_bfloat16 v) { return __bfloat162float(v); }

#define R8(d, o) "+f"(d[o]), "+f"(d[o + 1]), "+f"(d[o + 2]), "+f"(d[o + 3]), "+f"(d[o + 4]), "+f"(d[o + 5]), "+f"(d[o + 6]), "+f"(d[o + 7])
#define R16(d, o) R8(d, o), R8(d, o + 8)
#define R64(d, o) R16(d, o), R16(d, o + 16), R16(d, o + 32), R16(d, o + 48)
template <int TA> __device__ __forceinline__ void wgmma_n128(float* d, uint64_t da, uint64_t db, int scale_d) {
  asm volatile("{\n.reg .pred p;\nsetp.ne.b32 p, %66, 0;\n"
    "wgmma.mma_async.sync.aligned.m64n128k16.f32.bf16.bf16 {"
    "%0,%1,%2,%3,%4,%5,%6,%7,%8,%9,%10,%11,%12,%13,%14,%15,%16,%17,%18,%19,%20,%21,%22,%23,%24,%25,%26,%27,%28,%29,%30,%31,"
    "%32,%33,%34,%35,%36,%37,%38,%39,%40,%41,%42,%43,%44,%45,%46,%47,%48,%49,%50,%51,%52,%53,%54,%55,%56,%57,%58,%59,%60,%61,%62,%63"
    "}, %64, %65, p, 1, 1, %67, 0;\n}\n"
    : R64(d, 0)
    : "l"(da), "l"(db), "r"(scale_d), "n"(TA));
}
template <int N> __device__ __forceinline__ void fence_regs(float* d) {
#pragma unroll
  for (int i = 0; i < N; i++) asm volatile("" : "+f"(d[i])::"memory");
}
#define PMFENCE() asm volatile("pmevent 0;" ::: "memory")
__device__ __forceinline__ void cmul(float ar, float ai, float br, float bi, float& cr, float& ci) {
  cr = ar * br - ai * bi; ci = ar * bi + ai * br;
}
__device__ __forceinline__ void csq(float& r, float& i) { const float x = fmaf(r, r, -i * i), y = (r + r) * i; r = x; i = y; }

#define W8(d, o) "=f"(d[o]), "=f"(d[o + 1]), "=f"(d[o + 2]), "=f"(d[o + 3]), "=f"(d[o + 4]), "=f"(d[o + 5]), "=f"(d[o + 6]), "=f"(d[o + 7])
#define L16 "{%0,%1,%2,%3,%4,%5,%6,%7,%8,%9,%10,%11,%12,%13,%14,%15}"
#define L32 "{%0,%1,%2,%3,%4,%5,%6,%7,%8,%9,%10,%11,%12,%13,%14,%15,%16,%17,%18,%19,%20,%21,%22,%23,%24,%25,%26,%27,%28,%29,%30,%31}"
template <int ACC, int TB> __device__ __forceinline__ void rs_n32(float* d, const uint32_t* a, uint64_t db) {
  if constexpr (ACC) asm volatile("wgmma.mma_async.sync.aligned.m64n32k16.f32.bf16.bf16 " L16 ", {%16,%17,%18,%19}, %20, 1, 1, 1, %21;" : R16(d, 0) : "r"(a[0]), "r"(a[1]), "r"(a[2]), "r"(a[3]), "l"(db), "n"(TB));
  else asm volatile("wgmma.mma_async.sync.aligned.m64n32k16.f32.bf16.bf16 " L16 ", {%16,%17,%18,%19}, %20, 0, 1, 1, %21;" : W8(d, 0), W8(d, 8) : "r"(a[0]), "r"(a[1]), "r"(a[2]), "r"(a[3]), "l"(db), "n"(TB));
}
template <int ACC, int TB> __device__ __forceinline__ void ss_n64(float* d, uint64_t da, uint64_t db) {
  if constexpr (ACC) asm volatile("wgmma.mma_async.sync.aligned.m64n64k16.f32.bf16.bf16 " L32 ", %32, %33, 1, 1, 1, 0, %34;" : R16(d, 0), R16(d, 16) : "l"(da), "l"(db), "n"(TB));
  else asm volatile("wgmma.mma_async.sync.aligned.m64n64k16.f32.bf16.bf16 " L32 ", %32, %33, 0, 1, 1, 0, %34;" : W8(d, 0), W8(d, 8), W8(d, 16), W8(d, 24) : "l"(da), "l"(db), "n"(TB));
}
template <int ACC> __device__ __forceinline__ void ss_n32_tt(float* d, uint64_t da, uint64_t db) {
  if constexpr (ACC) asm volatile("wgmma.mma_async.sync.aligned.m64n32k16.f32.bf16.bf16 " L16 ", %16, %17, 1, 1, 1, 1, 1;" : R16(d, 0) : "l"(da), "l"(db));
  else asm volatile("wgmma.mma_async.sync.aligned.m64n32k16.f32.bf16.bf16 " L16 ", %16, %17, 0, 1, 1, 1, 1;" : W8(d, 0), W8(d, 8) : "l"(da), "l"(db));
}
__device__ __forceinline__ void stsm4(uint32_t a, uint32_t r0, uint32_t r1, uint32_t r2, uint32_t r3) {
  asm volatile("stmatrix.sync.aligned.m8n8.x4.shared.b16 [%0], {%1,%2,%3,%4};" ::"r"(a), "r"(r0), "r"(r1), "r"(r2), "r"(r3) : "memory");
}
template <int N> __device__ __forceinline__ void fence_u32(uint32_t* d) {
#pragma unroll
  for (int i = 0; i < N; i++) asm volatile("" : "+r"(d[i])::"memory");
}
__device__ __forceinline__ void pack32(uint32_t* f, const float* z) {
#pragma unroll
  for (int i = 0; i < 16; i++) f[i] = pack_bf16(z[2 * i], z[2 * i + 1]);
}
template <int INV> __device__ __forceinline__ void twiddle(uint32_t* f, const uint32_t* tp, const uint32_t* ts) {
#pragma unroll
  for (int i = 0; i < 8; i++) {
    uint32_t x = f[2 * i + INV], y = f[2 * i + 1 - INV];
    x = bfma2(tp[i & 3], y, x); y = bfma2(ts[i & 3], x, y); x = bfma2(tp[i & 3], y, x);
    f[2 * i + INV] = x; f[2 * i + 1 - INV] = y;
  }
}
__device__ __forceinline__ uint32_t bfnma2(uint32_t a, uint32_t b, uint32_t c) { uint32_t r; asm("{\n.reg .b32 t;\nmul.bf16x2 t, %1, %2;\nsub.bf16x2 %0, %3, t;\n}" : "=r"(r) : "r"(a), "r"(b), "r"(c)); return r; }
__device__ __forceinline__ uint32_t bfms2(uint32_t a, uint32_t b, uint32_t c) { uint32_t r; asm("{\n.reg .b32 t;\nmul.bf16x2 t, %1, %2;\nsub.bf16x2 %0, t, %3;\n}" : "=r"(r) : "r"(a), "r"(b), "r"(c)); return r; }
template <int ADD> __device__ __forceinline__ void bimac(uint32_t* o, const uint32_t* a, const uint32_t* b, const uint32_t* c) {
#pragma unroll
  for (int J = 0; J < 2; J++) {
    const uint32_t Pr = a[2 * J], Pi = a[2 * J + 1], Qr = a[2 * J + 4], Qi = a[2 * J + 5], pr = b[2 * J], pi = b[2 * J + 1], qr = b[2 * J + 4], qi = b[2 * J + 5];
    uint32_t x0, x1, x2, x3;
    if (ADD == 0) { x0 = bmul2(Pr, pr); x1 = bmul2(Pr, pi); x2 = bmul2(Pr, qr); x3 = bmul2(Pr, qi); }
    if (ADD == 1) { x0 = bfma2(Pr, pr, c[2 * J]); x1 = bfma2(Pr, pi, c[2 * J + 1]); x2 = bfma2(Pr, qr, c[2 * J + 4]); x3 = bfma2(Pr, qi, c[2 * J + 5]); }
    if (ADD == 2) { x0 = bfma2(Pr, pr, c[2 * J + 1]); x1 = bfms2(Pr, pi, c[2 * J]); x2 = bfma2(Pr, qr, c[2 * J + 5]); x3 = bfms2(Pr, qi, c[2 * J + 4]); }
    x0 = bfnma2(Pi, pi, x0); x1 = bfma2(Pi, pr, x1); x2 = bfnma2(Pi, qi, x2); x3 = bfma2(Pi, qr, x3);
    x0 = bfnma2(Qr, qr, x0); x1 = bfnma2(Qr, qi, x1); x2 = bfma2(Qr, pr, x2); x3 = bfma2(Qr, pi, x3);
    x0 = bfma2(Qi, qi, x0); x1 = bfnma2(Qi, qr, x1); x2 = bfnma2(Qi, pi, x2); x3 = bfma2(Qi, pr, x3);
    o[2 * J] = x0; o[2 * J + 1] = x1; o[2 * J + 4] = x2; o[2 * J + 5] = x3;
  }
}
__device__ __forceinline__ void sincos8k(int n, float& s, float& c) {
  const float x = (float)((n << 19) >> 19) * (6.283185307179586f / 8192.f);
  s = __sinf(x); c = __cosf(x);
}
__device__ __forceinline__ void fft_tables(uint32_t f1a, uint32_t f2a, int w, int lane, uint32_t* tp, uint32_t* ts, float& d0r, float& d0i) {
  const int c = lane & 3, f1 = 8 * w + (lane >> 2);
#pragma unroll 1
  for (int J = 3; J >= 0; J--) {
    const int a = 8 * J + 2 * c;
    float s0, c0, s1, c1;
    sincos8k(64 * (4 * f1 + 1) * a + 31 * (4 * f1 - 63), d0i, d0r); sincos8k(64 * (4 * f1 + 1) * (a + 1) + 31 * (4 * f1 - 63), s1, c1);
    d0r *= 0.125f; d0i *= 0.125f;
    sts32(f1a + w * 1024 + J * 128 + lane * 4, pack_bf16(d0r, 0.125f * c1)); sts32(f1a + w * 1024 + 512 + J * 128 + lane * 4, pack_bf16(d0i, 0.125f * s1));
    sincos8k(128 * (2 * (a & 15) + 1) * f1 - 128 * (a & 16), s0, c0); sincos8k(128 * (2 * (a & 15) + 3) * f1 - 128 * (a & 16), s1, c1);
    sts32(f2a + w * 512 + J * 128 + lane * 4, pack_bf16(c0, c1));
    sincos8k((4 * f1 - 63) * (2 * a - 31), s0, c0); sincos8k((4 * f1 - 63) * (2 * a - 29), s1, c1);
#pragma unroll
    for (int i = 3; i > 0; i--) { ts[i] = ts[i - 1]; tp[i] = tp[i - 1]; }
    ts[0] = pack_bf16(s0, s1); tp[0] = pack_bf16(-__fdividef(s0, 1.f + c0), -__fdividef(s1, 1.f + c1));
  }
  if (c != 0) d0r = d0i = 0.f;
}

template <int SWAPB>
__global__ void __cluster_dims__(2, 1, 1) __launch_bounds__(512, 1)
fused_kernel(const __grid_constant__ Params P, const __grid_constant__ CUtensorMap mX, const __grid_constant__ CUtensorMap mB,
             const __grid_constant__ CUtensorMap mCre, const __grid_constant__ CUtensorMap mCim, const __grid_constant__ CUtensorMap mXs,
             const __grid_constant__ CUtensorMap mK, const __grid_constant__ CUtensorMap mV, const __grid_constant__ CUtensorMap mQ, const __grid_constant__ CUtensorMap mS,
             const __grid_constant__ CUtensorMap mO) {
  extern __shared__ __align__(1024) uint8_t smem_raw[];
  const uint32_t sb = (uint32_t)__cvta_generic_to_shared(smem_raw);
  const uint32_t bars = sb + OFF_BAR;
  const int slot = (P.slot[blockIdx.x >> 3] >> (4 * (blockIdx.x & 6))) & 63, rank = blockIdx.x & 1;
  const int j = slot & 7, tc = 2 * (slot >> 3) + rank, b = 2 * slot + rank;
  const int tid = threadIdx.x;
  const int warp = __shfl_sync(0xffffffffu, tid >> 5, 0);
  const int wg = warp >> 2;
  const uint32_t c_start = clk32();
  auto kblock = [&](int n) { return ((n & 14) == 0 || (n & 14) == 2 * j ? n ^ (2 * j) : n) & 31; };
  auto send_y = [&](int r) {
    const uint32_t src = sb + OFF_U + 4 * (rank ^ 1) * U_N8 + r * U_CH, dst = r >= 2 ? sb + OFF_U + 4 * rank * U_N8 + (r - 2) * U_CH : sb + OFF_IN + 96 + r * 2064;
#pragma unroll 1
    for (int n = 0; n < 4; n++) bulk_send(dst + n * (r >= 2 ? U_N8 : 512), src + n * U_N8, 512, bars + (B_IN + r) * 8, rank ^ 1);
  };
  auto load_q = [&](int i, int off, int bar) {
    const uint32_t fb = bars + bar * 8 + 4 * (i & 2);
    mbar_expect(fb, 4096); tma4d(sb + off + 2048 * (i & 2), &mQ, 16 * slot, 0, 4 * i, 4 * rank, fb);
  };
  auto head = [&](int n) {
    const uint32_t fb = bars + (B_FULL + n) * 8, dst = sb + OFF_RING + n * STAGE_BYTES;
    mbar_expect(fb, STAGE_BYTES);
    tma4d(dst + 16384, &mX, 64 * n, 0, 4 * tc, 0, fb);
    tma4d(dst, &mB, 64 * n, 0, 0, 8 * j, fb);
    tma4d(dst + 8192, &mB, 64 * n, 0, 0, 8 * j + 4, fb);
  };
  if (warp == 0 && elect_one()) {
#pragma unroll
    for (int s = 0; s < STAGES; s++) mbar_init(bars + (B_FULL + s) * 8, 1);
    head(0);
    asm volatile("fence.mbarrier_init.release.cluster;" ::: "memory");
  }
  if (wg == 3 && elect_one()) {
    if (warp < 15) {
#pragma unroll
      for (int s = 0; s < 11; s++) mbar_init(bars + 8 * B_XI + (warp & 3) * 88 + 8 * s, 1);
    } else {
#pragma unroll
      for (int s = B_EMPTY; s < B_KVE + 3; s++) mbar_init(bars + 8 * s, s < B_COEF ? 2 : s == B_COEF ? 128 : 4);
    }
    asm volatile("fence.mbarrier_init.release.cluster;" ::: "memory");
  }
  __syncwarp();
  asm volatile("barrier.cluster.arrive.relaxed.aligned;" ::: "memory");
  if (warp == 0 && elect_one()) {
#pragma unroll 1
    for (int n = 1; n < HEAD; n++) { spin_until(c_start, ST_T0 + n * ST_DELAY); head(n); }
  }
  __syncwarp();
#define CLUSTER_WAIT() asm volatile("barrier.cluster.wait.aligned;" ::: "memory")

  if (wg == 3) {
    asm volatile("setmaxnreg.dec.sync.aligned.u32 24;");
    CLUSTER_WAIT();
    if (warp < 14) {
      if (elect_one()) {
        uint32_t so = 8 * (HEAD % STAGES), ph = HEAD < STAGES;
        auto step = [&](auto issue) {
          mbar_wait(bars + B_EMPTY * 8 + so, ph);
          issue(sb + OFF_RING + (so << 12), bars + B_FULL * 8 + so);
          so += 8;
          if (so == 8 * STAGES) { so = 0; ph ^= 1; }
        };
        if (warp == 12) {
          auto g1 = [&](int n0, int n1, int grp) {
#pragma unroll 1
            for (int n = n0; n < n1; n++) step([&](uint32_t dst, uint32_t fb) { mbar_expect(fb, STAGE_BYTES); tma4d_mc(dst + rank * 8192, &mB, n * 64, 0, 0, grp + 4 * rank, fb); });
          };
#pragma unroll 1
          for (int n = HEAD; n < STAGES; n++) { spin_until(c_start, ST_T0 + n * ST_DELAY); g1(n, n + 1, 8 * j); }
          g1(STAGES, 16, 8 * j);
          g1(0, XPOS - 16, 8 * j + 64);
          step([&](uint32_t dst, uint32_t fb) { mbar_expect(fb, STAGE_BYTES); tma4d(dst, &mXs, 128 * j, 0, 0, 16 * tc, fb); mbar_arrive(bars + B_XI * 8); });
          g1(XPOS - 16, 16, 8 * j + 64);
#pragma unroll 1
          for (int n = 0; n < 32; n += 2) {
            const int col = kblock(n) * 32;
#pragma unroll
            for (int part = 0; part < 2; part++)
              step([&](uint32_t dst, uint32_t fb) { mbar_expect(fb, STAGE_BYTES); tma5d_mc(dst + rank * 8192, part ? &mCim : &mCre, col, 0, 0, 0, 8 * j + 4 * rank, fb); });
          }
        } else {
          auto g1 = [&](int n0, int n1, int nb) {
#pragma unroll 1
            for (int n = n0; n < n1; n++) step([&](uint32_t dst, uint32_t fb) { tma4d(dst + 16384, &mX, n * 64, 0, 4 * tc, 0, fb); });
          };
          auto g2 = [&](int n0, int n1) {
#pragma unroll 1
            for (int n = n0; n < n1; n++) step([&](uint32_t dst, uint32_t fb) { bulk_load(dst + 16384, g_h + (32 * tc + kblock(n)) * 1024, 16384, fb); });
          };
#pragma unroll 1
          for (int n = HEAD; n < STAGES; n++) { spin_until(c_start, ST_T0 + n * ST_DELAY); g1(n, n + 1, 0); }
          g1(STAGES, 16, 0);
          g1(0, XPOS - 16, 16);
          step([&](uint32_t dst, uint32_t fb) { tma4d(dst + 16384, &mXs, 128 * j + 64, 0, 0, 16 * tc, fb); });
          g1(XPOS - 16, 16, 16);
#pragma unroll 1
          for (int v = 0; v < 2; v++) {
            mbar_wait(bars + B_HP * 8, v);
            fence_proxy_async_global();
            g2(16 * v, 16 * v + 2);
            mbar_wait(bars + B_HR * 8, v);
            fence_proxy_async_global();
            g2(16 * v + 2, 16 * v + 16);
          }
        }
      }
    } else if (warp == 15) {
      mbar_wait(bars + B_COEF * 8, 0);
      const unsigned epoch = lds32(bars + B_EPOCH * 8);
#pragma unroll 1
      for (int v = 0; v < 2; v++) {
        unsigned* fp = &g_flagH[(16 * v + tc) * 32];
        if (((PFC >> v) & 1) && elect_one()) {
          wait_until(v ? clk32() : c_start, (v ? PFC_T1 : PFC_T0) + (slot >> 3) * PFC_DT);
#pragma unroll
          for (int part = 0; part < 2; part++)
            asm volatile("cp.async.bulk.prefetch.tensor.5d.L2.global [%0, {%1, %2, %2, %2, %3}];" ::"l"(part ? &mCim : &mCre), "r"(512 * v + 8 * (slot & 56)), "r"(0), "r"(8 * j + 4 * rank) : "memory");
        }
        __syncwarp();
        bar_sync(4 + v, 160);
        if (elect_one()) {
          asm volatile("red.release.gpu.global.add.u32 [%0], 1;" ::"l"(fp) : "memory");
          mbar_arrive(bars + B_HP * 8);
          int it = 0;
          while (ld_acquire(fp) != 8 * epoch && ++it < (SPIN_LIMIT << 4)) __nanosleep(POLL_NS);
          mbar_arrive(bars + B_HR * 8);
        }
        __syncwarp();
      }
    } else if (elect_one()) {
      const int ch0 = 16 * slot;
      auto load_k = [&](int s, uint32_t dst) { const uint32_t fb = bars + (B_KF + (s & 1)) * 8; mbar_expect(fb, 4096); tma2d(dst, &mS, 0, 64 * (8 * b + s), fb); };
      prefetch_map(&mS); prefetch_map(&mK); prefetch_map(&mV);
      wait_until(c_start, K_T0);
      load_k(0, sb + OFF_U + (4 * rank + 3) * U_N8); load_k(1, sb + OFF_U + (4 * rank + 3) * U_N8 - 4096);
      {
        uint32_t so = 16, ph = 1;
#pragma unroll 1
        for (int e = 0; e < 9; e++) {
          const uint32_t fb = bars + B_KVF * 8 + so, dst = sb + OFF_KV + (so << 10);
          wait_until(c_start, KV_T0 + (e ? 2 * e - 1 : 0) * KV_DT);
          mbar_wait(bars + B_KVE * 8 + so, ph);
          const uint32_t c1 = clk32();
          mbar_expect(fb, e ? 8192 : 4096);
          tma3d(dst, &mK, ch0, 32 * rank - (e == 0), (4 * e - 4) & 31, fb);
          if (e > 0) { wait_until(c1, KV_DV); tma3d(dst + 4096, &mV, ch0, 32 * rank, 4 * e - 4, fb); }
          so += 8;
          if (so == 24) so = 0;
          if (so == 16) ph ^= 1;
        }
      }
      prefetch_map(&mCre); prefetch_map(&mCim); prefetch_map(&mXs); prefetch_map(&mQ); prefetch_map(&mO);
      mbar_wait(bars + B_KVE * 8, 0);
      load_k(2, sb + OFF_K); load_k(3, sb + OFF_K + 4096);
      mbar_wait(bars + (B_UF + 3) * 8, 0);
#pragma unroll 1
      for (int ch = 0; ch < 7; ch++) {
        if (ch > 0) {
          mbar_wait(bars + (B_Y + (ch & 3)) * 8, ch >> 2);
          if (ch > 2) mbar_wait(bars + (B_IN + ch - 3) * 8, 0);
          send_y(ch - 1);
        }
        if (ch < 6) {
          mbar_wait(bars + (B_KE + (ch & 1)) * 8, (ch >> 1) & 1);
          if (ch < 4) load_k(ch + 4, sb + OFF_K + (ch & 1) * 4096);
          if (PFQ && ch == PFQ - 1) asm volatile("cp.async.bulk.prefetch.tensor.4d.L2.global [%0, {%1, %2, %3, %4}];" ::"l"(&mQ), "r"(16 * (slot & ~3)), "r"(0), "r"(16 + 4 * (slot & 3)), "r"(4 * rank) : "memory");
          if (ch >= 2) load_q(2 * (ch & 1) + (ch < 4), ch < 4 ? OFF_Q : OFF_K, ch < 4 ? B_QF : B_KF);
        }
      }
    }
    return;
  } else if (wg == 2) {
    asm volatile("setmaxnreg.inc.sync.aligned.u32 %0;" ::"n"(488 - 2 * GREG));
    const int t = tid & 127, w = warp & 3, lane = t & 31, g = lane >> 2, c = lane & 3;
    const uint4 s2[2] = {ldg128_nc(P.shift_k + (8 * b + 2 * c) * 4), ldg128_nc(P.shift_k + (8 * (b ^ 1) + 2 * c) * 4)};
    const uint32_t dskip = __bfloat16_as_ushort(P.ssm_D[8 * b + (t & 7)]);
    uint32_t tp[4] = {}, ts[4] = {};
    float d0r, d0i;
    fft_tables(sb + OFF_F1, sb + OFF_F2, w, lane, tp, ts, d0r, d0i);
    CLUSTER_WAIT();
    if (t < 12) mbar_expect(bars + (B_IN + t) * 8, t < 6 ? 2048 : t < 8 ? 4 * (U_CH + 512) : U_N8);
    if (t < 8) sts32(sb + OFF_D + 4 * t, dskip << 16);
    const uint64_t dF1a = make_desc(sb + OFF_F1, 128, 512, 0), dF1b = make_desc(sb + OFF_F1, 512, 128, 0);
    const uint64_t dF2f = make_desc(sb + OFF_F2, 512, 128, 0), dF2i = make_desc(sb + OFF_F2, 128, 512, 0);
    auto T1k = [&](float* z, uint64_t dk) { wg_fence(); ss_n64<0, 1>(z, dF1a, dk); ss_n64<1, 1>(z, dF1a + 16, dk + 64); wg_commit(); };
    auto T1u = [&](float* z, uint64_t du) { wg_fence(); ss_n64<0, 0>(z, dF1a, du); ss_n64<1, 0>(z, dF1a + 16, du + 16); wg_commit(); };
    auto T2 = [&](float* s, const uint32_t* f) {
      wg_fence();
      rs_n32<0, 1>(s, f, dF2f); rs_n32<0, 1>(s + 16, f + 8, dF2f); rs_n32<1, 1>(s, f + 4, dF2f + 64); rs_n32<1, 1>(s + 16, f + 12, dF2f + 64);
      wg_commit();
    };
    auto product = [&](uint32_t* pr, const uint32_t* kh, const uint32_t* uh) {
      bimac<0>(pr, kh, uh, pr); bimac<2>(pr + 8, kh + 8, uh, pr); bimac<1>(pr + 8, kh, uh + 8, pr + 8);
      fence_u32<16>(pr);
    };
    float zk[32] = {};
    uint32_t pr[16];
    {
      uint32_t kh0[16];
      {
        float z0[32], sk[32];
        uint32_t fk[16];
        const uint64_t dk = make_desc(sb + OFF_U + (4 * rank + 3) * U_N8, 2048, 512, 2);
        fence_proxy_async_smem();
        bar_sync(7, 128);
        mbar_wait(bars + B_KF * 8, 0);
        T1k(z0, dk);
        mbar_wait(bars + (B_KF + 1) * 8, 0);
        T1k(zk, dk - 256);
        wg_wait<0>(); fence_regs<32>(z0); fence_regs<32>(zk);
        const float dd = __uint_as_float(lds32(sb + OFF_D));
        z0[0] = fmaf(d0r, dd, z0[0]); z0[2] = fmaf(d0i, dd, z0[2]);
        pack32(fk, z0); twiddle<0>(fk, tp, ts); fence_u32<16>(fk);
        T2(sk, fk);
        wg_wait<0>(); fence_regs<32>(sk); fence_u32<16>(fk);
        pack32(kh0, sk); fence_u32<16>(kh0);
      }
      {
        uint32_t sk[2][4], kx[2][8];
#pragma unroll
        for (int o = 0; o < 2; o++) {
          sk[o][0] = __byte_perm(s2[o].x, s2[o].z, 0x5410); sk[o][1] = __byte_perm(s2[o].x, s2[o].z, 0x7632);
          sk[o][2] = __byte_perm(s2[o].y, s2[o].w, 0x5410); sk[o][3] = __byte_perm(s2[o].y, s2[o].w, 0x7632);
        }
        const uint32_t la = sb + OFF_KV + (lane >> 3) * 1024 + (8 * w + (lane & 7)) * 32 + ((rank ^ ((lane >> 2) & 1)) << 4);
        const uint32_t uo = (lane & 7) * U_CH + w * 128 + (lane >> 3) * 16;
        mbar_wait(bars + (B_KVF + 2) * 8, 0);
        ldsm4(kx[0], la + 16384); ldsm4(kx[1], (la ^ 16) + 16384);
        if (lane == 0) mbar_arrive(bars + (B_KVE + 2) * 8 + (kx[0][1] & kx[1][1] & P.zero));
        uint32_t so = 0, ph = 0;
#pragma unroll 1
        for (int n = 0; n < 4; n++) {
          const uint32_t own = sb + OFF_U + (4 * rank + n) * U_N8, box = n < 3 ? sb + OFF_U + (4 * (rank ^ 1) + n + 1) * U_N8 : sb + OFF_IN;
#pragma unroll
          for (int e = 0; e < 2; e++) {
            uint32_t vx[2][4];
            mbar_wait(bars + B_KVF * 8 + so, ph);
#pragma unroll
            for (int o = 0; o < 2; o++) { ldsm4(kx[o] + 4, (la ^ (16 * o)) + (so << 10)); ldsm4(vx[o], (la ^ (16 * o)) + (so << 10) + 4096); }
            if (lane == 0) mbar_arrive(bars + B_KVE * 8 + so + (kx[0][4] & kx[1][4] & vx[0][0] & vx[1][0] & P.zero));
#pragma unroll
            for (int o = 0; o < 2; o++) {
#pragma unroll
              for (int i = 0; i < 4; i++) vx[o][i] = bmul2(bfma2(kx[o][i + 4], sk[o][0], bfma2(kx[o][i + 3], sk[o][1], bfma2(kx[o][i + 2], sk[o][2], bmul2(kx[o][i + 1], sk[o][3])))), vx[o][i]);
              stsm4t((o ? box : own) + uo + e * 64, vx[o][0], vx[o][1], vx[o][2], vx[o][3]);
              kx[o][1] = kx[o][5]; kx[o][2] = kx[o][6]; kx[o][3] = kx[o][7];
            }
            so += 8;
            if (so == 24) so = 0;
            if (so == 16) ph ^= 1;
          }
          fence_proxy_async_smem();
          bar_sync(7, 128);
          if (w == 0 && elect_one()) {
            if (n > 0) mbar_wait(bars + B_UF * 8 + 8 * (n - 1), 0);
            bulk_send(own, box, U_N8, bars + B_UF * 8 + 8 * n, rank ^ 1);
          }
          __syncwarp();
        }
      }
      float zu[32], su[32];
      uint32_t fu[16], uh[16];
#pragma unroll
      for (int n = 0; n < 4; n++) mbar_wait(bars + (B_UF + n) * 8, 0);
      T1u(zu, make_desc(sb + OFF_U, 128, U_N8, 0));
      wg_wait<0>(); fence_regs<32>(zu);
      pack32(fu, zu); twiddle<0>(fu, tp, ts); fence_u32<16>(fu);
      T2(su, fu);
      wg_wait<0>(); fence_regs<32>(su); fence_u32<16>(fu);
      pack32(uh, su);
      product(pr, kh0, uh);
    }
    {
#define CF(i) do { if ((CFM >> (i)) & 1) PMFENCE(); } while (0)
      const uint32_t vs = w < 2 ? 512 : U_N8;
      uint32_t va = (w < 2 ? sb + OFF_VP : sb + OFF_U) + ((lane >> 4) & 1) * vs + (w & 1) * 256 + (lane & 15) * 16;
      uint32_t ya = sb + OFF_U + (2 * w + ((lane >> 3) & 1)) * U_N8 + (lane >> 4) * 128 + (lane & 7) * 16;
      uint64_t du = make_desc(sb + OFF_U, 128, U_N8, 0), dk = make_desc(sb + OFF_K, 2048, 512, 2);
      const uint64_t dv = make_desc(sb + OFF_VP, 128, 512, 0);
      uint32_t yp[8] = {};
      uint32_t yq = sb + OFF_Q + lane * 16;
      auto store_y = [&]() { stsm4(yq, yp[0], yp[1], yp[2], yp[3]); stsm4(yq + 256, yp[4], yp[5], yp[6], yp[7]); };
      auto step = [&](int ch, auto fwd) {
        constexpr bool FWD = decltype(fwd)::value;
        float zu[32], sk[32], su[32], v[32], y[16];
        uint32_t kh[16], uh[16], fk[16], fu[16], fv[16];
        wg_fence();
        rs_n32<0, 0>(v, pr, dF2i); rs_n32<0, 0>(v + 16, pr + 8, dF2i); rs_n32<1, 0>(v, pr + 4, dF2i + 16); rs_n32<1, 0>(v + 16, pr + 12, dF2i + 16);
        wg_commit();
        CF(0);
        store_y();
        if (FWD) {
          const float dd = __uint_as_float(lds32(sb + OFF_D + 4 * (ch + 1)));
          zk[0] = fmaf(d0r, dd, zk[0]); zk[2] = fmaf(d0i, dd, zk[2]);
          pack32(fk, zk); twiddle<0>(fk, tp, ts); fence_u32<16>(fk);
          T2(sk, fk);
          CF(2);
          mbar_wait(bars + (B_KF + (ch & 1)) * 8, ((ch >> 1) & 1) ^ 1);
          wg_wait<1>();
        } else {
#pragma unroll
          for (int r = 3; r < 6; r++) mbar_wait(bars + (B_IN + r) * 8, 0);
          wg_wait<0>();
        }
        fence_regs<32>(v); fence_u32<16>(pr);
        pack32(fv, v); fence_u32<16>(fv);
        CF(4);
        if (FWD) T1u(zu, du + U_CH / 16);
        CF(5);
        if (FWD && (VO & 1)) { wg_wait<1>(); fence_regs<32>(sk); fence_u32<16>(fk); pack32(kh, sk); }
        twiddle<1>(fv, tp, ts);
#pragma unroll
        for (int i = 0; i < 4; i++) stsm4(va + 2 * i * vs, fv[4 * i], fv[4 * i + 1], fv[4 * i + 2], fv[4 * i + 3]);
        if (FWD) {
          if (!(VO & 1)) {
            CF(6);
            wg_wait<1>(); fence_regs<32>(sk); fence_u32<16>(fk);
            pack32(kh, sk);
          }
          fence_u32<16>(kh);
          CF(7);
          T1k(zk, dk);
          CF(8);
          wg_wait<1>(); fence_regs<32>(zu);
          pack32(fu, zu); twiddle<0>(fu, tp, ts); fence_u32<16>(fu);
          T2(su, fu);
          CF(10);
        }
        fence_proxy_async_smem();
        bar_sync(7, 128);
        wg_fence();
        ss_n32_tt<0>(y, dv, dF1b); ss_n32_tt<1>(y, dv + 16, dF1b + 64); ss_n32_tt<1>(y, du, dF1b + 128); ss_n32_tt<1>(y, du + 16, dF1b + 192);
        wg_commit();
        if (FWD && t == 0) mbar_arrive(bars + (B_Y + (ch & 3)) * 8);
        CF(12);
        if (FWD) {
          wg_wait<1>(); fence_regs<32>(su); fence_u32<16>(fu); fence_regs<32>(zk);
          if (t == 0) mbar_arrive(bars + (B_KE + (ch & 1)) * 8);
          pack32(uh, su);
          if (VO & 2) {
            bimac<0>(pr, kh, uh, pr); bimac<2>(pr + 8, kh + 8, uh, pr); fence_u32<16>(pr);
            CF(14);
            wg_wait<0>(); fence_regs<16>(y);
            bimac<1>(pr + 8, kh, uh + 8, pr + 8); fence_u32<8>(pr + 8);
          } else product(pr, kh, uh);
          du += U_CH / 16; dk += (ch & 1) ? -256 : 256;
          if (w >= 2) va += U_CH;
        }
        if (!FWD || !(VO & 2)) { CF(14); wg_wait<0>(); fence_regs<16>(y); }
#pragma unroll
        for (int i = 0; i < 8; i++) yp[i] = pack_bf16(y[2 * i], y[2 * i + 1]);
        fence_u32<8>(yp);
        yq = ya;
        ya += U_CH;
      };
#pragma unroll 1
      for (int ch = 0; ch < 7; ch++) step(ch, std::true_type());
      step(7, std::false_type());
      store_y();
    }
    fence_proxy_async_smem();
    bar_sync(7, 128);
    if (elect_one()) bulk_send(sb + OFF_U + (4 * rank + w) * U_N8 + 4 * U_CH, sb + OFF_U + (4 * (rank ^ 1) + w) * U_N8 + 6 * U_CH, U_CH + 512, bars + (B_IN + 6) * 8, rank ^ 1);
    __syncwarp();
    asm volatile("bar.arrive 9, 256;" ::: "memory");
  } else {
    asm volatile("setmaxnreg.inc.sync.aligned.u32 %0;" ::"n"(GREG));
    const int t = tid & 127, w = warp & 3, lane = t & 31, g = lane >> 2, c = lane & 3;
    if (wg == 1) {
      wait_until(c_start, COEF_T0);
      const int p = 64 * j + (t & 63) + 8 * (t & 64);
      const float Lr = bf2f(P.lam_re[p]), Li = bf2f(P.lam_im[p]);
      const uint32_t ds = __bfloat16_as_ushort(P.Dskip[128 * j + t]);
      const unsigned epoch = ld_relaxed(&g_epoch[b * 32]) + 1;
      const float dt = bf2f(__float2bfloat16_rn(expf(bf2f(P.log_dt[p]))));
      const float e = expf(dt * Lr);
      float sn, cs;
      {
        const double z = (double)(dt * Li) * 0.15915494309189535;
        sincospif(2.f * (float)(z - rint(z)), &sn, &cs);
      }
      const float lr = e * cs, li = e * sn;
      const float nr = lr - 1.0f, ni = li;
      const bool big = fabsf(Lr) >= fabsf(Li);
      const float la = big ? Lr : Li, lb = big ? Li : Lr, r = __fdiv_rn(lb, la), inv = __frcp_rn(fmaf(lb, r, la));
      const float br = (big ? fmaf(ni, r, nr) : fmaf(nr, r, ni)) * inv, bi = (big ? fmaf(-nr, r, ni) : fmaf(ni, r, -nr)) * inv;
      sts128(sb + OFF_COEF + t * 16, make_uint4(__float_as_uint(lr), __float_as_uint(li), pack_bf16(2.f * br, 2.f * br), pack_bf16(-2.f * bi, -2.f * bi)));
      sts32(sb + OFF_DS + 4 * t, ds << 16);
      if (t == 0) sts32(bars + B_EPOCH * 8, epoch);
    }
    CLUSTER_WAIT();
    if (wg == 1) mbar_arrive(bars + B_COEF * 8);
    float d[128];
    uint32_t so = 0, ph = 0, po = 0;
    uint32_t ra;
    auto set_ra = [&]() { asm volatile("mapa.shared::cluster.u32 %0, %1, %2;" : "=r"(ra) : "r"(bars + B_EMPTY * 8), "r"((t & 1) ? rank ^ 1 : rank)); };
    set_ra();
    auto release_at = [&](uint32_t off, bool skip) {
      asm volatile("{\n.reg .pred p;\nsetp.lt.u32 p, %1, %2;\n@p mbarrier.arrive.shared::cluster.b64 _, [%0];\n}\n" ::"r"(ra + off), "r"(t), "r"(skip ? 0 : 2) : "memory");
    };
    auto release = [&](bool first) { release_at(po, first); };
    auto block = [&](auto ta, uint64_t da0, uint64_t db0, bool first, bool zero, int nn) {
      constexpr int PH = decltype(ta)::value, TA = PH > 0, KS = TA ? 128 : 2, QD = PH == 0 ? QD1 : PH == 1 ? QD2 : QD3;
      mbar_wait(bars + B_FULL * 8 + so, ph);
      const uint64_t da = da0 + (so << 8), db = db0 + (so << 8);
      wg_fence();
      wgmma_n128<TA>(d, da, db, !zero);
      wgmma_n128<TA>(d + 64, da + 512, db, !zero);
      wg_commit();
      wg_wait<1>();
      if (RELPOS == 0) release(first);
#pragma unroll
      for (int k = 1; k < 4; k++) {
        if (QD == 2 || (QD == 4 && k == 2)) wg_fence();
        wgmma_n128<TA>(d, da + KS * k, db + 2 * k, 1);
        wgmma_n128<TA>(d + 64, da + 512 + KS * k, db + 2 * k, 1);
        if (QD == 2 || (QD == 4 && k == 1)) wg_commit();
        if (RELPOS == 1 && k == 1) release(first);
        if ((QD == 2 && k < 3) || (QD == 4 && k == 1)) wg_wait<1>();
      }
      if (QD != 2) wg_commit();
      if (RELPOS == 2) release(first);
      po = so;
      so += 8;
      if (so == 8 * STAGES) { so = 0; ph ^= 1; }
    };
    {
      so = wg ? 8 * (16 % STAGES) : 0; ph = wg ? (16 / STAGES) & 1 : 0; po = 0;
      const uint64_t da0 = make_desc(sb + OFF_RING, 16, 1024, 1), db0 = make_desc(sb + OFF_RING + 16384, 16, 1024, 1);
      if (wg == 1) bar_sync(1, 256);
#pragma unroll 1
      for (int kb = 0; kb < 16; kb++) {
        if (16 * wg + kb == XPOS) { so += 8; if (so == 8 * STAGES) { so = 0; ph ^= 1; } }
        block(std::integral_constant<int, 0>(), da0, db0, kb == 0, kb == 0, 16 * wg + kb);
      }
      asm volatile("bar.arrive %0, 256;" ::"r"(1 + wg) : "memory");
    }
    mbar_wait(bars + B_COEF * 8, 0);
    const uint32_t ca = sb + OFF_COEF + (64 * wg + 8 * w + g) * 16;
    const uint32_t tag = __shfl_sync(0xffffffffu, lds32(bars + B_EPOCH * 8) & 3, 0);
    constexpr int RE = SWAPB ? 2 : 0, IM = 2 - RE;
    uint2* cp = &g_carry[((16 * wg + 2 * j) * 16 + tc) * 32 + 8 * w];
    const int ct = lane >> 3;
    uint2 cv[4];
    auto load_carry = [&](int i) {
#pragma unroll
      for (int m = 0; m < 4; m++)
        asm volatile("{\n.reg .pred p;\n.reg .b64 v;\nsetp.lt.s32 p, %3, %4;\nmov.b64 v, {%0,%1};\n@p ld.relaxed.gpu.global.b64 v, [%2];\nmov.b64 {%0,%1}, v;\n}\n"
                     : "+r"(cv[m].x), "+r"(cv[m].y) : "l"(cp + 512 * i + (lane & 7) - 32 * (1 + ct) - 128 * m), "r"(ct), "r"(tc - 4 * m) : "memory");
    };
    auto first_load = [&](int i) {
#pragma unroll
      for (int m = 0; m < 4; m++) cv[m] = make_uint2(tag, 0);
      load_carry(i);
    };
    float lr[2], li[2], pr[2], pi[2], wr[2], wi[2], vr[2], vi[2], qr[2], qi[2], er[2], ei[2], gr[2], gi[2];
    auto powers = [&](int i) {
      const uint2 cf = lds64(ca + 512 * i);
      pr[i] = lr[i] = __uint_as_float(cf.x); pi[i] = li[i] = __uint_as_float(cf.y);
#pragma unroll
      for (int s = 0; s < 4; s++) csq(pr[i], pi[i]);
      gr[i] = pr[i]; gi[i] = pi[i];
      csq(pr[i], pi[i]);
      qr[i] = pr[i]; qi[i] = pi[i];
      csq(qr[i], qi[i]);
      er[i] = qr[i]; ei[i] = qi[i];
      wr[i] = (c & 1) ? pr[i] : 1.f; wi[i] = (c & 1) ? pi[i] : 0.f;
      if (c & 2) { float x, y; cmul(wr[i], wi[i], qr[i], qi[i], x, y); wr[i] = x; wi[i] = y; }
      vr[i] = wr[i]; vi[i] = wi[i];
      csq(vr[i], vi[i]); csq(vr[i], vi[i]);
      csq(qr[i], qi[i]); csq(qr[i], qi[i]); csq(qr[i], qi[i]);
      const int src = 4 * (lane & 7) + ct;
      vr[i] = __shfl_sync(0xffffffffu, vr[i], src); vi[i] = __shfl_sync(0xffffffffu, vi[i], src);
      qr[i] = __shfl_sync(0xffffffffu, qr[i], src); qi[i] = __shfl_sync(0xffffffffu, qi[i], src);
      asm volatile("" : "+f"(wr[i]), "+f"(wi[i]), "+f"(pr[i]), "+f"(pi[i]), "+f"(er[i]), "+f"(ei[i]));
    };
    powers(0);
    if (POW2 == 0) powers(1);
    PMFENCE();
    wg_wait<0>();
    fence_regs<128>(d);
    release(false);
#pragma unroll
    for (int i = 0; i < 2; i++) {
      const float* e = d + 64 * i;
      auto chain = [&](int s0, int s1, float& sr, float& si) {
        sr = e[2 * s0 + RE]; si = e[2 * s0 + IM];
#pragma unroll
        for (int s = s0 + 1; s < s1; s++) {
          const int ia = 4 * (s >> 1) + (s & 1);
          const float nr = fmaf(-li[i], si, fmaf(lr[i], sr, e[ia + RE])), ni = fmaf(li[i], sr, fmaf(lr[i], si, e[ia + IM]));
          sr = nr; si = ni;
          if (i == 1 && C_AT > 1 && s == C_AT) { asm volatile("pmevent 0;" : "+f"(sr), "+f"(si)::"memory"); first_load(0); }
        }
      };
      float sr, si;
      if (POW2 == 1 && i == 1) powers(1);
      if ((GREEDY >> i) & 1) {
        float ar, ai;
        chain(0, 16, ar, ai); chain(16, 32, sr, si);
        sr = fmaf(gr[i], ar, fmaf(-gi[i], ai, sr)); si = fmaf(gr[i], ai, fmaf(gi[i], ar, si));
      } else chain(0, 32, sr, si);
      if (i == 1 && C_AT == 0) { asm volatile("pmevent 0;" : "+f"(sr), "+f"(si)::"memory"); first_load(0); }
      float ur = __shfl_up_sync(0xffffffffu, sr, 1, 4), ui = __shfl_up_sync(0xffffffffu, si, 1, 4);
      if (c >= 1) { sr = fmaf(pr[i], ur, fmaf(-pi[i], ui, sr)); si = fmaf(pr[i], ui, fmaf(pi[i], ur, si)); }
      ur = __shfl_up_sync(0xffffffffu, sr, 2, 4); ui = __shfl_up_sync(0xffffffffu, si, 2, 4);
      if (c >= 2) { sr = fmaf(er[i], ur, fmaf(-ei[i], ui, sr)); si = fmaf(er[i], ui, fmaf(ei[i], ur, si)); }
      if (c == 3 && tc < 15)
        asm volatile("{\n.reg .b64 v;\nmov.b64 v, {%1,%2};\nst.relaxed.gpu.global.b64 [%0], v;\n}\n" ::"l"(cp + 512 * i + g), "r"((__float_as_uint(sr) & ~3u) | tag), "r"(__float_as_uint(si)) : "memory");
      if (i == 1 && C_AT == 1) first_load(0);
      PMFENCE();
      er[i] = __shfl_up_sync(0xffffffffu, sr, 1, 4); ei[i] = __shfl_up_sync(0xffffffffu, si, 1, 4);
      if (c == 0) er[i] = ei[i] = 0.f;
    }
    uint4* hp = g_h + (32 * tc + 16 * wg + 2 * j) * 1024 + 64 * w + 4 * g + (c ^ (g >> 1));
#pragma unroll
    for (int i = 0; i < 2; i++) {
      float* e = d + 64 * i;
      const uint2 cf = lds64(ca + 512 * i + 8);
      const uint32_t gp = cf.x, gms = cf.y;
      PMFENCE();
      int n = 0;
#pragma unroll 1
      while (!__all_sync(0xffffffffu, (((cv[0].x ^ tag) | (cv[1].x ^ tag) | (cv[2].x ^ tag) | (cv[3].x ^ tag)) & 3) == 0) && ++n <= (SPIN_LIMIT << 4)) load_carry(i);
      float hr = __uint_as_float(cv[3].x), hi = __uint_as_float(cv[3].y);
#pragma unroll
      for (int m = 2; m >= 0; m--) {
        const float nr = fmaf(qr[i], hr, fmaf(-qi[i], hi, __uint_as_float(cv[m].x))), ni = fmaf(qr[i], hi, fmaf(qi[i], hr, __uint_as_float(cv[m].y)));
        hr = nr; hi = ni;
      }
      { float x, y; cmul(hr, hi, vr[i], vi[i], x, y); hr = x; hi = y; }
      hr += __shfl_xor_sync(0xffffffffu, hr, 8); hi += __shfl_xor_sync(0xffffffffu, hi, 8);
      hr = __shfl_sync(0xffffffffu, hr, g) + __shfl_sync(0xffffffffu, hr, g + 16); hi = __shfl_sync(0xffffffffu, hi, g) + __shfl_sync(0xffffffffu, hi, g + 16);
      float sr = fmaf(wr[i], hr, fmaf(-wi[i], hi, er[i])), si = fmaf(wr[i], hi, fmaf(wi[i], hr, ei[i]));
#pragma unroll
      for (int i8 = 0; i8 < 4; i8++) {
        asm volatile("pmevent 0;" : "+f"(sr), "+f"(si)::"memory");
        if (i == 0 && i8 == C_AT2) first_load(1);
#pragma unroll
        for (int s = 8 * i8; s < 8 * i8 + 8; s++) {
          const int ia = 4 * (s >> 1) + (s & 1);
          const float nr = fmaf(-li[i], si, fmaf(lr[i], sr, e[ia + RE])), ni = fmaf(li[i], sr, fmaf(lr[i], si, e[ia + IM]));
          sr = nr; si = ni;
          e[ia + RE] = nr; e[ia + IM] = ni;
        }
        if (P2_SPLIT) PMFENCE();
        uint32_t hp0[4], hp1[4];
#pragma unroll
        for (int m = 0; m < 4; m++) {
          const float* f = e + 16 * i8 + 4 * m;
          const uint32_t x = pack_bf16(f[RE], f[RE + 1]), y = pack_bf16(f[IM], f[IM + 1]);
          hp0[m] = bfma2(gp, x, bmul2(gms, y)); hp1[m] = bfnma2(gp, y, bmul2(gms, x));
        }
        uint4* o = hp + 512 * (i8 >> 1) + 256 * i + 32 * (i8 & 1);
        stg128(o, make_uint4(hp0[0], hp0[1], hp0[2], hp0[3]));
        stg128(o + 1024, make_uint4(hp1[0], hp1[1], hp1[2], hp1[3]));
      }
    }
    const int trow = 128 * tc + 64 * (w & 1) + 8 * (w >> 1) + g;
    const int dcol = 128 * j + 4 * c;
    asm volatile("bar.arrive %0, 160;" ::"r"(4 + wg) : "memory");
    if (wg == 0) {
      set_ra();
      uint2 xv[32];
      {
        const int gp = 2 * (g & 3) + (g >> 2);
        const uint32_t xa = sb + OFF_RING + (XPOS % STAGES) * STAGE_BYTES + (64 * (w & 1) + 8 * (w >> 1) + gp) * 128 + (c & 1) * 8;
        mbar_wait(bars + B_XI * 8, 0);
        mbar_wait(bars + (B_FULL + XPOS % STAGES) * 8, (XPOS / STAGES) & 1);
#pragma unroll
        for (int u = 0; u < 32; u++) {
          const int J = (u >> 1) & 7;
          asm volatile("ld.shared.v2.u32 {%0,%1}, [%2];" : "=r"(xv[u].x), "=r"(xv[u].y) : "r"(xa + (J >> 2) * 16384 + (u >> 4) * 2048 + (u & 1) * 4096 + (((2 * (J & 3) + (c >> 1)) ^ gp) << 4)) : "memory");
        }
        uint32_t dep = P.zero;
#pragma unroll
        for (int u = 0; u < 32; u++) dep &= xv[u].x;
        bar_sync(3 + dep, 128);
        release_at(8 * (XPOS % STAGES), false);
      }
#pragma unroll
      for (int J = 0; J < 8; J++) {
        const uint4 ds = lds128(sb + OFF_DS + 16 * c + 64 * J);
#pragma unroll
        for (int r = 0; r < 4; r++) {
          const int u = 16 * (r >> 1) + 2 * J + (r & 1);
          float* e = d + 8 * (u >> 1) + 2 * (u & 1);
          e[0] = __uint_as_float(bfma2(blo2(xv[u].x), ds.x, 0)); e[1] = __uint_as_float(bfma2(xv[u].x, ds.y, 0));
          e[4] = __uint_as_float(bfma2(blo2(xv[u].y), ds.z, 0)); e[5] = __uint_as_float(bfma2(xv[u].y, ds.w, 0));
        }
      }
      fence_regs<128>(d);
      so = 8 * (33 % STAGES); ph = (33 / STAGES) & 1;
      const uint64_t da0 = make_desc(sb + OFF_RING + 16384, 512, 1024, 2), db0 = make_desc(sb + OFF_RING, 16, 1024, 1);
      bar_sync(2, 256);
#pragma unroll 1
      for (int kb = 0; kb < QSW; kb++) block(std::integral_constant<int, 1>(), da0, db0, kb == 0, false, 32 + kb);
#pragma unroll 1
      for (int kb = QSW; kb < 32 - TAILB; kb++) block(std::integral_constant<int, 2>(), da0, db0, false, false, 32 + kb);
      float* op = P.out + (size_t)trow * 2048 + 1024 + dcol;
      auto mma = [&](int i, int kb, int k0, int k1) {
        const int s = (33 + kb) % STAGES;
        wg_fence();
#pragma unroll
        for (int k = k0; k < k1; k++) wgmma_n128<1>(d + 64 * i, da0 + s * 2048 + 512 * i + 128 * k, db0 + (i ? 0 : P.zero) + s * 2048 + 2 * k, 1);
        wg_commit();
      };
      auto store = [&](int i, int J0, int J1) {
#pragma unroll
        for (int J = J0; J < J1; J++) {
#pragma unroll
          for (int h = 0; h < 2; h++) {
            const float* e = d + 64 * i + 8 * J + 2 * h;
            stg128(op + (size_t)(16 * i + 32 * h) * 2048 + 16 * J, make_uint4(__float_as_uint(e[0]), __float_as_uint(e[1]), __float_as_uint(e[4]), __float_as_uint(e[5])));
          }
        }
        PMFENCE();
      };
      constexpr int K0 = 32 - TAILB;
#pragma unroll
      for (int kb = K0; kb < 32; kb++) {
        mbar_wait(bars + (B_FULL + (33 + kb) % STAGES) * 8, ((33 + kb) / STAGES) & 1);
        if (TAILB == 5 && kb == K0) { mma(0, kb, 0, 2); wg_wait<1>(); release(false); mma(0, kb, 2, 4); }
        else mma(0, kb, 0, 4);
      }
      mma(1, K0, 0, 4);
      wg_wait<1>();
      fence_regs<64>(d);
#pragma unroll
      for (int kb = K0 + 1; kb < 32; kb++) {
        mma(1, kb, 0, 4);
        if (T_FENCE) PMFENCE();
        store(0, T_ST * (kb - K0 - 1), kb == 31 ? 8 : T_ST * (kb - K0));
      }
      wg_wait<0>();
      fence_regs<64>(d + 64);
      store(1, 0, 8);
      if (t == 0) g_epoch[b * 32] = lds32(bars + B_EPOCH * 8);
      return;
    }
    asm volatile("setmaxnreg.dec.sync.aligned.u32 %0;" ::"n"(488 - 2 * GREG));
  }
  {
    int lane;
    asm volatile("mov.u32 %0, %%laneid;" : "=r"(lane));
    const int w = warp & 3, h = wg & 1;
    const int lc = 2 * (lane & 2) + (lane & 1) + ((lane >> 2) & 2);
    const bool own = ((lane >> 2) & 1) == rank, spare = !own && lc < 2;
    const uint32_t ya = (spare ? sb + OFF_IN + 96 + lc * 2064 : sb + OFF_U + (own ? 4 * rank * U_N8 : 4 * (rank ^ 1) * U_N8 - 2 * U_CH) + lc * U_CH) + w * 128 + (lane >> 4) * 16 + h * 64;
    const uint32_t ys = spare ? 512 : U_N8;
    const uint32_t ob0 = sb + (h ? OFF_F1 : OFF_K) + 1024 * w, ob1 = sb + (h ? OFF_VP : OFF_K + 4096) + 1024 * w;
    uint32_t y[2][8];
    uint2 q[4][4];
    auto get_q = [&](int n, int off, int bar, int ph) {
#pragma unroll
      for (int u = 0; u < 2; u++) {
        mbar_wait(bars + (bar + u) * 8, ph);
#pragma unroll
        for (int r = 0; r < 4; r++) q[n + u][r] = lds64(sb + off + 4096 * u + 1024 * w + 256 * r + 8 * lane);
      }
    };
    auto get_y = [&](int n) { ldsm4t(y[n & 1], ya + n * ys); ldsm4t(y[n & 1] + 4, ya + n * ys + 32); };
    if (h) {
#pragma unroll
      for (int n = 0; n < 4; n += 2) {
        get_q(n, OFF_Q, B_QF, n >> 1);
        uint32_t dep = P.zero;
#pragma unroll
        for (int r = 0; r < 8; r++) dep &= q[n + (r >> 2)][r & 3].x;
        bar_sync(6 + dep, 128);
        if (Q_HOLD && n == 0) mbar_wait(bars + B_HP * 8, 1);
        if (w < 2 && elect_one()) load_q(5 + 2 * w - (n >> 1), OFF_Q, B_QF + n);
        __syncwarp();
      }
#pragma unroll 1
      for (int r = 0; r < 6; r++) mbar_wait(bars + (B_IN + r) * 8, 0);
      bar_sync(9, 256);
    } else get_q(0, OFF_K, B_KF, 0);
    if (O_WAIT) mbar_wait(bars + (O_WAIT == 1 ? B_HP : B_HR) * 8, 1);
    mbar_wait(bars + (B_IN + 6) * 8, 0);
    get_y(0);
    uint32_t oc = clk32() + (2 * w + h) * (O_PACE / 2);
#pragma unroll
    for (int n = 0; n < 4; n++) {
      uint32_t* o = y[n & 1];
#pragma unroll
      for (int r = 0; r < 4; r++) { o[2 * r] = bmul2(o[2 * r], q[n][r].x); o[2 * r + 1] = bmul2(o[2 * r + 1], q[n][r].y); }
#pragma unroll
      for (int u = 0; u < 2; u++) {
        const uint32_t ob = u ? ob1 : ob0;
        if (n > 0 && lane == 0) asm volatile("cp.async.bulk.wait_group.read 1;" ::: "memory");
        __syncwarp();
#pragma unroll
        for (int r = 2 * u; r < 2 * u + 2; r++)
          sts128(ob + (r & 1) * 512 + lane * 16, make_uint4(o[2 * r] << 16, o[2 * r] & 0xffff0000u, o[2 * r + 1] << 16, o[2 * r + 1] & 0xffff0000u));
        if (O_PACE) { while ((int)(clk32() - oc) < 0) { if (O_SLEEP) __nanosleep(O_SLEEP); } }
        oc += 4 * O_PACE;
        fence_proxy_async_smem();
        __syncwarp();
        if (lane == 0)
          asm volatile("cp.async.bulk.tensor.3d.global.shared::cta.bulk_group [%0, {%2, %3, %4}], [%1];\ncp.async.bulk.commit_group;"
                       ::"l"(&mO), "r"(ob), "r"(32 * slot), "r"(32 * rank + 8 * w), "r"(8 * n + 4 * h + 2 * u) : "memory");
        __syncwarp();
        if (u == 0 && n < 3) get_y(n + 1);
        if (u == 0 && n == 1 && !h) get_q(2, OFF_Q, B_QF + 2, 0);
      }
    }
    if (warp == 8 && lane == 0) mbar_arrive_cta(bars + B_ACK * 8, rank ^ 1);
    if (lane == 0) asm volatile("cp.async.bulk.wait_group 0;" ::: "memory");
    mbar_wait(bars + B_ACK * 8, 0);
  }
}

typedef CUresult (*EncodeFn)(CUtensorMap*, CUtensorMapDataType, cuuint32_t, void*, const cuuint64_t*, const cuuint64_t*, const cuuint32_t*,
                             const cuuint32_t*, CUtensorMapInterleave, CUtensorMapSwizzle, CUtensorMapL2promotion, CUtensorMapFloatOOBfill);

bool encode(EncodeFn fn, CUtensorMap* m, int rank, const void* base, const cuuint64_t* dims, const cuuint64_t* strides, const cuuint32_t* box, CUtensorMapSwizzle swz,
            CUtensorMapL2promotion promo = CU_TENSOR_MAP_L2_PROMOTION_L2_128B) {
  const cuuint32_t es[5] = {1, 1, 1, 1, 1};
  return fn(m, CU_TENSOR_MAP_DATA_TYPE_BFLOAT16, rank, const_cast<void*>(base), dims, strides, box, es, CU_TENSOR_MAP_INTERLEAVE_NONE, swz,
            promo, CU_TENSOR_MAP_FLOAT_OOB_FILL_NONE) == CUDA_SUCCESS;
}

}

extern "C" void kernel_launch(void* const* d_in, const int* in_sizes, int n_in, void* d_out, int out_size) {
  (void)in_sizes; (void)n_in; (void)out_size;
  typedef const __nv_bfloat16* In;
  const In q = (In)d_in[0], k = (In)d_in[1], v = (In)d_in[2], ssm_k = (In)d_in[4], x = (In)d_in[6], B_re = (In)d_in[9], B_im = (In)d_in[10], C_re = (In)d_in[11], C_im = (In)d_in[12];
  Params P = {};
  P.shift_k = (In)d_in[3]; P.ssm_D = (In)d_in[5]; P.lam_re = (In)d_in[7]; P.lam_im = (In)d_in[8]; P.log_dt = (In)d_in[13]; P.Dskip = (In)d_in[14];
  P.out = (float*)d_out;
  for (int cl = 0; cl < 64; cl++) P.slot[cl >> 2] |= (cl < 4 ? 4 + cl : cl < 36 ? 8 * ((cl - 4) & 7) + ((cl - 4) >> 3) : 8 * (1 + (cl - 36) % 7) + 4 + (cl - 36) / 7) << (8 * (cl & 3));
  const bool swapB = (uintptr_t)B_im < (uintptr_t)B_re;

  EncodeFn fn = nullptr;
  cudaDriverEntryPointQueryResult qr;
  cudaGetDriverEntryPoint("cuTensorMapEncodeTiled", (void**)&fn, cudaEnableDefault, &qr);
  if (!fn) return;

  CUtensorMap mX, mB, mCre, mCim, mXs, mK, mV, mQ, mS, mO;
  bool ok = true;
  {
    const cuuint64_t dims[4] = {1024, 2, 64, 16}, str[3] = {2048, 32 * 2048, 2 * 2048};
    const cuuint32_t box[4] = {64, 2, 4, 16};
    ok &= encode(fn, &mX, 4, x, dims, str, box, CU_TENSOR_MAP_SWIZZLE_128B, (CUtensorMapL2promotion)X_PROMO);
  }
  {
    const uintptr_t lo = swapB ? (uintptr_t)B_im : (uintptr_t)B_re, hi = swapB ? (uintptr_t)B_re : (uintptr_t)B_im;
    const cuuint64_t dims[4] = {1024, 8, 2, 128}, str[3] = {2048, (cuuint64_t)(hi - lo), 8 * 2048};
    const cuuint32_t box[4] = {64, 8, 2, 4};
    ok &= encode(fn, &mB, 4, (const void*)lo, dims, str, box, CU_TENSOR_MAP_SWIZZLE_128B, (CUtensorMapL2promotion)B_PROMO);
  }
  {
    const cuuint64_t dims[5] = {1024, 2, 4, 2, 64}, str[4] = {2048, 4 * 2048, 2 * 2048, 16 * 2048};
    const cuuint32_t box[5] = {64, 2, 4, 2, 4};
    ok &= encode(fn, &mCre, 5, C_re, dims, str, box, CU_TENSOR_MAP_SWIZZLE_128B, (CUtensorMapL2promotion)C_PROMO);
    ok &= encode(fn, &mCim, 5, C_im, dims, str, box, CU_TENSOR_MAP_SWIZZLE_128B, (CUtensorMapL2promotion)C_PROMO);
  }
  {
    const cuuint64_t dims[4] = {1024, 2, 4, 256}, str[3] = {4 * 2048, 2048, 8 * 2048};
    const cuuint32_t box[4] = {64, 2, 4, 16};
    ok &= encode(fn, &mXs, 4, x, dims, str, box, CU_TENSOR_MAP_SWIZZLE_128B);
  }
  {
    const cuuint64_t dims[3] = {1024, 64, 32}, str[2] = {32 * 2048, 2048};
    const cuuint32_t box[3] = {16, 32, 4};
    const cuuint64_t dimq[4] = {1024, 8, 32, 8}, strq[3] = {32 * 2048, 2048, 256 * 2048};
    const cuuint32_t boxq[4] = {16, 8, 4, 4};
    ok &= encode(fn, &mQ, 4, q, dimq, strq, boxq, CU_TENSOR_MAP_SWIZZLE_NONE, (CUtensorMapL2promotion)Q_PROMO);
    ok &= encode(fn, &mK, 3, k, dims, str, box, CU_TENSOR_MAP_SWIZZLE_32B, (CUtensorMapL2promotion)KV_PROMO);
    ok &= encode(fn, &mV, 3, v, dims, str, box, CU_TENSOR_MAP_SWIZZLE_32B, (CUtensorMapL2promotion)KV_PROMO);
  }
  {
    const cuuint64_t dims[2] = {32, 65536}, str[1] = {64};
    const cuuint32_t box[2] = {32, 64};
    ok &= encode(fn, &mS, 2, ssm_k, dims, str, box, CU_TENSOR_MAP_SWIZZLE_64B, (CUtensorMapL2promotion)S_PROMO);
  }
  {
    const cuuint64_t dims[3] = {2048, 64, 32}, str[2] = {32 * 8192, 8192};
    const cuuint32_t box[3] = {32, 8, 2};
    ok &= encode(fn, &mO, 3, d_out, dims, str, box, CU_TENSOR_MAP_SWIZZLE_NONE);
  }
  if (!ok) return;
  auto kern = swapB ? fused_kernel<1> : fused_kernel<0>;
  cudaFuncSetAttribute(kern, cudaFuncAttributeMaxDynamicSharedMemorySize, SMEM_BYTES);
  kern<<<NCTA, 512, SMEM_BYTES, cudaStreamPerThread>>>(P, mX, mB, mCre, mCim, mXs, mK, mV, mQ, mS, mO);
}
```

```cpp
#include <cuda_runtime.h>
#include <cuda_bf16.h>
#include <cuda.h>
#include <stdint.h>
#include <type_traits>

namespace {

constexpr int D_DIM = 1024;
constexpr int NCTA = 128;

constexpr int STAGES = 5, STAGE_BYTES = 32768;
constexpr int OFF_RING = 0;
constexpr int OFF_F1 = STAGES * STAGE_BYTES, OFF_F2 = OFF_F1 + 4096, OFF_K = OFF_F2 + 2048, OFF_VP = OFF_K + 8192, OFF_Q = OFF_VP + 4096, OFF_IN = OFF_Q + 8192;
constexpr int OFF_KV = OFF_K;
constexpr int U_CH = 528, U_N8 = 8 * U_CH, OFF_U = OFF_IN + U_N8;
constexpr int OFF_COEF = OFF_U + 8 * U_N8;
constexpr int OFF_DS = OFF_COEF + 2048, OFF_D = OFF_DS + 512;
constexpr int OFF_BAR = OFF_D + 64;
constexpr int SMEM_BYTES = OFF_BAR + 512;
static_assert(SMEM_BYTES <= 232448 && OFF_K % 1024 == 0 && (OFF_U + 3 * U_N8) % 512 == 0 && (4 * U_N8) % 512 == 0, "smem map");
constexpr int B_FULL = 0, B_XI = 5, B_HR = 6, B_HP = 7, B_KVF = 8, B_KF = 11, B_KE = 13, B_QF = 15, B_IN = 19, B_UF = 27, B_Y = 31, B_ACK = 36,
              B_EMPTY = 38, B_COEF = 43, B_KVE = 44, B_NONE = 47, B_EPOCH = 48;
constexpr int QD1 = 8;
constexpr int QD2 = 2;
constexpr int QD3 = 8;
constexpr int QSW = 16;
constexpr int HEAD = 3;
constexpr int ST_T0 = 200;
constexpr int ST_DELAY = 300;
constexpr int XPOS = 28;
constexpr int K_T0 = 800;
constexpr int KV_T0 = 1500;
constexpr int KV_DT = 560;
constexpr int KV_DV = 100;
constexpr int O_PACE = 0;
constexpr int POLL_NS = 30;
constexpr int GREEDY = 1;
constexpr int P2_SPLIT = 0;
constexpr int TAILB = 5;
constexpr int GREG = 176;
constexpr int O_WAIT = 2;
constexpr int COEF_T0 = 2500;
constexpr int RELPOS = 0;
constexpr int C_AT = 0;
constexpr int C_AT2 = 1;
constexpr int T_FENCE = 0;
constexpr int T_ST = 2;
constexpr int X_PROMO = 2;
constexpr int B_PROMO = 2;
constexpr int C_PROMO = 2;
constexpr int KV_PROMO = 2;
constexpr int Q_PROMO = 2;
constexpr int S_PROMO = 2;
constexpr int POW2 = 1;
constexpr int O_SLEEP = 20;
constexpr int VO = 3;
constexpr int PFC = 3;
constexpr int PFC_T0 = 13500;
constexpr int PFC_T1 = 1500;
constexpr int PFC_DT = 400;
constexpr int PFQ = 4;
constexpr int Q_HOLD = 0;
constexpr int FASTW = 1;
constexpr int CFM = 0x40f1;
constexpr int SPIN_LIMIT = 1 << 14;

struct Params {
  unsigned slot[16];
  unsigned zero;
  const __nv_bfloat16 *shift_k, *ssm_D, *lam_re, *lam_im, *log_dt, *Dskip;
  float* out;
};

__device__ __align__(1024) uint4 g_h[16 * 32 * 1024];
__device__ __align__(128) uint2 g_carry[32 * 16 * 32];
__device__ unsigned g_flagH[2 * 16 * 32];
__device__ unsigned g_epoch[NCTA * 32];

__device__ __forceinline__ uint64_t make_desc(uint32_t addr, uint32_t lbo, uint32_t sbo, uint32_t swz) {
  return (uint64_t)((addr & 0x3FFFF) >> 4) | ((uint64_t)(lbo >> 4) << 16) | ((uint64_t)(sbo >> 4) << 32) | ((uint64_t)swz << 62);
}
__device__ __forceinline__ void wg_fence() { asm volatile("wgmma.fence.sync.aligned;" ::: "memory"); }
__device__ __forceinline__ void wg_commit() { asm volatile("wgmma.commit_group.sync.aligned;" ::: "memory"); }
template <int N> __device__ __forceinline__ void wg_wait() { asm volatile("wgmma.wait_group.sync.aligned %0;" ::"n"(N) : "memory"); }
__device__ __forceinline__ void mbar_init(uint32_t bar, int cnt) { asm volatile("mbarrier.init.shared::cta.b64 [%0], %1;" ::"r"(bar), "r"(cnt) : "memory"); }
__device__ __forceinline__ void mbar_expect(uint32_t bar, uint32_t bytes) { asm volatile("mbarrier.arrive.expect_tx.shared::cta.b64 _, [%0], %1;" ::"r"(bar), "r"(bytes) : "memory"); }
__device__ __forceinline__ bool mbar_try(uint32_t bar, uint32_t parity) {
  uint32_t ok;
  asm volatile("{\n.reg .pred p;\nmbarrier.try_wait.parity.shared::cta.b64 p, [%1], %2;\nselp.u32 %0, 1, 0, p;\n}\n" : "=r"(ok) : "r"(bar), "r"(parity) : "memory");
  return ok;
}
__device__ __forceinline__ void mbar_wait(uint32_t bar, uint32_t parity) {
  int n = 0;
  while (!mbar_try(bar, parity) && ++n <= SPIN_LIMIT) {}
}
__device__ __forceinline__ void mbar_arrive(uint32_t bar) { asm volatile("mbarrier.arrive.shared::cta.b64 _, [%0];" ::"r"(bar) : "memory"); }
__device__ __forceinline__ void mbar_arrive_cta(uint32_t bar, uint32_t cta) {
  asm volatile("{\n.reg .b32 ra;\nmapa.shared::cluster.u32 ra, %0, %1;\nmbarrier.arrive.shared::cluster.b64 _, [ra];\n}\n" ::"r"(bar), "r"(cta) : "memory");
}
__device__ __forceinline__ bool elect_one() {
  uint32_t p;
  asm volatile("{\n.reg .pred P;\nelect.sync _|P, 0xffffffff;\nselp.u32 %0, 1, 0, P;\n}\n" : "=r"(p));
  return p != 0;
}
__device__ __forceinline__ void bar_sync(int id, int n) { asm volatile("bar.sync %0, %1;" ::"r"(id), "r"(n) : "memory"); }
#define TMA_LD(dim) "cp.async.bulk.tensor." dim ".shared::cluster.global.mbarrier::complete_tx::bytes"
__device__ __forceinline__ void tma2d(uint32_t dst, const CUtensorMap* m, int c0, int c1, uint32_t bar) {
  asm volatile(TMA_LD("2d") " [%0], [%1, {%3, %4}], [%2];" ::"r"(dst), "l"(m), "r"(bar), "r"(c0), "r"(c1) : "memory");
}
__device__ __forceinline__ void tma3d(uint32_t dst, const CUtensorMap* m, int c0, int c1, int c2, uint32_t bar) {
  asm volatile(TMA_LD("3d") " [%0], [%1, {%3, %4, %5}], [%2];" ::"r"(dst), "l"(m), "r"(bar), "r"(c0), "r"(c1), "r"(c2) : "memory");
}
__device__ __forceinline__ void tma4d(uint32_t dst, const CUtensorMap* m, int c0, int c1, int c2, int c3, uint32_t bar) {
  asm volatile(TMA_LD("4d") " [%0], [%1, {%3, %4, %5, %6}], [%2];" ::"r"(dst), "l"(m), "r"(bar), "r"(c0), "r"(c1), "r"(c2), "r"(c3) : "memory");
}
__device__ __forceinline__ void tma4d_mc(uint32_t dst, const CUtensorMap* m, int c0, int c1, int c2, int c3, uint32_t bar) {
  asm volatile(TMA_LD("4d") ".multicast::cluster [%0], [%1, {%3, %4, %5, %6}], [%2], %7;" ::"r"(dst), "l"(m), "r"(bar), "r"(c0), "r"(c1), "r"(c2), "r"(c3), "h"((uint16_t)3) : "memory");
}
__device__ __forceinline__ void tma5d_mc(uint32_t dst, const CUtensorMap* m, int c0, int c1, int c2, int c3, int c4, uint32_t bar) {
  asm volatile(TMA_LD("5d") ".multicast::cluster [%0], [%1, {%3, %4, %5, %6, %7}], [%2], %8;" ::"r"(dst), "l"(m), "r"(bar), "r"(c0), "r"(c1), "r"(c2), "r"(c3), "r"(c4), "h"((uint16_t)3) : "memory");
}
__device__ __forceinline__ void bulk_load(uint32_t dst, const void* src, uint32_t bytes, uint32_t bar) {
  asm volatile("cp.async.bulk.shared::cluster.global.mbarrier::complete_tx::bytes [%0], [%1], %2, [%3];" ::"r"(dst), "l"(src), "r"(bytes), "r"(bar) : "memory");
}
__device__ __forceinline__ void bulk_send(uint32_t dst, uint32_t src, uint32_t bytes, uint32_t bar, uint32_t cta) {
  asm volatile("{\n.reg .b32 rd, rb;\nmapa.shared::cluster.u32 rd, %0, %3;\nmapa.shared::cluster.u32 rb, %2, %3;\n"
               "cp.async.bulk.shared::cluster.shared::cta.mbarrier::complete_tx::bytes [rd], [%1], %4, [rb];\n}\n"
               ::"r"(dst), "r"(src), "r"(bar), "r"(cta), "r"(bytes) : "memory");
}
__device__ __forceinline__ void fence_proxy_async_smem() { asm volatile("fence.proxy.async.shared::cta;" ::: "memory"); }
__device__ __forceinline__ void fence_proxy_async_global() { asm volatile("fence.proxy.async.global;" ::: "memory"); }
__device__ __forceinline__ uint32_t clk32() { uint32_t c; asm volatile("mov.u32 %0, %%clock;" : "=r"(c)::"memory"); return c; }
__device__ __forceinline__ void wait_until(uint32_t t0, uint32_t dt) { while (clk32() - t0 < dt) __nanosleep(32); }
__device__ __forceinline__ void spin_until(uint32_t t0, uint32_t dt) { while (clk32() - t0 < dt) {} }
__device__ __forceinline__ void prefetch_map(const CUtensorMap* m) { asm volatile("prefetch.tensormap [%0];" ::"l"(m) : "memory"); }
__device__ __forceinline__ void prefetch_line(const void* p) { asm volatile("prefetch.global.L2 [%0];" ::"l"(p) : "memory"); }
__device__ __forceinline__ unsigned ld_acquire(const unsigned* p) { unsigned v; asm volatile("ld.acquire.gpu.global.u32 %0, [%1];" : "=r"(v) : "l"(p) : "memory"); return v; }
__device__ __forceinline__ unsigned ld_relaxed(const unsigned* p) { unsigned v; asm volatile("ld.relaxed.gpu.global.u32 %0, [%1];" : "=r"(v) : "l"(p) : "memory"); return v; }
__device__ __forceinline__ uint32_t lds32(uint32_t a) { uint32_t v; asm volatile("ld.shared.u32 %0, [%1];" : "=r"(v) : "r"(a)); return v; }
__device__ __forceinline__ uint2 lds64(uint32_t a) { uint2 v; asm volatile("ld.shared.v2.u32 {%0,%1}, [%2];" : "=r"(v.x), "=r"(v.y) : "r"(a) : "memory"); return v; }
__device__ __forceinline__ uint4 lds128(uint32_t a) { uint4 v; asm volatile("ld.shared.v4.u32 {%0,%1,%2,%3}, [%4];" : "=r"(v.x), "=r"(v.y), "=r"(v.z), "=r"(v.w) : "r"(a) : "memory"); return v; }
__device__ __forceinline__ void sts32(uint32_t a, uint32_t v) { asm volatile("st.shared.u32 [%0], %1;" ::"r"(a), "r"(v) : "memory"); }
__device__ __forceinline__ void sts128(uint32_t a, uint4 v) { asm volatile("st.shared.v4.u32 [%0], {%1,%2,%3,%4};" ::"r"(a), "r"(v.x), "r"(v.y), "r"(v.z), "r"(v.w) : "memory"); }
__device__ __forceinline__ void ldsm4(uint32_t* r, uint32_t a) { asm volatile("ldmatrix.sync.aligned.m8n8.x4.shared.b16 {%0,%1,%2,%3}, [%4];" : "=r"(r[0]), "=r"(r[1]), "=r"(r[2]), "=r"(r[3]) : "r"(a) : "memory"); }
__device__ __forceinline__ void ldsm4t(uint32_t* r, uint32_t a) { asm volatile("ldmatrix.sync.aligned.m8n8.x4.trans.shared.b16 {%0,%1,%2,%3}, [%4];" : "=r"(r[0]), "=r"(r[1]), "=r"(r[2]), "=r"(r[3]) : "r"(a) : "memory"); }
__device__ __forceinline__ void stsm4t(uint32_t a, uint32_t r0, uint32_t r1, uint32_t r2, uint32_t r3) {
  asm volatile("stmatrix.sync.aligned.m8n8.x4.trans.shared.b16 [%0], {%1,%2,%3,%4};" ::"r"(a), "r"(r0), "r"(r1), "r"(r2), "r"(r3) : "memory");
}
__device__ __forceinline__ uint4 ldg128_nc(const void* p) { uint4 v; asm volatile("ld.global.nc.L1::no_allocate.v4.u32 {%0,%1,%2,%3}, [%4];" : "=r"(v.x), "=r"(v.y), "=r"(v.z), "=r"(v.w) : "l"(p)); return v; }
__device__ __forceinline__ void stg128(void* p, uint4 v) { asm volatile("st.global.L1::no_allocate.v4.u32 [%0], {%1,%2,%3,%4};" ::"l"(p), "r"(v.x), "r"(v.y), "r"(v.z), "r"(v.w) : "memory"); }
__device__ __forceinline__ uint32_t pack_bf16(float lo, float hi) { uint32_t r; asm("cvt.rn.bf16x2.f32 %0, %1, %2;" : "=r"(r) : "f"(hi), "f"(lo)); return r; }
__device__ __forceinline__ uint32_t bmul2(uint32_t a, uint32_t b) { uint32_t r; asm("mul.rn.bf16x2 %0, %1, %2;" : "=r"(r) : "r"(a), "r"(b)); return r; }
__device__ __forceinline__ uint32_t bfma2(uint32_t a, uint32_t b, uint32_t c) { uint32_t r; asm("fma.rn.bf16x2 %0, %1, %2, %3;" : "=r"(r) : "r"(a), "r"(b), "r"(c)); return r; }
__device__ __forceinline__ uint32_t blo2(uint32_t a) { uint32_t r; asm("{\n.reg .b16 l, h;\nmov.b32 {l, h}, %1;\nmov.b32 %0, {l, l};\n}" : "=r"(r) : "r"(a)); return r; }
__device__ __forceinline__ float bf2f(__nv_bfloat16 v) { return __bfloat162float(v); }

#define R8(d, o) "+f"(d[o]), "+f"(d[o + 1]), "+f"(d[o + 2]), "+f"(d[o + 3]), "+f"(d[o + 4]), "+f"(d[o + 5]), "+f"(d[o + 6]), "+f"(d[o + 7])
#define R16(d, o) R8(d, o), R8(d, o + 8)
#define R64(d, o) R16(d, o), R16(d, o + 16), R16(d, o + 32), R16(d, o + 48)
template <int TA> __device__ __forceinline__ void wgmma_n128(float* d, uint64_t da, uint64_t db, int scale_d) {
  asm volatile("{\n.reg .pred p;\nsetp.ne.b32 p, %66, 0;\n"
    "wgmma.mma_async.sync.aligned.m64n128k16.f32.bf16.bf16 {"
    "%0,%1,%2,%3,%4,%5,%6,%7,%8,%9,%10,%11,%12,%13,%14,%15,%16,%17,%18,%19,%20,%21,%22,%23,%24,%25,%26,%27,%28,%29,%30,%31,"
    "%32,%33,%34,%35,%36,%37,%38,%39,%40,%41,%42,%43,%44,%45,%46,%47,%48,%49,%50,%51,%52,%53,%54,%55,%56,%57,%58,%59,%60,%61,%62,%63"
    "}, %64, %65, p, 1, 1, %67, 0;\n}\n"
    : R64(d, 0)
    : "l"(da), "l"(db), "r"(scale_d), "n"(TA));
}
template <int N> __device__ __forceinline__ void fence_regs(float* d) {
#pragma unroll
  for (int i = 0; i < N; i++) asm volatile("" : "+f"(d[i])::"memory");
}
#define PMFENCE() asm volatile("pmevent 0;" ::: "memory")
__device__ __forceinline__ void cmul(float ar, float ai, float br, float bi, float& cr, float& ci) {
  cr = ar * br - ai * bi; ci = ar * bi + ai * br;
}
__device__ __forceinline__ void csq(float& r, float& i) { const float x = fmaf(r, r, -i * i), y = r * i; r = x; i = y + y; }

#define W8(d, o) "=f"(d[o]), "=f"(d[o + 1]), "=f"(d[o + 2]), "=f"(d[o + 3]), "=f"(d[o + 4]), "=f"(d[o + 5]), "=f"(d[o + 6]), "=f"(d[o + 7])
#define L16 "{%0,%1,%2,%3,%4,%5,%6,%7,%8,%9,%10,%11,%12,%13,%14,%15}"
#define L32 "{%0,%1,%2,%3,%4,%5,%6,%7,%8,%9,%10,%11,%12,%13,%14,%15,%16,%17,%18,%19,%20,%21,%22,%23,%24,%25,%26,%27,%28,%29,%30,%31}"
template <int ACC, int TB> __device__ __forceinline__ void rs_n32(float* d, const uint32_t* a, uint64_t db) {
  if constexpr (ACC) asm volatile("wgmma.mma_async.sync.aligned.m64n32k16.f32.bf16.bf16 " L16 ", {%16,%17,%18,%19}, %20, 1, 1, 1, %21;" : R16(d, 0) : "r"(a[0]), "r"(a[1]), "r"(a[2]), "r"(a[3]), "l"(db), "n"(TB));
  else asm volatile("wgmma.mma_async.sync.aligned.m64n32k16.f32.bf16.bf16 " L16 ", {%16,%17,%18,%19}, %20, 0, 1, 1, %21;" : W8(d, 0), W8(d, 8) : "r"(a[0]), "r"(a[1]), "r"(a[2]), "r"(a[3]), "l"(db), "n"(TB));
}
template <int ACC, int TB> __device__ __forceinline__ void ss_n64(float* d, uint64_t da, uint64_t db) {
  if constexpr (ACC) asm volatile("wgmma.mma_async.sync.aligned.m64n64k16.f32.bf16.bf16 " L32 ", %32, %33, 1, 1, 1, 0, %34;" : R16(d, 0), R16(d, 16) : "l"(da), "l"(db), "n"(TB));
  else asm volatile("wgmma.mma_async.sync.aligned.m64n64k16.f32.bf16.bf16 " L32 ", %32, %33, 0, 1, 1, 0, %34;" : W8(d, 0), W8(d, 8), W8(d, 16), W8(d, 24) : "l"(da), "l"(db), "n"(TB));
}
template <int ACC> __device__ __forceinline__ void ss_n32_tt(float* d, uint64_t da, uint64_t db) {
  if constexpr (ACC) asm volatile("wgmma.mma_async.sync.aligned.m64n32k16.f32.bf16.bf16 " L16 ", %16, %17, 1, 1, 1, 1, 1;" : R16(d, 0) : "l"(da), "l"(db));
  else asm volatile("wgmma.mma_async.sync.aligned.m64n32k16.f32.bf16.bf16 " L16 ", %16, %17, 0, 1, 1, 1, 1;" : W8(d, 0), W8(d, 8) : "l"(da), "l"(db));
}
__device__ __forceinline__ void stsm4(uint32_t a, uint32_t r0, uint32_t r1, uint32_t r2, uint32_t r3) {
  asm volatile("stmatrix.sync.aligned.m8n8.x4.shared.b16 [%0], {%1,%2,%3,%4};" ::"r"(a), "r"(r0), "r"(r1), "r"(r2), "r"(r3) : "memory");
}
template <int N> __device__ __forceinline__ void fence_u32(uint32_t* d) {
#pragma unroll
  for (int i = 0; i < N; i++) asm volatile("" : "+r"(d[i])::"memory");
}
__device__ __forceinline__ void pack32(uint32_t* f, const float* z) {
#pragma unroll
  for (int i = 0; i < 16; i++) f[i] = pack_bf16(z[2 * i], z[2 * i + 1]);
}
template <int INV> __device__ __forceinline__ void twiddle(uint32_t* f, const uint32_t* tp, const uint32_t* ts) {
#pragma unroll
  for (int i = 0; i < 8; i++) {
    uint32_t x = f[2 * i + INV], y = f[2 * i + 1 - INV];
    x = bfma2(tp[i & 3], y, x); y = bfma2(ts[i & 3], x, y); x = bfma2(tp[i & 3], y, x);
    f[2 * i + INV] = x; f[2 * i + 1 - INV] = y;
  }
}
__device__ __forceinline__ uint32_t bfnma2(uint32_t a, uint32_t b, uint32_t c) { uint32_t r; asm("{\n.reg .b32 t;\nmul.bf16x2 t, %1, %2;\nsub.bf16x2 %0, %3, t;\n}" : "=r"(r) : "r"(a), "r"(b), "r"(c)); return r; }
__device__ __forceinline__ uint32_t bfms2(uint32_t a, uint32_t b, uint32_t c) { uint32_t r; asm("{\n.reg .b32 t;\nmul.bf16x2 t, %1, %2;\nsub.bf16x2 %0, t, %3;\n}" : "=r"(r) : "r"(a), "r"(b), "r"(c)); return r; }
template <int ADD> __device__ __forceinline__ void bimac(uint32_t* o, const uint32_t* a, const uint32_t* b, const uint32_t* c) {
#pragma unroll
  for (int J = 0; J < 2; J++) {
    const uint32_t Pr = a[2 * J], Pi = a[2 * J + 1], Qr = a[2 * J + 4], Qi = a[2 * J + 5], pr = b[2 * J], pi = b[2 * J + 1], qr = b[2 * J + 4], qi = b[2 * J + 5];
    uint32_t x0, x1, x2, x3;
    if (ADD == 0) { x0 = bmul2(Pr, pr); x1 = bmul2(Pr, pi); x2 = bmul2(Pr, qr); x3 = bmul2(Pr, qi); }
    if (ADD == 1) { x0 = bfma2(Pr, pr, c[2 * J]); x1 = bfma2(Pr, pi, c[2 * J + 1]); x2 = bfma2(Pr, qr, c[2 * J + 4]); x3 = bfma2(Pr, qi, c[2 * J + 5]); }
    if (ADD == 2) { x0 = bfma2(Pr, pr, c[2 * J + 1]); x1 = bfms2(Pr, pi, c[2 * J]); x2 = bfma2(Pr, qr, c[2 * J + 5]); x3 = bfms2(Pr, qi, c[2 * J + 4]); }
    x0 = bfnma2(Pi, pi, x0); x1 = bfma2(Pi, pr, x1); x2 = bfnma2(Pi, qi, x2); x3 = bfma2(Pi, qr, x3);
    x0 = bfnma2(Qr, qr, x0); x1 = bfnma2(Qr, qi, x1); x2 = bfma2(Qr, pr, x2); x3 = bfma2(Qr, pi, x3);
    x0 = bfma2(Qi, qi, x0); x1 = bfnma2(Qi, qr, x1); x2 = bfnma2(Qi, pi, x2); x3 = bfma2(Qi, pr, x3);
    o[2 * J] = x0; o[2 * J + 1] = x1; o[2 * J + 4] = x2; o[2 * J + 5] = x3;
  }
}
__device__ __forceinline__ void sincos8k(int n, float& s, float& c) {
  const float x = (float)((n << 19) >> 19) * (6.283185307179586f / 8192.f);
  s = __sinf(x); c = __cosf(x);
}
__device__ __forceinline__ void fft_tables(uint32_t f1a, uint32_t f2a, int w, int lane, uint32_t* tp, uint32_t* ts, float& d0r, float& d0i) {
  const int c = lane & 3, f1 = 8 * w + (lane >> 2);
#pragma unroll 1
  for (int J = 3; J >= 0; J--) {
    const int a = 8 * J + 2 * c;
    float s0, c0, s1, c1;
    sincos8k(64 * (4 * f1 + 1) * a + 31 * (4 * f1 - 63), d0i, d0r); sincos8k(64 * (4 * f1 + 1) * (a + 1) + 31 * (4 * f1 - 63), s1, c1);
    d0r *= 0.125f; d0i *= 0.125f;
    sts32(f1a + w * 1024 + J * 128 + lane * 4, pack_bf16(d0r, 0.125f * c1)); sts32(f1a + w * 1024 + 512 + J * 128 + lane * 4, pack_bf16(d0i, 0.125f * s1));
    sincos8k(128 * (2 * (a & 15) + 1) * f1 - 128 * (a & 16), s0, c0); sincos8k(128 * (2 * (a & 15) + 3) * f1 - 128 * (a & 16), s1, c1);
    sts32(f2a + w * 512 + J * 128 + lane * 4, pack_bf16(c0, c1));
    sincos8k((4 * f1 - 63) * (2 * a - 31), s0, c0); sincos8k((4 * f1 - 63) * (2 * a - 29), s1, c1);
#pragma unroll
    for (int i = 3; i > 0; i--) { ts[i] = ts[i - 1]; tp[i] = tp[i - 1]; }
    ts[0] = pack_bf16(s0, s1); tp[0] = pack_bf16(-__fdividef(s0, 1.f + c0), -__fdividef(s1, 1.f + c1));
  }
  if (c != 0) d0r = d0i = 0.f;
}

template <int SWAPB>
__global__ void __cluster_dims__(2, 1, 1) __launch_bounds__(512, 1)
fused_kernel(const __grid_constant__ Params P, const __grid_constant__ CUtensorMap mX, const __grid_constant__ CUtensorMap mB,
             const __grid_constant__ CUtensorMap mCre, const __grid_constant__ CUtensorMap mCim, const __grid_constant__ CUtensorMap mXs,
             const __grid_constant__ CUtensorMap mK, const __grid_constant__ CUtensorMap mV, const __grid_constant__ CUtensorMap mQ, const __grid_constant__ CUtensorMap mS,
             const __grid_constant__ CUtensorMap mO) {
  extern __shared__ __align__(1024) uint8_t smem_raw[];
  const uint32_t sb = (uint32_t)__cvta_generic_to_shared(smem_raw);
  const uint32_t bars = sb + OFF_BAR;
  const int slot = (P.slot[blockIdx.x >> 3] >> (4 * (blockIdx.x & 6))) & 63, rank = blockIdx.x & 1;
  const int j = slot & 7, tc = 2 * (slot >> 3) + rank, b = 2 * slot + rank;
  const int tid = threadIdx.x;
  const int warp = __shfl_sync(0xffffffffu, tid >> 5, 0);
  const int wg = warp >> 2;
  const uint32_t c_start = clk32();
  auto kblock = [&](int n) { return ((n & 14) == 0 || (n & 14) == 2 * j ? n ^ (2 * j) : n) & 31; };
  auto send_y = [&](int r) {
    const uint32_t src = sb + OFF_U + 4 * (rank ^ 1) * U_N8 + r * U_CH, dst = r >= 2 ? sb + OFF_U + 4 * rank * U_N8 + (r - 2) * U_CH : sb + OFF_IN + 96 + r * 2064;
#pragma unroll 1
    for (int n = 0; n < 4; n++) bulk_send(dst + n * (r >= 2 ? U_N8 : 512), src + n * U_N8, 512, bars + (B_IN + r) * 8, rank ^ 1);
  };
  auto load_q = [&](int i, int off, int bar) {
    const uint32_t fb = bars + bar * 8 + 4 * (i & 2);
    mbar_expect(fb, 4096); tma4d(sb + off + 2048 * (i & 2), &mQ, 16 * slot, 0, 4 * i, 4 * rank, fb);
  };
  auto head = [&](int n) {
    const uint32_t fb = bars + (B_FULL + n) * 8, dst = sb + OFF_RING + n * STAGE_BYTES;
    mbar_expect(fb, STAGE_BYTES);
    tma4d(dst + 16384, &mX, 64 * n, 0, 4 * tc, 0, fb);
    tma4d(dst, &mB, 64 * n, 0, 0, 8 * j, fb);
    tma4d(dst + 8192, &mB, 64 * n, 0, 0, 8 * j + 4, fb);
  };
  if (warp == 0 && elect_one()) {
#pragma unroll
    for (int s = 0; s < STAGES; s++) mbar_init(bars + (B_FULL + s) * 8, 1);
    head(0);
    asm volatile("fence.mbarrier_init.release.cluster;" ::: "memory");
  }
  if (wg == 3 && elect_one()) {
    if (warp < 15) {
#pragma unroll
      for (int s = 0; s < 11; s++) mbar_init(bars + 8 * B_XI + (warp & 3) * 88 + 8 * s, 1);
    } else {
#pragma unroll
      for (int s = B_EMPTY; s <= B_NONE; s++) mbar_init(bars + 8 * s, s < B_COEF ? 2 : s == B_COEF ? 128 : 4);
    }
    asm volatile("fence.mbarrier_init.release.cluster;" ::: "memory");
  }
  __syncwarp();
  asm volatile("barrier.cluster.arrive.relaxed.aligned;" ::: "memory");
  if (warp == 0 && elect_one()) {
#pragma unroll 1
    for (int n = 1; n < HEAD; n++) { spin_until(c_start, ST_T0 + n * ST_DELAY); head(n); }
  }
  __syncwarp();
#define CLUSTER_WAIT() asm volatile("barrier.cluster.wait.aligned;" ::: "memory")

  if (wg == 3) {
    asm volatile("setmaxnreg.dec.sync.aligned.u32 24;");
    CLUSTER_WAIT();
    if (warp < 14) {
      if (elect_one()) {
        uint32_t so = 8 * (HEAD % STAGES), ph = HEAD < STAGES;
        auto step = [&](auto issue) {
          mbar_wait(bars + B_EMPTY * 8 + so, ph);
          issue(sb + OFF_RING + (so << 12), bars + B_FULL * 8 + so);
          so += 8;
          if (so == 8 * STAGES) { so = 0; ph ^= 1; }
        };
        if (warp == 12) {
          auto g1 = [&](int n0, int n1, int grp) {
#pragma unroll 1
            for (int n = n0; n < n1; n++) step([&](uint32_t dst, uint32_t fb) { mbar_expect(fb, STAGE_BYTES); tma4d_mc(dst + rank * 8192, &mB, n * 64, 0, 0, grp + 4 * rank, fb); });
          };
#pragma unroll 1
          for (int n = HEAD; n < STAGES; n++) { spin_until(c_start, ST_T0 + n * ST_DELAY); g1(n, n + 1, 8 * j); }
          g1(STAGES, 16, 8 * j);
          g1(0, XPOS - 16, 8 * j + 64);
          step([&](uint32_t dst, uint32_t fb) { mbar_expect(fb, STAGE_BYTES); tma4d(dst, &mXs, 128 * j, 0, 0, 16 * tc, fb); mbar_arrive(bars + B_XI * 8); });
          g1(XPOS - 16, 16, 8 * j + 64);
#pragma unroll 1
          for (int n = 0; n < 32; n += 2) {
            const int col = kblock(n) * 32;
#pragma unroll
            for (int part = 0; part < 2; part++)
              step([&](uint32_t dst, uint32_t fb) { mbar_expect(fb, STAGE_BYTES); tma5d_mc(dst + rank * 8192, part ? &mCim : &mCre, col, 0, 0, 0, 8 * j + 4 * rank, fb); });
          }
        } else {
          auto g1 = [&](int n0, int n1, int nb) {
#pragma unroll 1
            for (int n = n0; n < n1; n++) step([&](uint32_t dst, uint32_t fb) { tma4d(dst + 16384, &mX, n * 64, 0, 4 * tc, 0, fb); });
          };
          auto g2 = [&](int n0, int n1) {
#pragma unroll 1
            for (int n = n0; n < n1; n++) step([&](uint32_t dst, uint32_t fb) { bulk_load(dst + 16384, g_h + (32 * tc + kblock(n)) * 1024, 16384, fb); });
          };
#pragma unroll 1
          for (int n = HEAD; n < STAGES; n++) { spin_until(c_start, ST_T0 + n * ST_DELAY); g1(n, n + 1, 0); }
          g1(STAGES, 16, 0);
          g1(0, XPOS - 16, 16);
          step([&](uint32_t dst, uint32_t fb) { tma4d(dst + 16384, &mXs, 128 * j + 64, 0, 0, 16 * tc, fb); });
          g1(XPOS - 16, 16, 16);
#pragma unroll 1
          for (int v = 0; v < 2; v++) {
            mbar_wait(bars + B_HP * 8, v);
            fence_proxy_async_global();
            g2(16 * v, 16 * v + 2);
            mbar_wait(bars + B_HR * 8, v);
            fence_proxy_async_global();
            g2(16 * v + 2, 16 * v + 16);
          }
        }
      }
    } else if (warp == 15) {
      mbar_wait(bars + B_COEF * 8, 0);
      const unsigned epoch = lds32(bars + B_EPOCH * 8);
#pragma unroll 1
      for (int v = 0; v < 2; v++) {
        unsigned* fp = &g_flagH[(16 * v + tc) * 32];
        if (((PFC >> v) & 1) && elect_one()) {
          wait_until(v ? clk32() : c_start, (v ? PFC_T1 : PFC_T0) + (slot >> 3) * PFC_DT);
#pragma unroll
          for (int part = 0; part < 2; part++)
            asm volatile("cp.async.bulk.prefetch.tensor.5d.L2.global [%0, {%1, %2, %2, %2, %3}];" ::"l"(part ? &mCim : &mCre), "r"(512 * v + 8 * (slot & 56)), "r"(0), "r"(8 * j + 4 * rank) : "memory");
        }
        __syncwarp();
        bar_sync(4 + v, 160);
        if (elect_one()) {
          asm volatile("red.release.gpu.global.add.u32 [%0], 1;" ::"l"(fp) : "memory");
          mbar_arrive(bars + B_HP * 8);
          int it = 0;
          while (ld_acquire(fp) != 8 * epoch && ++it < (SPIN_LIMIT << 4)) __nanosleep(POLL_NS);
          mbar_arrive(bars + B_HR * 8);
        }
        __syncwarp();
      }
    } else if (elect_one()) {
      const int ch0 = 16 * slot;
      auto load_k = [&](int s, uint32_t dst) { const uint32_t fb = bars + (B_KF + (s & 1)) * 8; mbar_expect(fb, 4096); tma2d(dst, &mS, 0, 64 * (8 * b + s), fb); };
      prefetch_map(&mS); prefetch_map(&mK); prefetch_map(&mV);
      wait_until(c_start, K_T0);
      load_k(0, sb + OFF_U + (4 * rank + 3) * U_N8); load_k(1, sb + OFF_U + (4 * rank + 3) * U_N8 - 4096);
      {
        uint32_t so = 16, ph = 1;
#pragma unroll 1
        for (int e = 0; e < 9; e++) {
          const uint32_t fb = bars + B_KVF * 8 + so, dst = sb + OFF_KV + (so << 10);
          wait_until(c_start, KV_T0 + (e ? 2 * e - 1 : 0) * KV_DT);
          mbar_wait(bars + B_KVE * 8 + so, ph);
          const uint32_t c1 = clk32();
          mbar_expect(fb, e ? 8192 : 4096);
          tma3d(dst, &mK, ch0, 32 * rank - (e == 0), (4 * e - 4) & 31, fb);
          if (e > 0) { wait_until(c1, KV_DV); tma3d(dst + 4096, &mV, ch0, 32 * rank, 4 * e - 4, fb); }
          so += 8;
          if (so == 24) so = 0;
          if (so == 16) ph ^= 1;
        }
      }
      prefetch_map(&mCre); prefetch_map(&mCim); prefetch_map(&mXs); prefetch_map(&mQ); prefetch_map(&mO);
      mbar_wait(bars + B_KVE * 8, 0);
      load_k(2, sb + OFF_K); load_k(3, sb + OFF_K + 4096);
      mbar_wait(bars + (B_UF + 3) * 8, 0);
#pragma unroll 1
      for (int ch = 0; ch < 7; ch++) {
        if (ch > 0) {
          mbar_wait(bars + (B_Y + (ch & 3)) * 8, ch >> 2);
          if (ch > 2) mbar_wait(bars + (B_IN + ch - 3) * 8, 0);
          send_y(ch - 1);
        }
        if (ch < 6) {
          mbar_wait(bars + (B_KE + (ch & 1)) * 8, (ch >> 1) & 1);
          if (ch < 4) load_k(ch + 4, sb + OFF_K + (ch & 1) * 4096);
          if (PFQ && ch == PFQ - 1) asm volatile("cp.async.bulk.prefetch.tensor.4d.L2.global [%0, {%1, %2, %3, %4}];" ::"l"(&mQ), "r"(16 * (slot & ~3)), "r"(0), "r"(16 + 4 * (slot & 3)), "r"(4 * rank) : "memory");
          if (ch >= 2) load_q(2 * (ch & 1) + (ch < 4), ch < 4 ? OFF_Q : OFF_K, ch < 4 ? B_QF : B_KF);
        }
      }
    }
    return;
  } else if (wg == 2) {
    asm volatile("setmaxnreg.inc.sync.aligned.u32 %0;" ::"n"(488 - 2 * GREG));
    const int t = tid & 127, w = warp & 3, lane = t & 31, g = lane >> 2, c = lane & 3;
    const uint4 s2[2] = {ldg128_nc(P.shift_k + (8 * b + 2 * c) * 4), ldg128_nc(P.shift_k + (8 * (b ^ 1) + 2 * c) * 4)};
    const uint32_t dskip = __bfloat16_as_ushort(P.ssm_D[8 * b + (t & 7)]);
    uint32_t tp[4] = {}, ts[4] = {};
    float d0r, d0i;
    fft_tables(sb + OFF_F1, sb + OFF_F2, w, lane, tp, ts, d0r, d0i);
    CLUSTER_WAIT();
    if (t < 12) mbar_expect(bars + (B_IN + t) * 8, t < 6 ? 2048 : t < 8 ? 4 * (U_CH + 512) : U_N8);
    if (t < 8) sts32(sb + OFF_D + 4 * t, dskip << 16);
    const uint64_t dF1a = make_desc(sb + OFF_F1, 128, 512, 0), dF1b = make_desc(sb + OFF_F1, 512, 128, 0);
    const uint64_t dF2f = make_desc(sb + OFF_F2, 512, 128, 0), dF2i = make_desc(sb + OFF_F2, 128, 512, 0);
    auto T1k = [&](float* z, uint64_t dk) { wg_fence(); ss_n64<0, 1>(z, dF1a, dk); ss_n64<1, 1>(z, dF1a + 16, dk + 64); wg_commit(); };
    auto T1u = [&](float* z, uint64_t du) { wg_fence(); ss_n64<0, 0>(z, dF1a, du); ss_n64<1, 0>(z, dF1a + 16, du + 16); wg_commit(); };
    auto T2 = [&](float* s, const uint32_t* f) {
      wg_fence();
      rs_n32<0, 1>(s, f, dF2f); rs_n32<0, 1>(s + 16, f + 8, dF2f); rs_n32<1, 1>(s, f + 4, dF2f + 64); rs_n32<1, 1>(s + 16, f + 12, dF2f + 64);
      wg_commit();
    };
    auto product = [&](uint32_t* pr, const uint32_t* kh, const uint32_t* uh) {
      bimac<0>(pr, kh, uh, pr); bimac<2>(pr + 8, kh + 8, uh, pr); bimac<1>(pr + 8, kh, uh + 8, pr + 8);
      fence_u32<16>(pr);
    };
    float zk[32] = {};
    uint32_t pr[16];
    {
      uint32_t kh0[16];
      {
        float z0[32], sk[32];
        uint32_t fk[16];
        const uint64_t dk = make_desc(sb + OFF_U + (4 * rank + 3) * U_N8, 2048, 512, 2);
        fence_proxy_async_smem();
        bar_sync(7, 128);
        mbar_wait(bars + B_KF * 8, 0);
        T1k(z0, dk);
        mbar_wait(bars + (B_KF + 1) * 8, 0);
        T1k(zk, dk - 256);
        wg_wait<0>(); fence_regs<32>(z0); fence_regs<32>(zk);
        const float dd = __uint_as_float(lds32(sb + OFF_D));
        z0[0] = fmaf(d0r, dd, z0[0]); z0[2] = fmaf(d0i, dd, z0[2]);
        pack32(fk, z0); twiddle<0>(fk, tp, ts); fence_u32<16>(fk);
        T2(sk, fk);
        wg_wait<0>(); fence_regs<32>(sk); fence_u32<16>(fk);
        pack32(kh0, sk); fence_u32<16>(kh0);
      }
      {
        uint32_t sk[2][4], kx[2][8];
#pragma unroll
        for (int o = 0; o < 2; o++) {
          sk[o][0] = __byte_perm(s2[o].x, s2[o].z, 0x5410); sk[o][1] = __byte_perm(s2[o].x, s2[o].z, 0x7632);
          sk[o][2] = __byte_perm(s2[o].y, s2[o].w, 0x5410); sk[o][3] = __byte_perm(s2[o].y, s2[o].w, 0x7632);
        }
        const uint32_t la = sb + OFF_KV + (lane >> 3) * 1024 + (8 * w + (lane & 7)) * 32 + ((rank ^ ((lane >> 2) & 1)) << 4);
        const uint32_t uo = (lane & 7) * U_CH + w * 128 + (lane >> 3) * 16;
        mbar_wait(bars + (B_KVF + 2) * 8, 0);
        ldsm4(kx[0], la + 16384); ldsm4(kx[1], (la ^ 16) + 16384);
        if (lane == 0) mbar_arrive(bars + (B_KVE + 2) * 8 + (kx[0][1] & kx[1][1] & P.zero));
        uint32_t so = 0, ph = 0;
#pragma unroll 1
        for (int n = 0; n < 4; n++) {
          const uint32_t own = sb + OFF_U + (4 * rank + n) * U_N8, box = n < 3 ? sb + OFF_U + (4 * (rank ^ 1) + n + 1) * U_N8 : sb + OFF_IN;
#pragma unroll
          for (int e = 0; e < 2; e++) {
            uint32_t vx[2][4];
            mbar_wait(bars + B_KVF * 8 + so, ph);
#pragma unroll
            for (int o = 0; o < 2; o++) { ldsm4(kx[o] + 4, (la ^ (16 * o)) + (so << 10)); ldsm4(vx[o], (la ^ (16 * o)) + (so << 10) + 4096); }
            if (lane == 0) mbar_arrive(bars + B_KVE * 8 + so + (kx[0][4] & kx[1][4] & vx[0][0] & vx[1][0] & P.zero));
#pragma unroll
            for (int o = 0; o < 2; o++) {
#pragma unroll
              for (int i = 0; i < 4; i++) vx[o][i] = bmul2(bfma2(kx[o][i + 4], sk[o][0], bfma2(kx[o][i + 3], sk[o][1], bfma2(kx[o][i + 2], sk[o][2], bmul2(kx[o][i + 1], sk[o][3])))), vx[o][i]);
              stsm4t((o ? box : own) + uo + e * 64, vx[o][0], vx[o][1], vx[o][2], vx[o][3]);
              kx[o][1] = kx[o][5]; kx[o][2] = kx[o][6]; kx[o][3] = kx[o][7];
            }
            so += 8;
            if (so == 24) so = 0;
            if (so == 16) ph ^= 1;
          }
          fence_proxy_async_smem();
          bar_sync(7, 128);
          if (w == 0 && elect_one()) {
            if (n > 0) mbar_wait(bars + B_UF * 8 + 8 * (n - 1), 0);
            bulk_send(own, box, U_N8, bars + B_UF * 8 + 8 * n, rank ^ 1);
          }
          __syncwarp();
        }
      }
      float zu[32], su[32];
      uint32_t fu[16], uh[16];
#pragma unroll
      for (int n = 0; n < 4; n++) mbar_wait(bars + (B_UF + n) * 8, 0);
      T1u(zu, make_desc(sb + OFF_U, 128, U_N8, 0));
      wg_wait<0>(); fence_regs<32>(zu);
      pack32(fu, zu); twiddle<0>(fu, tp, ts); fence_u32<16>(fu);
      T2(su, fu);
      wg_wait<0>(); fence_regs<32>(su); fence_u32<16>(fu);
      pack32(uh, su);
      product(pr, kh0, uh);
    }
    {
#define CF(i) do { if ((CFM >> (i)) & 1) PMFENCE(); } while (0)
      const uint32_t vs = w < 2 ? 512 : U_N8;
      uint32_t va = (w < 2 ? sb + OFF_VP : sb + OFF_U) + ((lane >> 4) & 1) * vs + (w & 1) * 256 + (lane & 15) * 16;
      uint32_t ya = sb + OFF_U + (2 * w + ((lane >> 3) & 1)) * U_N8 + (lane >> 4) * 128 + (lane & 7) * 16;
      uint64_t du = make_desc(sb + OFF_U, 128, U_N8, 0), dk = make_desc(sb + OFF_K, 2048, 512, 2);
      const uint64_t dv = make_desc(sb + OFF_VP, 128, 512, 0);
      uint32_t yp[8] = {};
      uint32_t yq = sb + OFF_Q + lane * 16;
      auto store_y = [&]() { stsm4(yq, yp[0], yp[1], yp[2], yp[3]); stsm4(yq + 256, yp[4], yp[5], yp[6], yp[7]); };
      auto step = [&](int ch, auto fwd) {
        constexpr bool FWD = decltype(fwd)::value;
        float zu[32], sk[32], su[32], v[32], y[16];
        uint32_t kh[16], uh[16], fk[16], fu[16], fv[16];
        wg_fence();
        rs_n32<0, 0>(v, pr, dF2i); rs_n32<0, 0>(v + 16, pr + 8, dF2i); rs_n32<1, 0>(v, pr + 4, dF2i + 16); rs_n32<1, 0>(v + 16, pr + 12, dF2i + 16);
        wg_commit();
        CF(0);
        store_y();
        if (FWD) {
          const float dd = __uint_as_float(lds32(sb + OFF_D + 4 * (ch + 1)));
          zk[0] = fmaf(d0r, dd, zk[0]); zk[2] = fmaf(d0i, dd, zk[2]);
          pack32(fk, zk); twiddle<0>(fk, tp, ts); fence_u32<16>(fk);
          T2(sk, fk);
          CF(2);
          mbar_wait(bars + (B_KF + (ch & 1)) * 8, ((ch >> 1) & 1) ^ 1);
          wg_wait<1>();
        } else {
#pragma unroll
          for (int r = 3; r < 6; r++) mbar_wait(bars + (B_IN + r) * 8, 0);
          wg_wait<0>();
        }
        fence_regs<32>(v); fence_u32<16>(pr);
        pack32(fv, v); fence_u32<16>(fv);
        CF(4);
        if (FWD) T1u(zu, du + U_CH / 16);
        CF(5);
        if (FWD && (VO & 1)) { wg_wait<1>(); fence_regs<32>(sk); fence_u32<16>(fk); pack32(kh, sk); }
        twiddle<1>(fv, tp, ts);
#pragma unroll
        for (int i = 0; i < 4; i++) stsm4(va + 2 * i * vs, fv[4 * i], fv[4 * i + 1], fv[4 * i + 2], fv[4 * i + 3]);
        if (FWD) {
          if (!(VO & 1)) {
            CF(6);
            wg_wait<1>(); fence_regs<32>(sk); fence_u32<16>(fk);
            pack32(kh, sk);
          }
          fence_u32<16>(kh);
          CF(7);
          T1k(zk, dk);
          CF(8);
          wg_wait<1>(); fence_regs<32>(zu);
          pack32(fu, zu); twiddle<0>(fu, tp, ts); fence_u32<16>(fu);
          T2(su, fu);
          CF(10);
        }
        fence_proxy_async_smem();
        bar_sync(7, 128);
        wg_fence();
        ss_n32_tt<0>(y, dv, dF1b); ss_n32_tt<1>(y, dv + 16, dF1b + 64); ss_n32_tt<1>(y, du, dF1b + 128); ss_n32_tt<1>(y, du + 16, dF1b + 192);
        wg_commit();
        if (FWD && t == 0) mbar_arrive(bars + (B_Y + (ch & 3)) * 8);
        CF(12);
        if (FWD) {
          wg_wait<1>(); fence_regs<32>(su); fence_u32<16>(fu); fence_regs<32>(zk);
          if (t == 0) mbar_arrive(bars + (B_KE + (ch & 1)) * 8);
          pack32(uh, su);
          if (VO & 2) {
            bimac<0>(pr, kh, uh, pr); bimac<2>(pr + 8, kh + 8, uh, pr); fence_u32<16>(pr);
            CF(14);
            wg_wait<0>(); fence_regs<16>(y);
            bimac<1>(pr + 8, kh, uh + 8, pr + 8); fence_u32<8>(pr + 8);
          } else product(pr, kh, uh);
          du += U_CH / 16; dk += (ch & 1) ? -256 : 256;
          if (w >= 2) va += U_CH;
        }
        if (!FWD || !(VO & 2)) { CF(14); wg_wait<0>(); fence_regs<16>(y); }
#pragma unroll
        for (int i = 0; i < 8; i++) yp[i] = pack_bf16(y[2 * i], y[2 * i + 1]);
        fence_u32<8>(yp);
        yq = ya;
        ya += U_CH;
      };
#pragma unroll 1
      for (int ch = 0; ch < 7; ch++) step(ch, std::true_type());
      step(7, std::false_type());
      store_y();
    }
    fence_proxy_async_smem();
    bar_sync(7, 128);
    if (elect_one()) bulk_send(sb + OFF_U + (4 * rank + w) * U_N8 + 4 * U_CH, sb + OFF_U + (4 * (rank ^ 1) + w) * U_N8 + 6 * U_CH, U_CH + 512, bars + (B_IN + 6) * 8, rank ^ 1);
    __syncwarp();
    asm volatile("bar.arrive 9, 256;" ::: "memory");
  } else {
    asm volatile("setmaxnreg.inc.sync.aligned.u32 %0;" ::"n"(GREG));
    const int t = tid & 127, w = warp & 3, lane = t & 31, g = lane >> 2, c = lane & 3;
    if (wg == 1) {
      wait_until(c_start, COEF_T0);
      const int p = 64 * j + (t & 63) + 8 * (t & 64);
      const float Lr = bf2f(P.lam_re[p]), Li = bf2f(P.lam_im[p]);
      const uint32_t ds = __bfloat16_as_ushort(P.Dskip[128 * j + t]);
      const unsigned epoch = ld_relaxed(&g_epoch[b * 32]) + 1;
      const float dt = bf2f(__float2bfloat16_rn(expf(bf2f(P.log_dt[p]))));
      const float e = expf(dt * Lr);
      float sn, cs;
      {
        const double z = (double)(dt * Li) * 0.15915494309189535;
        sincospif(2.f * (float)(z - rint(z)), &sn, &cs);
      }
      const float lr = e * cs, li = e * sn;
      const float nr = lr - 1.0f, ni = li;
      const bool big = fabsf(Lr) >= fabsf(Li);
      const float la = big ? Lr : Li, lb = big ? Li : Lr, r = __fdiv_rn(lb, la), inv = __frcp_rn(fmaf(lb, r, la));
      const float br = (big ? fmaf(ni, r, nr) : fmaf(nr, r, ni)) * inv, bi = (big ? fmaf(-nr, r, ni) : fmaf(ni, r, -nr)) * inv;
      sts128(sb + OFF_COEF + t * 16, make_uint4(__float_as_uint(lr), __float_as_uint(li), pack_bf16(2.f * br, 2.f * br), pack_bf16(-2.f * bi, -2.f * bi)));
      sts32(sb + OFF_DS + 4 * t, ds << 16);
      if (t == 0) sts32(bars + B_EPOCH * 8, epoch);
    }
    CLUSTER_WAIT();
    if (wg == 1) mbar_arrive(bars + B_COEF * 8);
    float d[128];
    uint32_t so = 0, ph = 0, po = 0;
    uint32_t ra;
    auto set_ra = [&]() { asm volatile("mapa.shared::cluster.u32 %0, %1, %2;" : "=r"(ra) : "r"(bars + B_EMPTY * 8), "r"((t & 1) ? rank ^ 1 : rank)); };
    set_ra();
    auto release = [&](uint32_t off) { if (t < 2) asm volatile("mbarrier.arrive.shared::cluster.b64 _, [%0];" ::"r"(ra + off) : "memory"); };
    constexpr uint32_t NOBAR = 8 * (B_NONE - B_EMPTY);
    auto block = [&](auto ta, uint64_t da0, uint64_t db0, bool zero, int nn) {
      constexpr int PH = decltype(ta)::value, TA = PH > 0, KS = TA ? 128 : 2, QD = PH == 0 ? QD1 : PH == 1 ? QD2 : QD3;
      mbar_wait(bars + B_FULL * 8 + so, ph);
      const uint64_t da = da0 + (so << 8), db = db0 + (so << 8);
      wg_fence();
      wgmma_n128<TA>(d, da, db, !zero);
      wgmma_n128<TA>(d + 64, da + 512, db, !zero);
      wg_commit();
      wg_wait<1>();
      if (RELPOS == 0) release(po);
#pragma unroll
      for (int k = 1; k < 4; k++) {
        if (QD == 2 || (QD == 4 && k == 2)) wg_fence();
        wgmma_n128<TA>(d, da + KS * k, db + 2 * k, 1);
        wgmma_n128<TA>(d + 64, da + 512 + KS * k, db + 2 * k, 1);
        if (QD == 2 || (QD == 4 && k == 1)) wg_commit();
        if (RELPOS == 1 && k == 1) release(po);
        if ((QD == 2 && k < 3) || (QD == 4 && k == 1)) wg_wait<1>();
      }
      if (QD != 2) wg_commit();
      if (RELPOS == 2) release(po);
      po = so;
      so += 8;
      if (so == 8 * STAGES) { so = 0; ph ^= 1; }
    };
    {
      so = wg ? 8 * (16 % STAGES) : 0; ph = wg ? (16 / STAGES) & 1 : 0; po = NOBAR;
      const uint64_t da0 = make_desc(sb + OFF_RING, 16, 1024, 1), db0 = make_desc(sb + OFF_RING + 16384, 16, 1024, 1);
      if (wg == 1) bar_sync(1, 256);
#pragma unroll 1
      for (int kb = 0; kb < 16; kb++) {
        if (16 * wg + kb == XPOS) { so += 8; if (so == 8 * STAGES) { so = 0; ph ^= 1; } }
        block(std::integral_constant<int, 0>(), da0, db0, kb == 0, 16 * wg + kb);
      }
      asm volatile("bar.arrive %0, 256;" ::"r"(1 + wg) : "memory");
    }
    mbar_wait(bars + B_COEF * 8, 0);
    const uint32_t ca = sb + OFF_COEF + (64 * wg + 8 * w + g) * 16;
    const uint32_t tag = __shfl_sync(0xffffffffu, lds32(bars + B_EPOCH * 8) & 3, 0);
    constexpr int RE = SWAPB ? 2 : 0, IM = 2 - RE;
    const int ct = lane >> 3;
    const uint2* cp = g_carry + __shfl_sync(0xffffffffu, ((16 * wg + 2 * j) * 16 + tc - 1 - ct) * 32 + 8 * w + (lane & 7), lane);
    unsigned long long cv[4];
    auto load_carry = [&](int i) {
#pragma unroll
      for (int m = 0; m < 4; m++)
        asm volatile("{\n.reg .pred p;\nsetp.lt.s32 p, %2, %3;\n@p ld.relaxed.gpu.global.b64 %0, [%1];\n}\n" : "=l"(cv[m]) : "l"(cp + 512 * i - 128 * m), "r"(ct + 4 * m), "r"(tc) : "memory");
    };
    float lr[2], li[2], pr[2], pi[2], wr[2], wi[2], vr[2], vi[2], qr[2], qi[2], er[2], ei[2], gr[2], gi[2];
    auto powers = [&](int i) {
      const uint2 cf = lds64(ca + 512 * i);
      pr[i] = lr[i] = __uint_as_float(cf.x); pi[i] = li[i] = __uint_as_float(cf.y);
#pragma unroll
      for (int s = 0; s < 4; s++) csq(pr[i], pi[i]);
      gr[i] = pr[i]; gi[i] = pi[i];
      csq(pr[i], pi[i]);
      qr[i] = pr[i]; qi[i] = pi[i];
      csq(qr[i], qi[i]);
      er[i] = qr[i]; ei[i] = qi[i];
      wr[i] = (c & 1) ? pr[i] : 1.f; wi[i] = (c & 1) ? pi[i] : 0.f;
      if (c & 2) { float x, y; cmul(wr[i], wi[i], qr[i], qi[i], x, y); wr[i] = x; wi[i] = y; }
      vr[i] = wr[i]; vi[i] = wi[i];
      csq(vr[i], vi[i]); csq(vr[i], vi[i]);
      csq(qr[i], qi[i]); csq(qr[i], qi[i]); csq(qr[i], qi[i]);
      const int src = 4 * (lane & 7) + ct;
      vr[i] = __shfl_sync(0xffffffffu, vr[i], src); vi[i] = __shfl_sync(0xffffffffu, vi[i], src);
      qr[i] = __shfl_sync(0xffffffffu, qr[i], src); qi[i] = __shfl_sync(0xffffffffu, qi[i], src);
      asm volatile("" : "+f"(wr[i]), "+f"(wi[i]), "+f"(pr[i]), "+f"(pi[i]), "+f"(er[i]), "+f"(ei[i]));
    };
    powers(0);
    if (POW2 == 0) powers(1);
    PMFENCE();
    wg_wait<0>();
    fence_regs<128>(d);
    release(po);
#pragma unroll
    for (int i = 0; i < 2; i++) {
      const float* e = d + 64 * i;
      auto chain = [&](int s0, int s1, float& sr, float& si) {
        sr = e[2 * s0 + RE]; si = e[2 * s0 + IM];
#pragma unroll
        for (int s = s0 + 1; s < s1; s++) {
          const int ia = 4 * (s >> 1) + (s & 1);
          const float nr = fmaf(-li[i], si, fmaf(lr[i], sr, e[ia + RE])), ni = fmaf(li[i], sr, fmaf(lr[i], si, e[ia + IM]));
          sr = nr; si = ni;
          if (i == 1 && C_AT > 1 && s == C_AT) { asm volatile("pmevent 0;" : "+f"(sr), "+f"(si)::"memory"); load_carry(0); }
        }
      };
      float sr, si;
      if (POW2 == 1 && i == 1) powers(1);
      if ((GREEDY >> i) & 1) {
        float ar, ai;
        chain(0, 16, ar, ai); chain(16, 32, sr, si);
        sr = fmaf(gr[i], ar, fmaf(-gi[i], ai, sr)); si = fmaf(gr[i], ai, fmaf(gi[i], ar, si));
      } else chain(0, 32, sr, si);
      if (i == 1 && C_AT == 0) { asm volatile("pmevent 0;" : "+f"(sr), "+f"(si)::"memory"); load_carry(0); }
      float ur = __shfl_up_sync(0xffffffffu, sr, 1, 4), ui = __shfl_up_sync(0xffffffffu, si, 1, 4);
      if (c >= 1) { sr = fmaf(pr[i], ur, fmaf(-pi[i], ui, sr)); si = fmaf(pr[i], ui, fmaf(pi[i], ur, si)); }
      ur = __shfl_up_sync(0xffffffffu, sr, 2, 4); ui = __shfl_up_sync(0xffffffffu, si, 2, 4);
      if (c >= 2) { sr = fmaf(er[i], ur, fmaf(-ei[i], ui, sr)); si = fmaf(er[i], ui, fmaf(ei[i], ur, si)); }
      ur = __shfl_sync(0xffffffffu, sr, 4 * lane + 3); ui = __shfl_sync(0xffffffffu, si, 4 * lane + 3);
      asm volatile("{\n.reg .pred p;\n.reg .b64 v;\nsetp.lt.u32 p, %3, 8;\nmov.b64 v, {%1,%2};\n@p st.relaxed.gpu.global.b64 [%0], v;\n}\n"
                   ::"l"(cp + 512 * i + 32), "r"((__float_as_uint(ur) & ~3u) | tag), "r"(__float_as_uint(ui)), "r"(lane) : "memory");
      if (i == 1 && C_AT == 1) load_carry(0);
      PMFENCE();
      er[i] = __shfl_up_sync(0xffffffffu, sr, 1, 4); ei[i] = __shfl_up_sync(0xffffffffu, si, 1, 4);
      if (c == 0) er[i] = ei[i] = 0.f;
    }
    uint4* hp = g_h + (32 * tc + 16 * wg + 2 * j) * 1024 + 64 * w + 4 * g + (c ^ (g >> 1));
#pragma unroll
    for (int i = 0; i < 2; i++) {
      float* e = d + 64 * i;
      const uint2 cf = lds64(ca + 512 * i + 8);
      const uint32_t gp = cf.x, gms = cf.y;
      PMFENCE();
      auto ready = [&]() {
        uint32_t bad = 0;
#pragma unroll
        for (int m = 0; m < 4; m++) if (ct + 4 * m < tc) bad |= (uint32_t)cv[m] ^ tag;
        return __all_sync(0xffffffffu, (bad & 3) == 0);
      };
      if (!ready()) {
        int n = 0;
#pragma unroll 1
        do load_carry(i); while (!ready() && ++n <= (SPIN_LIMIT << 4));
      }
      float hr = 0.f, hi = 0.f;
#pragma unroll
      for (int m = 3; m >= 0; m--) {
        const float x = __uint_as_float((uint32_t)cv[m]), y = __uint_as_float((uint32_t)(cv[m] >> 32));
        const float nr = m == 3 ? x : fmaf(qr[i], hr, fmaf(-qi[i], hi, x)), ni = m == 3 ? y : fmaf(qr[i], hi, fmaf(qi[i], hr, y));
        if (ct + 4 * m < tc) { hr = nr; hi = ni; }
      }
      { float x, y; cmul(hr, hi, vr[i], vi[i], x, y); hr = x; hi = y; }
      hr += __shfl_xor_sync(0xffffffffu, hr, 8); hi += __shfl_xor_sync(0xffffffffu, hi, 8);
      hr = __shfl_sync(0xffffffffu, hr, g) + __shfl_sync(0xffffffffu, hr, g + 16); hi = __shfl_sync(0xffffffffu, hi, g) + __shfl_sync(0xffffffffu, hi, g + 16);
      float sr = fmaf(wr[i], hr, fmaf(-wi[i], hi, er[i])), si = fmaf(wr[i], hi, fmaf(wi[i], hr, ei[i]));
#pragma unroll
      for (int i8 = 0; i8 < 4; i8++) {
        asm volatile("pmevent 0;" : "+f"(sr), "+f"(si)::"memory");
        if (i == 0 && i8 == C_AT2) load_carry(1);
#pragma unroll
        for (int s = 8 * i8; s < 8 * i8 + 8; s++) {
          const int ia = 4 * (s >> 1) + (s & 1);
          const float nr = fmaf(-li[i], si, fmaf(lr[i], sr, e[ia + RE])), ni = fmaf(li[i], sr, fmaf(lr[i], si, e[ia + IM]));
          sr = nr; si = ni;
          e[ia + RE] = nr; e[ia + IM] = ni;
        }
        if (P2_SPLIT) PMFENCE();
        uint32_t hp0[4], hp1[4];
#pragma unroll
        for (int m = 0; m < 4; m++) {
          const float* f = e + 16 * i8 + 4 * m;
          const uint32_t x = pack_bf16(f[RE], f[RE + 1]), y = pack_bf16(f[IM], f[IM + 1]);
          hp0[m] = bfma2(gp, x, bmul2(gms, y)); hp1[m] = bfnma2(gp, y, bmul2(gms, x));
        }
        uint4* o = hp + 512 * (i8 >> 1) + 256 * i + 32 * (i8 & 1);
        stg128(o, make_uint4(hp0[0], hp0[1], hp0[2], hp0[3]));
        stg128(o + 1024, make_uint4(hp1[0], hp1[1], hp1[2], hp1[3]));
      }
    }
    const int trow = 128 * tc + 64 * (w & 1) + 8 * (w >> 1) + g;
    const int dcol = 128 * j + 4 * c;
    asm volatile("bar.arrive %0, 160;" ::"r"(4 + wg) : "memory");
    if (wg == 0) {
      set_ra();
      uint2 xv[32];
      {
        const int gp = 2 * (g & 3) + (g >> 2);
        const uint32_t xa = sb + OFF_RING + (XPOS % STAGES) * STAGE_BYTES + (64 * (w & 1) + 8 * (w >> 1) + gp) * 128 + (c & 1) * 8;
        mbar_wait(bars + B_XI * 8, 0);
        mbar_wait(bars + (B_FULL + XPOS % STAGES) * 8, (XPOS / STAGES) & 1);
#pragma unroll
        for (int u = 0; u < 32; u++) {
          const int J = (u >> 1) & 7;
          asm volatile("ld.shared.v2.u32 {%0,%1}, [%2];" : "=r"(xv[u].x), "=r"(xv[u].y) : "r"(xa + (J >> 2) * 16384 + (u >> 4) * 2048 + (u & 1) * 4096 + (((2 * (J & 3) + (c >> 1)) ^ gp) << 4)) : "memory");
        }
        uint32_t dep = P.zero;
#pragma unroll
        for (int u = 0; u < 32; u++) dep &= xv[u].x;
        bar_sync(3 + dep, 128);
        release(8 * (XPOS % STAGES));
      }
#pragma unroll
      for (int J = 0; J < 8; J++) {
        const uint4 ds = lds128(sb + OFF_DS + 16 * c + 64 * J);
#pragma unroll
        for (int r = 0; r < 4; r++) {
          const int u = 16 * (r >> 1) + 2 * J + (r & 1);
          float* e = d + 8 * (u >> 1) + 2 * (u & 1);
          e[0] = __uint_as_float(bfma2(blo2(xv[u].x), ds.x, 0)); e[1] = __uint_as_float(bfma2(xv[u].x, ds.y, 0));
          e[4] = __uint_as_float(bfma2(blo2(xv[u].y), ds.z, 0)); e[5] = __uint_as_float(bfma2(xv[u].y, ds.w, 0));
        }
      }
      fence_regs<128>(d);
      so = 8 * (33 % STAGES); ph = (33 / STAGES) & 1; po = NOBAR;
      const uint64_t da0 = make_desc(sb + OFF_RING + 16384, 512, 1024, 2), db0 = make_desc(sb + OFF_RING, 16, 1024, 1);
      bar_sync(2, 256);
#pragma unroll 1
      for (int kb = 0; kb < QSW; kb++) block(std::integral_constant<int, 1>(), da0, db0, false, 32 + kb);
#pragma unroll 1
      for (int kb = QSW; kb < 32 - TAILB; kb++) block(std::integral_constant<int, 2>(), da0, db0, false, 32 + kb);
      float* op = P.out + (size_t)trow * 2048 + 1024 + dcol;
      auto mma = [&](int i, int kb, int k0, int k1) {
        const int s = (33 + kb) % STAGES;
        wg_fence();
#pragma unroll
        for (int k = k0; k < k1; k++) wgmma_n128<1>(d + 64 * i, da0 + s * 2048 + 512 * i + 128 * k, db0 + (i ? 0 : P.zero) + s * 2048 + 2 * k, 1);
        wg_commit();
      };
      auto store = [&](int i, int J0, int J1) {
#pragma unroll
        for (int J = J0; J < J1; J++) {
#pragma unroll
          for (int h = 0; h < 2; h++) {
            const float* e = d + 64 * i + 8 * J + 2 * h;
            stg128(op + (size_t)(16 * i + 32 * h) * 2048 + 16 * J, make_uint4(__float_as_uint(e[0]), __float_as_uint(e[1]), __float_as_uint(e[4]), __float_as_uint(e[5])));
          }
        }
        PMFENCE();
      };
      constexpr int K0 = 32 - TAILB;
#pragma unroll
      for (int kb = K0; kb < 32; kb++) {
        mbar_wait(bars + (B_FULL + (33 + kb) % STAGES) * 8, ((33 + kb) / STAGES) & 1);
        if (TAILB == 5 && kb == K0) { mma(0, kb, 0, 2); wg_wait<1>(); release(po); mma(0, kb, 2, 4); }
        else mma(0, kb, 0, 4);
      }
      mma(1, K0, 0, 4);
      wg_wait<1>();
      fence_regs<64>(d);
#pragma unroll
      for (int kb = K0 + 1; kb < 32; kb++) {
        mma(1, kb, 0, 4);
        if (T_FENCE) PMFENCE();
        store(0, T_ST * (kb - K0 - 1), kb == 31 ? 8 : T_ST * (kb - K0));
      }
      wg_wait<0>();
      fence_regs<64>(d + 64);
      store(1, 0, 8);
      if (t == 0) g_epoch[b * 32] = lds32(bars + B_EPOCH * 8);
      return;
    }
    asm volatile("setmaxnreg.dec.sync.aligned.u32 %0;" ::"n"(488 - 2 * GREG));
  }
  {
    int lane;
    asm volatile("mov.u32 %0, %%laneid;" : "=r"(lane));
    const int w = warp & 3, h = wg & 1;
    const int lc = 2 * (lane & 2) + (lane & 1) + ((lane >> 2) & 2);
    const bool own = ((lane >> 2) & 1) == rank, spare = !own && lc < 2;
    const uint32_t ya = (spare ? sb + OFF_IN + 96 + lc * 2064 : sb + OFF_U + (own ? 4 * rank * U_N8 : 4 * (rank ^ 1) * U_N8 - 2 * U_CH) + lc * U_CH) + w * 128 + (lane >> 4) * 16 + h * 64;
    const uint32_t ys = spare ? 512 : U_N8;
    const uint32_t ob0 = sb + (h ? OFF_F1 : OFF_K) + 1024 * w, ob1 = sb + (h ? OFF_VP : OFF_K + 4096) + 1024 * w;
    uint32_t y[2][8];
    uint2 q[4][4];
    auto get_q = [&](int n, int off, int bar, int ph) {
#pragma unroll
      for (int u = 0; u < 2; u++) {
        mbar_wait(bars + (bar + u) * 8, ph);
#pragma unroll
        for (int r = 0; r < 4; r++) q[n + u][r] = lds64(sb + off + 4096 * u + 1024 * w + 256 * r + 8 * lane);
      }
    };
    auto get_y = [&](int n) { ldsm4t(y[n & 1], ya + n * ys); ldsm4t(y[n & 1] + 4, ya + n * ys + 32); };
    if (h) {
#pragma unroll
      for (int n = 0; n < 4; n += 2) {
        get_q(n, OFF_Q, B_QF, n >> 1);
        uint32_t dep = P.zero;
#pragma unroll
        for (int r = 0; r < 8; r++) dep &= q[n + (r >> 2)][r & 3].x;
        bar_sync(6 + dep, 128);
        if (Q_HOLD && n == 0) mbar_wait(bars + B_HP * 8, 1);
        if (w < 2 && elect_one()) load_q(5 + 2 * w - (n >> 1), OFF_Q, B_QF + n);
        __syncwarp();
      }
#pragma unroll 1
      for (int r = 0; r < 6; r++) mbar_wait(bars + (B_IN + r) * 8, 0);
      bar_sync(9, 256);
    } else get_q(0, OFF_K, B_KF, 0);
    if (O_WAIT) mbar_wait(bars + (O_WAIT == 1 ? B_HP : B_HR) * 8, 1);
    mbar_wait(bars + (B_IN + 6) * 8, 0);
    get_y(0);
    uint32_t oc = clk32() + (2 * w + h) * (O_PACE / 2);
#pragma unroll
    for (int n = 0; n < 4; n++) {
      uint32_t* o = y[n & 1];
#pragma unroll
      for (int r = 0; r < 4; r++) { o[2 * r] = bmul2(o[2 * r], q[n][r].x); o[2 * r + 1] = bmul2(o[2 * r + 1], q[n][r].y); }
#pragma unroll
      for (int u = 0; u < 2; u++) {
        const uint32_t ob = u ? ob1 : ob0;
        if (n > 0 && lane == 0) asm volatile("cp.async.bulk.wait_group.read 1;" ::: "memory");
        __syncwarp();
#pragma unroll
        for (int r = 2 * u; r < 2 * u + 2; r++)
          sts128(ob + (r & 1) * 512 + lane * 16, make_uint4(o[2 * r] << 16, o[2 * r] & 0xffff0000u, o[2 * r + 1] << 16, o[2 * r + 1] & 0xffff0000u));
        if (O_PACE) { while ((int)(clk32() - oc) < 0) { if (O_SLEEP) __nanosleep(O_SLEEP); } }
        oc += 4 * O_PACE;
        fence_proxy_async_smem();
        __syncwarp();
        if (lane == 0)
          asm volatile("cp.async.bulk.tensor.3d.global.shared::cta.bulk_group [%0, {%2, %3, %4}], [%1];\ncp.async.bulk.commit_group;"
                       ::"l"(&mO), "r"(ob), "r"(32 * slot), "r"(32 * rank + 8 * w), "r"(8 * n + 4 * h + 2 * u) : "memory");
        __syncwarp();
        if (u == 0 && n < 3) get_y(n + 1);
        if (u == 0 && n == 1 && !h) get_q(2, OFF_Q, B_QF + 2, 0);
      }
    }
    if (warp == 8 && lane == 0) mbar_arrive_cta(bars + B_ACK * 8, rank ^ 1);
    if (lane == 0) asm volatile("cp.async.bulk.wait_group 0;" ::: "memory");
    mbar_wait(bars + B_ACK * 8, 0);
  }
}

typedef CUresult (*EncodeFn)(CUtensorMap*, CUtensorMapDataType, cuuint32_t, void*, const cuuint64_t*, const cuuint64_t*, const cuuint32_t*,
                             const cuuint32_t*, CUtensorMapInterleave, CUtensorMapSwizzle, CUtensorMapL2promotion, CUtensorMapFloatOOBfill);

bool encode(EncodeFn fn, CUtensorMap* m, int rank, const void* base, const cuuint64_t* dims, const cuuint64_t* strides, const cuuint32_t* box, CUtensorMapSwizzle swz,
            CUtensorMapL2promotion promo = CU_TENSOR_MAP_L2_PROMOTION_L2_128B) {
  const cuuint32_t es[5] = {1, 1, 1, 1, 1};
  return fn(m, CU_TENSOR_MAP_DATA_TYPE_BFLOAT16, rank, const_cast<void*>(base), dims, strides, box, es, CU_TENSOR_MAP_INTERLEAVE_NONE, swz,
            promo, CU_TENSOR_MAP_FLOAT_OOB_FILL_NONE) == CUDA_SUCCESS;
}

}

extern "C" void kernel_launch(void* const* d_in, const int* in_sizes, int n_in, void* d_out, int out_size) {
  (void)in_sizes; (void)n_in; (void)out_size;
  typedef const __nv_bfloat16* In;
  const In q = (In)d_in[0], k = (In)d_in[1], v = (In)d_in[2], ssm_k = (In)d_in[4], x = (In)d_in[6], B_re = (In)d_in[9], B_im = (In)d_in[10], C_re = (In)d_in[11], C_im = (In)d_in[12];
  Params P = {};
  P.shift_k = (In)d_in[3]; P.ssm_D = (In)d_in[5]; P.lam_re = (In)d_in[7]; P.lam_im = (In)d_in[8]; P.log_dt = (In)d_in[13]; P.Dskip = (In)d_in[14];
  P.out = (float*)d_out;
  for (int cl = 0; cl < 64; cl++) P.slot[cl >> 2] |= (cl < 4 ? 4 + cl : cl < 36 ? 8 * ((cl - 4) & 7) + ((cl - 4) >> 3) : 8 * (1 + (cl - 36) % 7) + 4 + (cl - 36) / 7) << (8 * (cl & 3));
  const bool swapB = (uintptr_t)B_im < (uintptr_t)B_re;

  EncodeFn fn = nullptr;
  cudaDriverEntryPointQueryResult qr;
  cudaGetDriverEntryPoint("cuTensorMapEncodeTiled", (void**)&fn, cudaEnableDefault, &qr);
  if (!fn) return;

  CUtensorMap mX, mB, mCre, mCim, mXs, mK, mV, mQ, mS, mO;
  bool ok = true;
  {
    const cuuint64_t dims[4] = {1024, 2, 64, 16}, str[3] = {2048, 32 * 2048, 2 * 2048};
    const cuuint32_t box[4] = {64, 2, 4, 16};
    ok &= encode(fn, &mX, 4, x, dims, str, box, CU_TENSOR_MAP_SWIZZLE_128B, (CUtensorMapL2promotion)X_PROMO);
  }
  {
    const uintptr_t lo = swapB ? (uintptr_t)B_im : (uintptr_t)B_re, hi = swapB ? (uintptr_t)B_re : (uintptr_t)B_im;
    const cuuint64_t dims[4] = {1024, 8, 2, 128}, str[3] = {2048, (cuuint64_t)(hi - lo), 8 * 2048};
    const cuuint32_t box[4] = {64, 8, 2, 4};
    ok &= encode(fn, &mB, 4, (const void*)lo, dims, str, box, CU_TENSOR_MAP_SWIZZLE_128B, (CUtensorMapL2promotion)B_PROMO);
  }
  {
    const cuuint64_t dims[5] = {1024, 2, 4, 2, 64}, str[4] = {2048, 4 * 2048, 2 * 2048, 16 * 2048};
    const cuuint32_t box[5] = {64, 2, 4, 2, 4};
    ok &= encode(fn, &mCre, 5, C_re, dims, str, box, CU_TENSOR_MAP_SWIZZLE_128B, (CUtensorMapL2promotion)C_PROMO);
    ok &= encode(fn, &mCim, 5, C_im, dims, str, box, CU_TENSOR_MAP_SWIZZLE_128B, (CUtensorMapL2promotion)C_PROMO);
  }
  {
    const cuuint64_t dims[4] = {1024, 2, 4, 256}, str[3] = {4 * 2048, 2048, 8 * 2048};
    const cuuint32_t box[4] = {64, 2, 4, 16};
    ok &= encode(fn, &mXs, 4, x, dims, str, box, CU_TENSOR_MAP_SWIZZLE_128B);
  }
  {
    const cuuint64_t dims[3] = {1024, 64, 32}, str[2] = {32 * 2048, 2048};
    const cuuint32_t box[3] = {16, 32, 4};
    const cuuint64_t dimq[4] = {1024, 8, 32, 8}, strq[3] = {32 * 2048, 2048, 256 * 2048};
    const cuuint32_t boxq[4] = {16, 8, 4, 4};
    ok &= encode(fn, &mQ, 4, q, dimq, strq, boxq, CU_TENSOR_MAP_SWIZZLE_NONE, (CUtensorMapL2promotion)Q_PROMO);
    ok &= encode(fn, &mK, 3, k, dims, str, box, CU_TENSOR_MAP_SWIZZLE_32B, (CUtensorMapL2promotion)KV_PROMO);
    ok &= encode(fn, &mV, 3, v, dims, str, box, CU_TENSOR_MAP_SWIZZLE_32B, (CUtensorMapL2promotion)KV_PROMO);
  }
  {
    const cuuint64_t dims[2] = {32, 65536}, str[1] = {64};
    const cuuint32_t box[2] = {32, 64};
    ok &= encode(fn, &mS, 2, ssm_k, dims, str, box, CU_TENSOR_MAP_SWIZZLE_64B, (CUtensorMapL2promotion)S_PROMO);
  }
  {
    const cuuint64_t dims[3] = {2048, 64, 32}, str[2] = {32 * 8192, 8192};
    const cuuint32_t box[3] = {32, 8, 2};
    ok &= encode(fn, &mO, 3, d_out, dims, str, box, CU_TENSOR_MAP_SWIZZLE_NONE);
  }
  if (!ok) return;
  auto kern = swapB ? fused_kernel<1> : fused_kernel<0>;
  cudaFuncSetAttribute(kern, cudaFuncAttributeMaxDynamicSharedMemorySize, SMEM_BYTES);
  kern<<<NCTA, 512, SMEM_BYTES, cudaStreamPerThread>>>(P, mX, mB, mCre, mCim, mXs, mK, mV, mQ, mS, mO);
}
```

```cpp
#include <cuda_runtime.h>
#include <cuda_bf16.h>
#include <cuda.h>
#include <stdint.h>
#include <type_traits>

namespace {

constexpr int D_DIM = 1024;
constexpr int NCTA = 128;

constexpr int STAGES = 5, STAGE_BYTES = 32768;
constexpr int OFF_RING = 0;
constexpr int OFF_F1 = STAGES * STAGE_BYTES, OFF_F2 = OFF_F1 + 4096, OFF_K = OFF_F2 + 2048, OFF_VP = OFF_K + 8192, OFF_Q = OFF_VP + 4096, OFF_IN = OFF_Q + 8192;
constexpr int OFF_KV = OFF_K;
constexpr int U_CH = 528, U_N8 = 8 * U_CH, OFF_U = OFF_IN + U_N8;
constexpr int OFF_COEF = OFF_U + 8 * U_N8;
constexpr int OFF_DS = OFF_COEF + 2048, OFF_D = OFF_DS + 512;
constexpr int OFF_BAR = OFF_D + 64;
constexpr int SMEM_BYTES = OFF_BAR + 512;
static_assert(SMEM_BYTES <= 232448 && OFF_K % 1024 == 0 && (OFF_U + 3 * U_N8) % 512 == 0 && (4 * U_N8) % 512 == 0, "smem map");
constexpr int B_FULL = 0, B_XI = 5, B_HR = 6, B_HP = 7, B_KVF = 8, B_KF = 11, B_KE = 13, B_QF = 15, B_IN = 19, B_UF = 27, B_Y = 31, B_ACK = 36,
              B_EMPTY = 38, B_COEF = 43, B_KVE = 44, B_NONE = 47, B_EPOCH = 48;
constexpr int QD1 = 8;
constexpr int QD2 = 2;
constexpr int QD3 = 8;
constexpr int QSW = 16;
constexpr int HEAD = 3;
constexpr int ST_T0 = 200;
constexpr int ST_DELAY = 300;
constexpr int XPOS = 28;
constexpr int K_T0 = 800;
constexpr int KV_T0 = 1500;
constexpr int KV_DT = 560;
constexpr int KV_DV = 100;
constexpr int POLL_NS = 30;
constexpr int GREEDY = 1;
constexpr int TAILB = 5;
constexpr int GREG = 176;
constexpr int COEF_T0 = 2500;
constexpr int T_ST = 2;
constexpr int PFC_T0 = 13500;
constexpr int PFC_T1 = 1500;
constexpr int PFC_DT = 400;
constexpr int CFM = 0x40f1;
constexpr int SPIN_LIMIT = 1 << 14;

struct Params {
  unsigned slot[16];
  unsigned zero;
  const __nv_bfloat16 *shift_k, *ssm_D, *lam_re, *lam_im, *log_dt, *Dskip;
  float* out;
};

__device__ __align__(1024) uint4 g_h[16 * 32 * 1024];
__device__ __align__(128) uint2 g_carry[32 * 16 * 32];
__device__ unsigned g_flagH[2 * 16 * 32];
__device__ unsigned g_epoch[NCTA * 32];

__device__ __forceinline__ uint64_t make_desc(uint32_t addr, uint32_t lbo, uint32_t sbo, uint32_t swz) {
  return (uint64_t)((addr & 0x3FFFF) >> 4) | ((uint64_t)(lbo >> 4) << 16) | ((uint64_t)(sbo >> 4) << 32) | ((uint64_t)swz << 62);
}
__device__ __forceinline__ void wg_fence() { asm volatile("wgmma.fence.sync.aligned;" ::: "memory"); }
__device__ __forceinline__ void wg_commit() { asm volatile("wgmma.commit_group.sync.aligned;" ::: "memory"); }
template <int N> __device__ __forceinline__ void wg_wait() { asm volatile("wgmma.wait_group.sync.aligned %0;" ::"n"(N) : "memory"); }
__device__ __forceinline__ void mbar_init(uint32_t bar, int cnt) { asm volatile("mbarrier.init.shared::cta.b64 [%0], %1;" ::"r"(bar), "r"(cnt) : "memory"); }
__device__ __forceinline__ void mbar_expect(uint32_t bar, uint32_t bytes) { asm volatile("mbarrier.arrive.expect_tx.shared::cta.b64 _, [%0], %1;" ::"r"(bar), "r"(bytes) : "memory"); }
__device__ __forceinline__ bool mbar_try(uint32_t bar, uint32_t parity) {
  uint32_t ok;
  asm volatile("{\n.reg .pred p;\nmbarrier.try_wait.parity.shared::cta.b64 p, [%1], %2;\nselp.u32 %0, 1, 0, p;\n}\n" : "=r"(ok) : "r"(bar), "r"(parity) : "memory");
  return ok;
}
__device__ __forceinline__ void mbar_wait(uint32_t bar, uint32_t parity) {
  if (__builtin_expect(!mbar_try(bar, parity), 0)) {
#pragma unroll 1
    for (int n = 0; n < SPIN_LIMIT && !mbar_try(bar, parity); n++) {}
  }
}
__device__ __forceinline__ void mbar_arrive(uint32_t bar) { asm volatile("mbarrier.arrive.shared::cta.b64 _, [%0];" ::"r"(bar) : "memory"); }
__device__ __forceinline__ void mbar_arrive_cta(uint32_t bar, uint32_t cta) {
  asm volatile("{\n.reg .b32 ra;\nmapa.shared::cluster.u32 ra, %0, %1;\nmbarrier.arrive.shared::cluster.b64 _, [ra];\n}\n" ::"r"(bar), "r"(cta) : "memory");
}
__device__ __forceinline__ bool elect_one() {
  uint32_t p;
  asm volatile("{\n.reg .pred P;\nelect.sync _|P, 0xffffffff;\nselp.u32 %0, 1, 0, P;\n}\n" : "=r"(p));
  return p != 0;
}
__device__ __forceinline__ void bar_sync(int id, int n) { asm volatile("bar.sync %0, %1;" ::"r"(id), "r"(n) : "memory"); }
#define TMA_LD(dim) "cp.async.bulk.tensor." dim ".shared::cluster.global.mbarrier::complete_tx::bytes"
__device__ __forceinline__ void tma2d(uint32_t dst, const CUtensorMap* m, int c0, int c1, uint32_t bar) {
  asm volatile(TMA_LD("2d") " [%0], [%1, {%3, %4}], [%2];" ::"r"(dst), "l"(m), "r"(bar), "r"(c0), "r"(c1) : "memory");
}
__device__ __forceinline__ void tma3d(uint32_t dst, const CUtensorMap* m, int c0, int c1, int c2, uint32_t bar) {
  asm volatile(TMA_LD("3d") " [%0], [%1, {%3, %4, %5}], [%2];" ::"r"(dst), "l"(m), "r"(bar), "r"(c0), "r"(c1), "r"(c2) : "memory");
}
__device__ __forceinline__ void tma4d(uint32_t dst, const CUtensorMap* m, int c0, int c1, int c2, int c3, uint32_t bar) {
  asm volatile(TMA_LD("4d") " [%0], [%1, {%3, %4, %5, %6}], [%2];" ::"r"(dst), "l"(m), "r"(bar), "r"(c0), "r"(c1), "r"(c2), "r"(c3) : "memory");
}
__device__ __forceinline__ void tma4d_mc(uint32_t dst, const CUtensorMap* m, int c0, int c1, int c2, int c3, uint32_t bar) {
  asm volatile(TMA_LD("4d") ".multicast::cluster [%0], [%1, {%3, %4, %5, %6}], [%2], %7;" ::"r"(dst), "l"(m), "r"(bar), "r"(c0), "r"(c1), "r"(c2), "r"(c3), "h"((uint16_t)3) : "memory");
}
__device__ __forceinline__ void tma5d_mc(uint32_t dst, const CUtensorMap* m, int c0, int c1, int c2, int c3, int c4, uint32_t bar) {
  asm volatile(TMA_LD("5d") ".multicast::cluster [%0], [%1, {%3, %4, %5, %6, %7}], [%2], %8;" ::"r"(dst), "l"(m), "r"(bar), "r"(c0), "r"(c1), "r"(c2), "r"(c3), "r"(c4), "h"((uint16_t)3) : "memory");
}
__device__ __forceinline__ void bulk_load(uint32_t dst, const void* src, uint32_t bytes, uint32_t bar) {
  asm volatile("cp.async.bulk.shared::cluster.global.mbarrier::complete_tx::bytes [%0], [%1], %2, [%3];" ::"r"(dst), "l"(src), "r"(bytes), "r"(bar) : "memory");
}
__device__ __forceinline__ void bulk_send(uint32_t dst, uint32_t src, uint32_t bytes, uint32_t bar, uint32_t cta) {
  asm volatile("{\n.reg .b32 rd, rb;\nmapa.shared::cluster.u32 rd, %0, %3;\nmapa.shared::cluster.u32 rb, %2, %3;\n"
               "cp.async.bulk.shared::cluster.shared::cta.mbarrier::complete_tx::bytes [rd], [%1], %4, [rb];\n}\n"
               ::"r"(dst), "r"(src), "r"(bar), "r"(cta), "r"(bytes) : "memory");
}
__device__ __forceinline__ void fence_proxy_async_smem() { asm volatile("fence.proxy.async.shared::cta;" ::: "memory"); }
__device__ __forceinline__ void fence_proxy_async_global() { asm volatile("fence.proxy.async.global;" ::: "memory"); }
__device__ __forceinline__ uint32_t clk32() { uint32_t c; asm volatile("mov.u32 %0, %%clock;" : "=r"(c)::"memory"); return c; }
__device__ __forceinline__ void wait_until(uint32_t t0, uint32_t dt) { while (clk32() - t0 < dt) __nanosleep(32); }
__device__ __forceinline__ void spin_until(uint32_t t0, uint32_t dt) { while (clk32() - t0 < dt) {} }
__device__ __forceinline__ void prefetch_map(const CUtensorMap* m) { asm volatile("prefetch.tensormap [%0];" ::"l"(m) : "memory"); }
__device__ __forceinline__ void prefetch_line(const void* p) { asm volatile("prefetch.global.L2 [%0];" ::"l"(p) : "memory"); }
__device__ __forceinline__ unsigned ld_acquire(const unsigned* p) { unsigned v; asm volatile("ld.acquire.gpu.global.u32 %0, [%1];" : "=r"(v) : "l"(p) : "memory"); return v; }
__device__ __forceinline__ unsigned ld_relaxed(const unsigned* p) { unsigned v; asm volatile("ld.relaxed.gpu.global.u32 %0, [%1];" : "=r"(v) : "l"(p) : "memory"); return v; }
__device__ __forceinline__ uint32_t lds32(uint32_t a) { uint32_t v; asm volatile("ld.shared.u32 %0, [%1];" : "=r"(v) : "r"(a)); return v; }
__device__ __forceinline__ uint2 lds64(uint32_t a) { uint2 v; asm volatile("ld.shared.v2.u32 {%0,%1}, [%2];" : "=r"(v.x), "=r"(v.y) : "r"(a) : "memory"); return v; }
__device__ __forceinline__ uint4 lds128(uint32_t a) { uint4 v; asm volatile("ld.shared.v4.u32 {%0,%1,%2,%3}, [%4];" : "=r"(v.x), "=r"(v.y), "=r"(v.z), "=r"(v.w) : "r"(a) : "memory"); return v; }
__device__ __forceinline__ void sts32(uint32_t a, uint32_t v) { asm volatile("st.shared.u32 [%0], %1;" ::"r"(a), "r"(v) : "memory"); }
__device__ __forceinline__ void sts128(uint32_t a, uint4 v) { asm volatile("st.shared.v4.u32 [%0], {%1,%2,%3,%4};" ::"r"(a), "r"(v.x), "r"(v.y), "r"(v.z), "r"(v.w) : "memory"); }
__device__ __forceinline__ void ldsm4(uint32_t* r, uint32_t a) { asm volatile("ldmatrix.sync.aligned.m8n8.x4.shared.b16 {%0,%1,%2,%3}, [%4];" : "=r"(r[0]), "=r"(r[1]), "=r"(r[2]), "=r"(r[3]) : "r"(a) : "memory"); }
__device__ __forceinline__ void ldsm4t(uint32_t* r, uint32_t a) { asm volatile("ldmatrix.sync.aligned.m8n8.x4.trans.shared.b16 {%0,%1,%2,%3}, [%4];" : "=r"(r[0]), "=r"(r[1]), "=r"(r[2]), "=r"(r[3]) : "r"(a) : "memory"); }
__device__ __forceinline__ void stsm4t(uint32_t a, uint32_t r0, uint32_t r1, uint32_t r2, uint32_t r3) {
  asm volatile("stmatrix.sync.aligned.m8n8.x4.trans.shared.b16 [%0], {%1,%2,%3,%4};" ::"r"(a), "r"(r0), "r"(r1), "r"(r2), "r"(r3) : "memory");
}
__device__ __forceinline__ uint4 ldg128_nc(const void* p) { uint4 v; asm volatile("ld.global.nc.L1::no_allocate.v4.u32 {%0,%1,%2,%3}, [%4];" : "=r"(v.x), "=r"(v.y), "=r"(v.z), "=r"(v.w) : "l"(p)); return v; }
__device__ __forceinline__ void stg128(void* p, uint4 v) { asm volatile("st.global.L1::no_allocate.v4.u32 [%0], {%1,%2,%3,%4};" ::"l"(p), "r"(v.x), "r"(v.y), "r"(v.z), "r"(v.w) : "memory"); }
__device__ __forceinline__ uint32_t pack_bf16(float lo, float hi) { uint32_t r; asm("cvt.rn.bf16x2.f32 %0, %1, %2;" : "=r"(r) : "f"(hi), "f"(lo)); return r; }
__device__ __forceinline__ uint32_t bmul2(uint32_t a, uint32_t b) { uint32_t r; asm("mul.rn.bf16x2 %0, %1, %2;" : "=r"(r) : "r"(a), "r"(b)); return r; }
__device__ __forceinline__ uint32_t bfma2(uint32_t a, uint32_t b, uint32_t c) { uint32_t r; asm("fma.rn.bf16x2 %0, %1, %2, %3;" : "=r"(r) : "r"(a), "r"(b), "r"(c)); return r; }
__device__ __forceinline__ uint32_t blo2(uint32_t a) { uint32_t r; asm("{\n.reg .b16 l, h;\nmov.b32 {l, h}, %1;\nmov.b32 %0, {l, l};\n}" : "=r"(r) : "r"(a)); return r; }
__device__ __forceinline__ float bf2f(__nv_bfloat16 v) { return __bfloat162float(v); }

#define R8(d, o) "+f"(d[o]), "+f"(d[o + 1]), "+f"(d[o + 2]), "+f"(d[o + 3]), "+f"(d[o + 4]), "+f"(d[o + 5]), "+f"(d[o + 6]), "+f"(d[o + 7])
#define R16(d, o) R8(d, o), R8(d, o + 8)
#define R64(d, o) R16(d, o), R16(d, o + 16), R16(d, o + 32), R16(d, o + 48)
template <int TA> __device__ __forceinline__ void wgmma_n128(float* d, uint64_t da, uint64_t db, int scale_d) {
  asm volatile("{\n.reg .pred p;\nsetp.ne.b32 p, %66, 0;\n"
    "wgmma.mma_async.sync.aligned.m64n128k16.f32.bf16.bf16 {"
    "%0,%1,%2,%3,%4,%5,%6,%7,%8,%9,%10,%11,%12,%13,%14,%15,%16,%17,%18,%19,%20,%21,%22,%23,%24,%25,%26,%27,%28,%29,%30,%31,"
    "%32,%33,%34,%35,%36,%37,%38,%39,%40,%41,%42,%43,%44,%45,%46,%47,%48,%49,%50,%51,%52,%53,%54,%55,%56,%57,%58,%59,%60,%61,%62,%63"
    "}, %64, %65, p, 1, 1, %67, 0;\n}\n"
    : R64(d, 0)
    : "l"(da), "l"(db), "r"(scale_d), "n"(TA));
}
template <int N> __device__ __forceinline__ void fence_regs(float* d) {
#pragma unroll
  for (int i = 0; i < N; i++) asm volatile("" : "+f"(d[i])::"memory");
}
#define PMFENCE() asm volatile("pmevent 0;" ::: "memory")
__device__ __forceinline__ void cmul(float ar, float ai, float br, float bi, float& cr, float& ci) {
  cr = ar * br - ai * bi; ci = ar * bi + ai * br;
}
__device__ __forceinline__ void csq(float& r, float& i) { const float x = fmaf(r, r, -i * i), y = r * i; r = x; i = y + y; }

#define W8(d, o) "=f"(d[o]), "=f"(d[o + 1]), "=f"(d[o + 2]), "=f"(d[o + 3]), "=f"(d[o + 4]), "=f"(d[o + 5]), "=f"(d[o + 6]), "=f"(d[o + 7])
#define L16 "{%0,%1,%2,%3,%4,%5,%6,%7,%8,%9,%10,%11,%12,%13,%14,%15}"
#define L32 "{%0,%1,%2,%3,%4,%5,%6,%7,%8,%9,%10,%11,%12,%13,%14,%15,%16,%17,%18,%19,%20,%21,%22,%23,%24,%25,%26,%27,%28,%29,%30,%31}"
template <int ACC, int TB> __device__ __forceinline__ void rs_n32(float* d, const uint32_t* a, uint64_t db) {
  if constexpr (ACC) asm volatile("wgmma.mma_async.sync.aligned.m64n32k16.f32.bf16.bf16 " L16 ", {%16,%17,%18,%19}, %20, 1, 1, 1, %21;" : R16(d, 0) : "r"(a[0]), "r"(a[1]), "r"(a[2]), "r"(a[3]), "l"(db), "n"(TB));
  else asm volatile("wgmma.mma_async.sync.aligned.m64n32k16.f32.bf16.bf16 " L16 ", {%16,%17,%18,%19}, %20, 0, 1, 1, %21;" : W8(d, 0), W8(d, 8) : "r"(a[0]), "r"(a[1]), "r"(a[2]), "r"(a[3]), "l"(db), "n"(TB));
}
template <int ACC, int TB> __device__ __forceinline__ void ss_n64(float* d, uint64_t da, uint64_t db) {
  if constexpr (ACC) asm volatile("wgmma.mma_async.sync.aligned.m64n64k16.f32.bf16.bf16 " L32 ", %32, %33, 1, 1, 1, 0, %34;" : R16(d, 0), R16(d, 16) : "l"(da), "l"(db), "n"(TB));
  else asm volatile("wgmma.mma_async.sync.aligned.m64n64k16.f32.bf16.bf16 " L32 ", %32, %33, 0, 1, 1, 0, %34;" : W8(d, 0), W8(d, 8), W8(d, 16), W8(d, 24) : "l"(da), "l"(db), "n"(TB));
}
template <int ACC> __device__ __forceinline__ void ss_n32_tt(float* d, uint64_t da, uint64_t db) {
  if constexpr (ACC) asm volatile("wgmma.mma_async.sync.aligned.m64n32k16.f32.bf16.bf16 " L16 ", %16, %17, 1, 1, 1, 1, 1;" : R16(d, 0) : "l"(da), "l"(db));
  else asm volatile("wgmma.mma_async.sync.aligned.m64n32k16.f32.bf16.bf16 " L16 ", %16, %17, 0, 1, 1, 1, 1;" : W8(d, 0), W8(d, 8) : "l"(da), "l"(db));
}
__device__ __forceinline__ void stsm4(uint32_t a, uint32_t r0, uint32_t r1, uint32_t r2, uint32_t r3) {
  asm volatile("stmatrix.sync.aligned.m8n8.x4.shared.b16 [%0], {%1,%2,%3,%4};" ::"r"(a), "r"(r0), "r"(r1), "r"(r2), "r"(r3) : "memory");
}
template <int N> __device__ __forceinline__ void fence_u32(uint32_t* d) {
#pragma unroll
  for (int i = 0; i < N; i++) asm volatile("" : "+r"(d[i])::"memory");
}
__device__ __forceinline__ void pack32(uint32_t* f, const float* z) {
#pragma unroll
  for (int i = 0; i < 16; i++) f[i] = pack_bf16(z[2 * i], z[2 * i + 1]);
}
template <int INV> __device__ __forceinline__ void twiddle(uint32_t* f, const uint32_t* tp, const uint32_t* ts) {
#pragma unroll
  for (int i = 0; i < 8; i++) {
    uint32_t x = f[2 * i + INV], y = f[2 * i + 1 - INV];
    x = bfma2(tp[i & 3], y, x); y = bfma2(ts[i & 3], x, y); x = bfma2(tp[i & 3], y, x);
    f[2 * i + INV] = x; f[2 * i + 1 - INV] = y;
  }
}
__device__ __forceinline__ uint32_t bfnma2(uint32_t a, uint32_t b, uint32_t c) { uint32_t r; asm("{\n.reg .b32 t;\nmul.bf16x2 t, %1, %2;\nsub.bf16x2 %0, %3, t;\n}" : "=r"(r) : "r"(a), "r"(b), "r"(c)); return r; }
__device__ __forceinline__ uint32_t bfms2(uint32_t a, uint32_t b, uint32_t c) { uint32_t r; asm("{\n.reg .b32 t;\nmul.bf16x2 t, %1, %2;\nsub.bf16x2 %0, t, %3;\n}" : "=r"(r) : "r"(a), "r"(b), "r"(c)); return r; }
template <int ADD> __device__ __forceinline__ void bimac(uint32_t* o, const uint32_t* a, const uint32_t* b, const uint32_t* c) {
#pragma unroll
  for (int J = 0; J < 2; J++) {
    const uint32_t Pr = a[2 * J], Pi = a[2 * J + 1], Qr = a[2 * J + 4], Qi = a[2 * J + 5], pr = b[2 * J], pi = b[2 * J + 1], qr = b[2 * J + 4], qi = b[2 * J + 5];
    uint32_t x0, x1, x2, x3;
    if (ADD == 0) { x0 = bmul2(Pr, pr); x1 = bmul2(Pr, pi); x2 = bmul2(Pr, qr); x3 = bmul2(Pr, qi); }
    if (ADD == 1) { x0 = bfma2(Pr, pr, c[2 * J]); x1 = bfma2(Pr, pi, c[2 * J + 1]); x2 = bfma2(Pr, qr, c[2 * J + 4]); x3 = bfma2(Pr, qi, c[2 * J + 5]); }
    if (ADD == 2) { x0 = bfma2(Pr, pr, c[2 * J + 1]); x1 = bfms2(Pr, pi, c[2 * J]); x2 = bfma2(Pr, qr, c[2 * J + 5]); x3 = bfms2(Pr, qi, c[2 * J + 4]); }
    x0 = bfnma2(Pi, pi, x0); x1 = bfma2(Pi, pr, x1); x2 = bfnma2(Pi, qi, x2); x3 = bfma2(Pi, qr, x3);
    x0 = bfnma2(Qr, qr, x0); x1 = bfnma2(Qr, qi, x1); x2 = bfma2(Qr, pr, x2); x3 = bfma2(Qr, pi, x3);
    x0 = bfma2(Qi, qi, x0); x1 = bfnma2(Qi, qr, x1); x2 = bfnma2(Qi, pi, x2); x3 = bfma2(Qi, pr, x3);
    o[2 * J] = x0; o[2 * J + 1] = x1; o[2 * J + 4] = x2; o[2 * J + 5] = x3;
  }
}
__device__ __forceinline__ void sincos8k(int n, float& s, float& c) {
  const float x = (float)((n << 19) >> 19) * (6.283185307179586f / 8192.f);
  s = __sinf(x); c = __cosf(x);
}
__device__ __forceinline__ void fft_tables(uint32_t f1a, uint32_t f2a, int w, int lane, uint32_t* tp, uint32_t* ts, float& d0r, float& d0i) {
  const int c = lane & 3, f1 = 8 * w + (lane >> 2);
#pragma unroll 1
  for (int J = 3; J >= 0; J--) {
    const int a = 8 * J + 2 * c;
    float s0, c0, s1, c1;
    sincos8k(64 * (4 * f1 + 1) * a + 31 * (4 * f1 - 63), d0i, d0r); sincos8k(64 * (4 * f1 + 1) * (a + 1) + 31 * (4 * f1 - 63), s1, c1);
    d0r *= 0.125f; d0i *= 0.125f;
    sts32(f1a + w * 1024 + J * 128 + lane * 4, pack_bf16(d0r, 0.125f * c1)); sts32(f1a + w * 1024 + 512 + J * 128 + lane * 4, pack_bf16(d0i, 0.125f * s1));
    sincos8k(128 * (2 * (a & 15) + 1) * f1 - 128 * (a & 16), s0, c0); sincos8k(128 * (2 * (a & 15) + 3) * f1 - 128 * (a & 16), s1, c1);
    sts32(f2a + w * 512 + J * 128 + lane * 4, pack_bf16(c0, c1));
    sincos8k((4 * f1 - 63) * (2 * a - 31), s0, c0); sincos8k((4 * f1 - 63) * (2 * a - 29), s1, c1);
#pragma unroll
    for (int i = 3; i > 0; i--) { ts[i] = ts[i - 1]; tp[i] = tp[i - 1]; }
    ts[0] = pack_bf16(s0, s1); tp[0] = pack_bf16(-__fdividef(s0, 1.f + c0), -__fdividef(s1, 1.f + c1));
  }
  if (c != 0) d0r = d0i = 0.f;
}

template <int SWAPB>
__global__ void __cluster_dims__(2, 1, 1) __launch_bounds__(512, 1)
fused_kernel(const __grid_constant__ Params P, const __grid_constant__ CUtensorMap mX, const __grid_constant__ CUtensorMap mB,
             const __grid_constant__ CUtensorMap mCre, const __grid_constant__ CUtensorMap mCim, const __grid_constant__ CUtensorMap mXs,
             const __grid_constant__ CUtensorMap mK, const __grid_constant__ CUtensorMap mV, const __grid_constant__ CUtensorMap mQ, const __grid_constant__ CUtensorMap mS,
             const __grid_constant__ CUtensorMap mO) {
  extern __shared__ __align__(1024) uint8_t smem_raw[];
  const uint32_t sb = (uint32_t)__cvta_generic_to_shared(smem_raw);
  const uint32_t bars = sb + OFF_BAR;
  const int slot = (P.slot[blockIdx.x >> 3] >> (4 * (blockIdx.x & 6))) & 63, rank = blockIdx.x & 1;
  const int j = slot & 7, tc = 2 * (slot >> 3) + rank, b = 2 * slot + rank;
  const int tid = threadIdx.x;
  const int warp = __shfl_sync(0xffffffffu, tid >> 5, 0);
  const int wg = warp >> 2;
  const uint32_t c_start = clk32();
  auto kblock = [&](int n) { return ((n & 14) == 0 || (n & 14) == 2 * j ? n ^ (2 * j) : n) & 31; };
  auto send_y = [&](int r) {
    const uint32_t src = sb + OFF_U + 4 * (rank ^ 1) * U_N8 + r * U_CH, dst = r >= 2 ? sb + OFF_U + 4 * rank * U_N8 + (r - 2) * U_CH : sb + OFF_IN + 96 + r * 2064;
#pragma unroll 1
    for (int n = 0; n < 4; n++) bulk_send(dst + n * (r >= 2 ? U_N8 : 512), src + n * U_N8, 512, bars + (B_IN + r) * 8, rank ^ 1);
  };
  auto load_q = [&](int i, int off, int bar) {
    const uint32_t fb = bars + bar * 8 + 4 * (i & 2);
    mbar_expect(fb, 4096); tma4d(sb + off + 2048 * (i & 2), &mQ, 16 * slot, 0, 4 * i, 4 * rank, fb);
  };
  auto head = [&](int n) {
    const uint32_t fb = bars + (B_FULL + n) * 8, dst = sb + OFF_RING + n * STAGE_BYTES;
    mbar_expect(fb, STAGE_BYTES);
    tma4d(dst + 16384, &mX, 64 * n, 0, 4 * tc, 0, fb);
    tma4d(dst, &mB, 64 * n, 0, 0, 8 * j, fb);
    tma4d(dst + 8192, &mB, 64 * n, 0, 0, 8 * j + 4, fb);
  };
  if (warp == 0 && elect_one()) {
#pragma unroll
    for (int s = 0; s < STAGES; s++) mbar_init(bars + (B_FULL + s) * 8, 1);
    head(0);
    asm volatile("fence.mbarrier_init.release.cluster;" ::: "memory");
  }
  if (wg == 3 && elect_one()) {
    if (warp < 15) {
#pragma unroll
      for (int s = 0; s < 11; s++) mbar_init(bars + 8 * B_XI + (warp & 3) * 88 + 8 * s, 1);
    } else {
#pragma unroll
      for (int s = B_EMPTY; s <= B_NONE; s++) mbar_init(bars + 8 * s, s < B_COEF ? 2 : s == B_COEF ? 128 : 4);
    }
    asm volatile("fence.mbarrier_init.release.cluster;" ::: "memory");
  }
  __syncwarp();
  asm volatile("barrier.cluster.arrive.relaxed.aligned;" ::: "memory");
  if (warp == 0 && elect_one()) {
#pragma unroll 1
    for (int n = 1; n < HEAD; n++) { spin_until(c_start, ST_T0 + n * ST_DELAY); head(n); }
  }
  __syncwarp();
#define CLUSTER_WAIT() asm volatile("barrier.cluster.wait.aligned;" ::: "memory")

  if (wg == 3) {
    asm volatile("setmaxnreg.dec.sync.aligned.u32 24;");
    CLUSTER_WAIT();
    if (warp < 14) {
      if (elect_one()) {
        uint32_t so = 8 * (HEAD % STAGES), ph = HEAD < STAGES;
        auto step = [&](auto issue) {
          mbar_wait(bars + B_EMPTY * 8 + so, ph);
          issue(sb + OFF_RING + (so << 12), bars + B_FULL * 8 + so);
          so += 8;
          if (so == 8 * STAGES) { so = 0; ph ^= 1; }
        };
        if (warp == 12) {
          auto g1 = [&](int n0, int n1, int grp) {
#pragma unroll 1
            for (int n = n0; n < n1; n++) step([&](uint32_t dst, uint32_t fb) { mbar_expect(fb, STAGE_BYTES); tma4d_mc(dst + rank * 8192, &mB, n * 64, 0, 0, grp + 4 * rank, fb); });
          };
#pragma unroll 1
          for (int n = HEAD; n < STAGES; n++) { spin_until(c_start, ST_T0 + n * ST_DELAY); g1(n, n + 1, 8 * j); }
          g1(STAGES, 16, 8 * j);
          g1(0, XPOS - 16, 8 * j + 64);
          step([&](uint32_t dst, uint32_t fb) { mbar_expect(fb, STAGE_BYTES); tma4d(dst, &mXs, 128 * j, 0, 0, 16 * tc, fb); mbar_arrive(bars + B_XI * 8); });
          g1(XPOS - 16, 16, 8 * j + 64);
#pragma unroll 1
          for (int n = 0; n < 32; n += 2) {
            const int col = kblock(n) * 32;
#pragma unroll
            for (int part = 0; part < 2; part++)
              step([&](uint32_t dst, uint32_t fb) { mbar_expect(fb, STAGE_BYTES); tma5d_mc(dst + rank * 8192, part ? &mCim : &mCre, col, 0, 0, 0, 8 * j + 4 * rank, fb); });
          }
        } else {
          auto g1 = [&](int n0, int n1, int nb) {
#pragma unroll 1
            for (int n = n0; n < n1; n++) step([&](uint32_t dst, uint32_t fb) { tma4d(dst + 16384, &mX, n * 64, 0, 4 * tc, 0, fb); });
          };
          auto g2 = [&](int n0, int n1) {
#pragma unroll 1
            for (int n = n0; n < n1; n++) step([&](uint32_t dst, uint32_t fb) { bulk_load(dst + 16384, g_h + (32 * tc + kblock(n)) * 1024, 16384, fb); });
          };
#pragma unroll 1
          for (int n = HEAD; n < STAGES; n++) { spin_until(c_start, ST_T0 + n * ST_DELAY); g1(n, n + 1, 0); }
          g1(STAGES, 16, 0);
          g1(0, XPOS - 16, 16);
          step([&](uint32_t dst, uint32_t fb) { tma4d(dst + 16384, &mXs, 128 * j + 64, 0, 0, 16 * tc, fb); });
          g1(XPOS - 16, 16, 16);
#pragma unroll 1
          for (int v = 0; v < 2; v++) {
            mbar_wait(bars + B_HP * 8, v);
            fence_proxy_async_global();
            g2(16 * v, 16 * v + 2);
            mbar_wait(bars + B_HR * 8, v);
            fence_proxy_async_global();
            g2(16 * v + 2, 16 * v + 16);
          }
        }
      }
    } else if (warp == 15) {
      mbar_wait(bars + B_COEF * 8, 0);
      const unsigned epoch = lds32(bars + B_EPOCH * 8);
#pragma unroll 1
      for (int v = 0; v < 2; v++) {
        unsigned* fp = &g_flagH[(16 * v + tc) * 32];
        if (elect_one()) {
          wait_until(v ? clk32() : c_start, (v ? PFC_T1 : PFC_T0) + (slot >> 3) * PFC_DT);
#pragma unroll
          for (int part = 0; part < 2; part++)
            asm volatile("cp.async.bulk.prefetch.tensor.5d.L2.global [%0, {%1, %2, %2, %2, %3}];" ::"l"(part ? &mCim : &mCre), "r"(512 * v + 8 * (slot & 56)), "r"(0), "r"(8 * j + 4 * rank) : "memory");
        }
        __syncwarp();
        bar_sync(4 + v, 160);
        if (elect_one()) {
          asm volatile("red.release.gpu.global.add.u32 [%0], 1;" ::"l"(fp) : "memory");
          mbar_arrive(bars + B_HP * 8);
          int it = 0;
          while (ld_acquire(fp) != 8 * epoch && ++it < (SPIN_LIMIT << 4)) __nanosleep(POLL_NS);
          mbar_arrive(bars + B_HR * 8);
        }
        __syncwarp();
      }
    } else if (elect_one()) {
      const int ch0 = 16 * slot;
      auto load_k = [&](int s, uint32_t dst) { const uint32_t fb = bars + (B_KF + (s & 1)) * 8; mbar_expect(fb, 4096); tma2d(dst, &mS, 0, 64 * (8 * b + s), fb); };
      prefetch_map(&mS); prefetch_map(&mK); prefetch_map(&mV);
      wait_until(c_start, K_T0);
      load_k(0, sb + OFF_U + (4 * rank + 3) * U_N8); load_k(1, sb + OFF_U + (4 * rank + 3) * U_N8 - 4096);
      {
        uint32_t so = 16, ph = 1;
#pragma unroll 1
        for (int e = 0; e < 9; e++) {
          const uint32_t fb = bars + B_KVF * 8 + so, dst = sb + OFF_KV + (so << 10);
          wait_until(c_start, KV_T0 + (e ? 2 * e - 1 : 0) * KV_DT);
          mbar_wait(bars + B_KVE * 8 + so, ph);
          const uint32_t c1 = clk32();
          mbar_expect(fb, e ? 8192 : 4096);
          tma3d(dst, &mK, ch0, 32 * rank - (e == 0), (4 * e - 4) & 31, fb);
          if (e > 0) { wait_until(c1, KV_DV); tma3d(dst + 4096, &mV, ch0, 32 * rank, 4 * e - 4, fb); }
          so += 8;
          if (so == 24) so = 0;
          if (so == 16) ph ^= 1;
        }
      }
      prefetch_map(&mCre); prefetch_map(&mCim); prefetch_map(&mXs); prefetch_map(&mQ); prefetch_map(&mO);
      mbar_wait(bars + B_KVE * 8, 0);
      load_k(2, sb + OFF_K); load_k(3, sb + OFF_K + 4096);
      mbar_wait(bars + (B_UF + 3) * 8, 0);
#pragma unroll 1
      for (int ch = 0; ch < 7; ch++) {
        if (ch > 0) {
          mbar_wait(bars + (B_Y + (ch & 3)) * 8, ch >> 2);
          if (ch > 2) mbar_wait(bars + (B_IN + ch - 3) * 8, 0);
          send_y(ch - 1);
        }
        if (ch < 6) {
          mbar_wait(bars + (B_KE + (ch & 1)) * 8, (ch >> 1) & 1);
          if (ch < 4) load_k(ch + 4, sb + OFF_K + (ch & 1) * 4096);
          if (ch == 3) asm volatile("cp.async.bulk.prefetch.tensor.4d.L2.global [%0, {%1, %2, %3, %4}];" ::"l"(&mQ), "r"(16 * (slot & ~3)), "r"(0), "r"(16 + 4 * (slot & 3)), "r"(4 * rank) : "memory");
          if (ch >= 2) load_q(2 * (ch & 1) + (ch < 4), ch < 4 ? OFF_Q : OFF_K, ch < 4 ? B_QF : B_KF);
        }
      }
    }
    return;
  } else if (wg == 2) {
    asm volatile("setmaxnreg.inc.sync.aligned.u32 %0;" ::"n"(488 - 2 * GREG));
    const int t = tid & 127, w = warp & 3, lane = t & 31, g = lane >> 2, c = lane & 3;
    const uint4 s2[2] = {ldg128_nc(P.shift_k + (8 * b + 2 * c) * 4), ldg128_nc(P.shift_k + (8 * (b ^ 1) + 2 * c) * 4)};
    const uint32_t dskip = __bfloat16_as_ushort(P.ssm_D[8 * b + (t & 7)]);
    uint32_t tp[4] = {}, ts[4] = {};
    float d0r, d0i;
    fft_tables(sb + OFF_F1, sb + OFF_F2, w, lane, tp, ts, d0r, d0i);
    CLUSTER_WAIT();
    if (t < 12) mbar_expect(bars + (B_IN + t) * 8, t < 6 ? 2048 : t < 8 ? 4 * (U_CH + 512) : U_N8);
    if (t < 8) sts32(sb + OFF_D + 4 * t, dskip << 16);
    const uint64_t dF1a = make_desc(sb + OFF_F1, 128, 512, 0), dF1b = make_desc(sb + OFF_F1, 512, 128, 0);
    const uint64_t dF2f = make_desc(sb + OFF_F2, 512, 128, 0), dF2i = make_desc(sb + OFF_F2, 128, 512, 0);
    auto T1k = [&](float* z, uint64_t dk) { wg_fence(); ss_n64<0, 1>(z, dF1a, dk); ss_n64<1, 1>(z, dF1a + 16, dk + 64); wg_commit(); };
    auto T1u = [&](float* z, uint64_t du) { wg_fence(); ss_n64<0, 0>(z, dF1a, du); ss_n64<1, 0>(z, dF1a + 16, du + 16); wg_commit(); };
    auto T2 = [&](float* s, const uint32_t* f) {
      wg_fence();
      rs_n32<0, 1>(s, f, dF2f); rs_n32<0, 1>(s + 16, f + 8, dF2f); rs_n32<1, 1>(s, f + 4, dF2f + 64); rs_n32<1, 1>(s + 16, f + 12, dF2f + 64);
      wg_commit();
    };
    auto product = [&](uint32_t* pr, const uint32_t* kh, const uint32_t* uh) {
      bimac<0>(pr, kh, uh, pr); bimac<2>(pr + 8, kh + 8, uh, pr); bimac<1>(pr + 8, kh, uh + 8, pr + 8);
      fence_u32<16>(pr);
    };
    float zk[32] = {};
    uint32_t pr[16];
    {
      uint32_t kh0[16];
      {
        float z0[32], sk[32];
        uint32_t fk[16];
        const uint64_t dk = make_desc(sb + OFF_U + (4 * rank + 3) * U_N8, 2048, 512, 2);
        fence_proxy_async_smem();
        bar_sync(7, 128);
        mbar_wait(bars + B_KF * 8, 0);
        T1k(z0, dk);
        mbar_wait(bars + (B_KF + 1) * 8, 0);
        T1k(zk, dk - 256);
        wg_wait<0>(); fence_regs<32>(z0); fence_regs<32>(zk);
        const float dd = __uint_as_float(lds32(sb + OFF_D));
        z0[0] = fmaf(d0r, dd, z0[0]); z0[2] = fmaf(d0i, dd, z0[2]);
        pack32(fk, z0); twiddle<0>(fk, tp, ts); fence_u32<16>(fk);
        T2(sk, fk);
        wg_wait<0>(); fence_regs<32>(sk); fence_u32<16>(fk);
        pack32(kh0, sk); fence_u32<16>(kh0);
      }
      {
        uint32_t sk[2][4], kx[2][8];
#pragma unroll
        for (int o = 0; o < 2; o++) {
          sk[o][0] = __byte_perm(s2[o].x, s2[o].z, 0x5410); sk[o][1] = __byte_perm(s2[o].x, s2[o].z, 0x7632);
          sk[o][2] = __byte_perm(s2[o].y, s2[o].w, 0x5410); sk[o][3] = __byte_perm(s2[o].y, s2[o].w, 0x7632);
        }
        const uint32_t la = sb + OFF_KV + (lane >> 3) * 1024 + (8 * w + (lane & 7)) * 32 + ((rank ^ ((lane >> 2) & 1)) << 4);
        const uint32_t uo = (lane & 7) * U_CH + w * 128 + (lane >> 3) * 16;
        mbar_wait(bars + (B_KVF + 2) * 8, 0);
        ldsm4(kx[0], la + 16384); ldsm4(kx[1], (la ^ 16) + 16384);
        if (lane == 0) mbar_arrive(bars + (B_KVE + 2) * 8 + (kx[0][1] & kx[1][1] & P.zero));
        uint32_t so = 0, ph = 0;
#pragma unroll 1
        for (int n = 0; n < 4; n++) {
          const uint32_t own = sb + OFF_U + (4 * rank + n) * U_N8, box = n < 3 ? sb + OFF_U + (4 * (rank ^ 1) + n + 1) * U_N8 : sb + OFF_IN;
#pragma unroll
          for (int e = 0; e < 2; e++) {
            uint32_t vx[2][4];
            mbar_wait(bars + B_KVF * 8 + so, ph);
#pragma unroll
            for (int o = 0; o < 2; o++) { ldsm4(kx[o] + 4, (la ^ (16 * o)) + (so << 10)); ldsm4(vx[o], (la ^ (16 * o)) + (so << 10) + 4096); }
            if (lane == 0) mbar_arrive(bars + B_KVE * 8 + so + (kx[0][4] & kx[1][4] & vx[0][0] & vx[1][0] & P.zero));
#pragma unroll
            for (int o = 0; o < 2; o++) {
#pragma unroll
              for (int i = 0; i < 4; i++) vx[o][i] = bmul2(bfma2(kx[o][i + 4], sk[o][0], bfma2(kx[o][i + 3], sk[o][1], bfma2(kx[o][i + 2], sk[o][2], bmul2(kx[o][i + 1], sk[o][3])))), vx[o][i]);
              stsm4t((o ? box : own) + uo + e * 64, vx[o][0], vx[o][1], vx[o][2], vx[o][3]);
              kx[o][1] = kx[o][5]; kx[o][2] = kx[o][6]; kx[o][3] = kx[o][7];
            }
            so += 8;
            if (so == 24) so = 0;
            if (so == 16) ph ^= 1;
          }
          fence_proxy_async_smem();
          bar_sync(7, 128);
          if (w == 0 && elect_one()) {
            if (n > 0) mbar_wait(bars + B_UF * 8 + 8 * (n - 1), 0);
            bulk_send(own, box, U_N8, bars + B_UF * 8 + 8 * n, rank ^ 1);
          }
          __syncwarp();
        }
      }
      float zu[32], su[32];
      uint32_t fu[16], uh[16];
#pragma unroll
      for (int n = 0; n < 4; n++) mbar_wait(bars + (B_UF + n) * 8, 0);
      T1u(zu, make_desc(sb + OFF_U, 128, U_N8, 0));
      wg_wait<0>(); fence_regs<32>(zu);
      pack32(fu, zu); twiddle<0>(fu, tp, ts); fence_u32<16>(fu);
      T2(su, fu);
      wg_wait<0>(); fence_regs<32>(su); fence_u32<16>(fu);
      pack32(uh, su);
      product(pr, kh0, uh);
    }
    {
#define CF(i) do { if ((CFM >> (i)) & 1) PMFENCE(); } while (0)
      const uint32_t vs = w < 2 ? 512 : U_N8;
      uint32_t va = (w < 2 ? sb + OFF_VP : sb + OFF_U) + ((lane >> 4) & 1) * vs + (w & 1) * 256 + (lane & 15) * 16;
      uint32_t ya = sb + OFF_U + (2 * w + ((lane >> 3) & 1)) * U_N8 + (lane >> 4) * 128 + (lane & 7) * 16;
      uint64_t du = make_desc(sb + OFF_U, 128, U_N8, 0), dk = make_desc(sb + OFF_K, 2048, 512, 2);
      const uint64_t dv = make_desc(sb + OFF_VP, 128, 512, 0);
      uint32_t yp[8] = {};
      uint32_t yq = sb + OFF_Q + lane * 16;
      auto store_y = [&]() { stsm4(yq, yp[0], yp[1], yp[2], yp[3]); stsm4(yq + 256, yp[4], yp[5], yp[6], yp[7]); };
      auto step = [&](int ch, auto fwd) {
        constexpr bool FWD = decltype(fwd)::value;
        float zu[32], sk[32], su[32], v[32], y[16];
        uint32_t kh[16], uh[16], fk[16], fu[16], fv[16];
        wg_fence();
        rs_n32<0, 0>(v, pr, dF2i); rs_n32<0, 0>(v + 16, pr + 8, dF2i); rs_n32<1, 0>(v, pr + 4, dF2i + 16); rs_n32<1, 0>(v + 16, pr + 12, dF2i + 16);
        wg_commit();
        CF(0);
        store_y();
        if (FWD) {
          const float dd = __uint_as_float(lds32(sb + OFF_D + 4 * (ch + 1)));
          zk[0] = fmaf(d0r, dd, zk[0]); zk[2] = fmaf(d0i, dd, zk[2]);
          pack32(fk, zk); twiddle<0>(fk, tp, ts); fence_u32<16>(fk);
          T2(sk, fk);
          CF(2);
          mbar_wait(bars + (B_KF + (ch & 1)) * 8, ((ch >> 1) & 1) ^ 1);
          wg_wait<1>();
        } else {
#pragma unroll
          for (int r = 3; r < 6; r++) mbar_wait(bars + (B_IN + r) * 8, 0);
          wg_wait<0>();
        }
        fence_regs<32>(v); fence_u32<16>(pr);
        pack32(fv, v); fence_u32<16>(fv);
        CF(4);
        if (FWD) T1u(zu, du + U_CH / 16);
        CF(5);
        if (FWD) { wg_wait<1>(); fence_regs<32>(sk); fence_u32<16>(fk); pack32(kh, sk); }
        twiddle<1>(fv, tp, ts);
#pragma unroll
        for (int i = 0; i < 4; i++) stsm4(va + 2 * i * vs, fv[4 * i], fv[4 * i + 1], fv[4 * i + 2], fv[4 * i + 3]);
        if (FWD) {
          fence_u32<16>(kh);
          CF(7);
          T1k(zk, dk);
          CF(8);
          wg_wait<1>(); fence_regs<32>(zu);
          pack32(fu, zu); twiddle<0>(fu, tp, ts); fence_u32<16>(fu);
          T2(su, fu);
          CF(10);
        }
        fence_proxy_async_smem();
        bar_sync(7, 128);
        wg_fence();
        ss_n32_tt<0>(y, dv, dF1b); ss_n32_tt<1>(y, dv + 16, dF1b + 64); ss_n32_tt<1>(y, du, dF1b + 128); ss_n32_tt<1>(y, du + 16, dF1b + 192);
        wg_commit();
        if (FWD && t == 0) mbar_arrive(bars + (B_Y + (ch & 3)) * 8);
        CF(12);
        if (FWD) {
          wg_wait<1>(); fence_regs<32>(su); fence_u32<16>(fu); fence_regs<32>(zk);
          if (t == 0) mbar_arrive(bars + (B_KE + (ch & 1)) * 8);
          pack32(uh, su);
          bimac<0>(pr, kh, uh, pr); bimac<2>(pr + 8, kh + 8, uh, pr); fence_u32<16>(pr);
          CF(14);
          wg_wait<0>(); fence_regs<16>(y);
          bimac<1>(pr + 8, kh, uh + 8, pr + 8); fence_u32<8>(pr + 8);
          du += U_CH / 16; dk += (ch & 1) ? -256 : 256;
          if (w >= 2) va += U_CH;
        }
        if (!FWD) { wg_wait<0>(); fence_regs<16>(y); }
#pragma unroll
        for (int i = 0; i < 8; i++) yp[i] = pack_bf16(y[2 * i], y[2 * i + 1]);
        fence_u32<8>(yp);
        yq = ya;
        ya += U_CH;
      };
#pragma unroll 1
      for (int ch = 0; ch < 7; ch++) step(ch, std::true_type());
      step(7, std::false_type());
      store_y();
    }
    fence_proxy_async_smem();
    bar_sync(7, 128);
    if (elect_one()) bulk_send(sb + OFF_U + (4 * rank + w) * U_N8 + 4 * U_CH, sb + OFF_U + (4 * (rank ^ 1) + w) * U_N8 + 6 * U_CH, U_CH + 512, bars + (B_IN + 6) * 8, rank ^ 1);
    __syncwarp();
    asm volatile("bar.arrive 9, 256;" ::: "memory");
  } else {
    asm volatile("setmaxnreg.inc.sync.aligned.u32 %0;" ::"n"(GREG));
    const int t = tid & 127, w = warp & 3, lane = t & 31, g = lane >> 2, c = lane & 3;
    if (wg == 1) {
      wait_until(c_start, COEF_T0);
      const int p = 64 * j + (t & 63) + 8 * (t & 64);
      const float Lr = bf2f(P.lam_re[p]), Li = bf2f(P.lam_im[p]);
      const uint32_t ds = __bfloat16_as_ushort(P.Dskip[128 * j + t]);
      const unsigned epoch = ld_relaxed(&g_epoch[b * 32]) + 1;
      const float dt = bf2f(__float2bfloat16_rn(expf(bf2f(P.log_dt[p]))));
      const float e = expf(dt * Lr);
      float sn, cs;
      {
        const double z = (double)(dt * Li) * 0.15915494309189535;
        sincospif(2.f * (float)(z - rint(z)), &sn, &cs);
      }
      const float lr = e * cs, li = e * sn;
      const float nr = lr - 1.0f, ni = li;
      const bool big = fabsf(Lr) >= fabsf(Li);
      const float la = big ? Lr : Li, lb = big ? Li : Lr, r = __fdiv_rn(lb, la), inv = __frcp_rn(fmaf(lb, r, la));
      const float br = (big ? fmaf(ni, r, nr) : fmaf(nr, r, ni)) * inv, bi = (big ? fmaf(-nr, r, ni) : fmaf(ni, r, -nr)) * inv;
      sts128(sb + OFF_COEF + t * 16, make_uint4(__float_as_uint(lr), __float_as_uint(li), pack_bf16(2.f * br, 2.f * br), pack_bf16(-2.f * bi, -2.f * bi)));
      sts32(sb + OFF_DS + 4 * t, ds << 16);
      if (t == 0) sts32(bars + B_EPOCH * 8, epoch);
    }
    CLUSTER_WAIT();
    if (wg == 1) mbar_arrive(bars + B_COEF * 8);
    float d[128];
    uint32_t so = 0, ph = 0, po = 0;
    uint32_t ra;
    auto set_ra = [&]() { asm volatile("mapa.shared::cluster.u32 %0, %1, %2;" : "=r"(ra) : "r"(bars + B_EMPTY * 8), "r"((t & 1) ? rank ^ 1 : rank)); };
    set_ra();
    auto release = [&](uint32_t off) { if (t < 2) asm volatile("mbarrier.arrive.shared::cluster.b64 _, [%0];" ::"r"(ra + off) : "memory"); };
    constexpr uint32_t NOBAR = 8 * (B_NONE - B_EMPTY);
    auto block = [&](auto ta, uint64_t da0, uint64_t db0, bool zero, int nn) {
      constexpr int PH = decltype(ta)::value, TA = PH > 0, KS = TA ? 128 : 2, QD = PH == 0 ? QD1 : PH == 1 ? QD2 : QD3;
      mbar_wait(bars + B_FULL * 8 + so, ph);
      const uint64_t da = da0 + (so << 8), db = db0 + (so << 8);
      wg_fence();
      wgmma_n128<TA>(d, da, db, !zero);
      wgmma_n128<TA>(d + 64, da + 512, db, !zero);
      wg_commit();
      wg_wait<1>();
      release(po);
#pragma unroll
      for (int k = 1; k < 4; k++) {
        if (QD == 2 || (QD == 4 && k == 2)) wg_fence();
        wgmma_n128<TA>(d, da + KS * k, db + 2 * k, 1);
        wgmma_n128<TA>(d + 64, da + 512 + KS * k, db + 2 * k, 1);
        if (QD == 2 || (QD == 4 && k == 1)) wg_commit();
        if ((QD == 2 && k < 3) || (QD == 4 && k == 1)) wg_wait<1>();
      }
      if (QD != 2) wg_commit();
      po = so;
      so += 8;
      if (so == 8 * STAGES) { so = 0; ph ^= 1; }
    };
    {
      so = wg ? 8 * (16 % STAGES) : 0; ph = wg ? (16 / STAGES) & 1 : 0; po = NOBAR;
      const uint64_t da0 = make_desc(sb + OFF_RING, 16, 1024, 1), db0 = make_desc(sb + OFF_RING + 16384, 16, 1024, 1);
      if (wg == 1) bar_sync(1, 256);
#pragma unroll 1
      for (int kb = 0; kb < 16; kb++) {
        if (16 * wg + kb == XPOS) { so += 8; if (so == 8 * STAGES) { so = 0; ph ^= 1; } }
        block(std::integral_constant<int, 0>(), da0, db0, kb == 0, 16 * wg + kb);
      }
      asm volatile("bar.arrive %0, 256;" ::"r"(1 + wg) : "memory");
    }
    mbar_wait(bars + B_COEF * 8, 0);
    const uint32_t ca = sb + OFF_COEF + (64 * wg + 8 * w + g) * 16;
    const uint32_t tag = __shfl_sync(0xffffffffu, lds32(bars + B_EPOCH * 8) & 3, 0);
    constexpr int RE = SWAPB ? 2 : 0, IM = 2 - RE;
    const int ct = lane >> 3;
    const uint2* cp = g_carry + __shfl_sync(0xffffffffu, ((16 * wg + 2 * j) * 16 + tc - 1 - ct) * 32 + 8 * w + (lane & 7), lane);
    unsigned long long cv[4];
    auto load_carry = [&](int i) {
#pragma unroll
      for (int m = 0; m < 4; m++)
        asm volatile("{\n.reg .pred p;\nsetp.lt.s32 p, %2, %3;\n@p ld.relaxed.gpu.global.b64 %0, [%1];\n}\n" : "=l"(cv[m]) : "l"(cp + 512 * i - 128 * m), "r"(ct + 4 * m), "r"(tc) : "memory");
    };
    float lr[2], li[2], pr[2], pi[2], wr[2], wi[2], vr[2], vi[2], qr[2], qi[2], er[2], ei[2], gr[2], gi[2];
    auto powers = [&](int i) {
      const uint2 cf = lds64(ca + 512 * i);
      pr[i] = lr[i] = __uint_as_float(cf.x); pi[i] = li[i] = __uint_as_float(cf.y);
#pragma unroll
      for (int s = 0; s < 4; s++) csq(pr[i], pi[i]);
      gr[i] = pr[i]; gi[i] = pi[i];
      csq(pr[i], pi[i]);
      qr[i] = pr[i]; qi[i] = pi[i];
      csq(qr[i], qi[i]);
      er[i] = qr[i]; ei[i] = qi[i];
      wr[i] = (c & 1) ? pr[i] : 1.f; wi[i] = (c & 1) ? pi[i] : 0.f;
      if (c & 2) { float x, y; cmul(wr[i], wi[i], qr[i], qi[i], x, y); wr[i] = x; wi[i] = y; }
      vr[i] = wr[i]; vi[i] = wi[i];
      csq(vr[i], vi[i]); csq(vr[i], vi[i]);
      csq(qr[i], qi[i]); csq(qr[i], qi[i]); csq(qr[i], qi[i]);
      const int src = 4 * (lane & 7) + ct;
      vr[i] = __shfl_sync(0xffffffffu, vr[i], src); vi[i] = __shfl_sync(0xffffffffu, vi[i], src);
      qr[i] = __shfl_sync(0xffffffffu, qr[i], src); qi[i] = __shfl_sync(0xffffffffu, qi[i], src);
      asm volatile("" : "+f"(wr[i]), "+f"(wi[i]), "+f"(pr[i]), "+f"(pi[i]), "+f"(er[i]), "+f"(ei[i]));
    };
    powers(0);
    PMFENCE();
    wg_wait<0>();
    fence_regs<128>(d);
    release(po);
#pragma unroll
    for (int i = 0; i < 2; i++) {
      const float* e = d + 64 * i;
      auto chain = [&](int s0, int s1, float& sr, float& si) {
        sr = e[2 * s0 + RE]; si = e[2 * s0 + IM];
#pragma unroll
        for (int s = s0 + 1; s < s1; s++) {
          const int ia = 4 * (s >> 1) + (s & 1);
          const float nr = fmaf(-li[i], si, fmaf(lr[i], sr, e[ia + RE])), ni = fmaf(li[i], sr, fmaf(lr[i], si, e[ia + IM]));
          sr = nr; si = ni;
        }
      };
      float sr, si;
      if (i == 1) powers(1);
      if ((GREEDY >> i) & 1) {
        float ar, ai;
        chain(0, 16, ar, ai); chain(16, 32, sr, si);
        sr = fmaf(gr[i], ar, fmaf(-gi[i], ai, sr)); si = fmaf(gr[i], ai, fmaf(gi[i], ar, si));
      } else chain(0, 32, sr, si);
      if (i == 1) { asm volatile("pmevent 0;" : "+f"(sr), "+f"(si)::"memory"); load_carry(0); }
      float ur = __shfl_up_sync(0xffffffffu, sr, 1, 4), ui = __shfl_up_sync(0xffffffffu, si, 1, 4);
      if (c >= 1) { sr = fmaf(pr[i], ur, fmaf(-pi[i], ui, sr)); si = fmaf(pr[i], ui, fmaf(pi[i], ur, si)); }
      ur = __shfl_up_sync(0xffffffffu, sr, 2, 4); ui = __shfl_up_sync(0xffffffffu, si, 2, 4);
      if (c >= 2) { sr = fmaf(er[i], ur, fmaf(-ei[i], ui, sr)); si = fmaf(er[i], ui, fmaf(ei[i], ur, si)); }
      ur = __shfl_sync(0xffffffffu, sr, 4 * lane + 3); ui = __shfl_sync(0xffffffffu, si, 4 * lane + 3);
      asm volatile("{\n.reg .pred p;\n.reg .b64 v;\nsetp.lt.u32 p, %3, 8;\nmov.b64 v, {%1,%2};\n@p st.relaxed.gpu.global.b64 [%0], v;\n}\n"
                   ::"l"(cp + 512 * i + 32), "r"((__float_as_uint(ur) & ~3u) | tag), "r"(__float_as_uint(ui)), "r"(lane) : "memory");
      PMFENCE();
      er[i] = __shfl_up_sync(0xffffffffu, sr, 1, 4); ei[i] = __shfl_up_sync(0xffffffffu, si, 1, 4);
      if (c == 0) er[i] = ei[i] = 0.f;
    }
    uint4* hp = g_h + (32 * tc + 16 * wg + 2 * j) * 1024 + 64 * w + 4 * g + (c ^ (g >> 1));
#pragma unroll
    for (int i = 0; i < 2; i++) {
      float* e = d + 64 * i;
      const uint2 cf = lds64(ca + 512 * i + 8);
      const uint32_t gp = cf.x, gms = cf.y;
      PMFENCE();
      auto ready = [&]() {
        uint32_t bad = 0;
#pragma unroll
        for (int m = 0; m < 4; m++) if (ct + 4 * m < tc) bad |= (uint32_t)cv[m] ^ tag;
        return __all_sync(0xffffffffu, (bad & 3) == 0);
      };
      if (!ready()) {
        int n = 0;
#pragma unroll 1
        do load_carry(i); while (!ready() && ++n <= (SPIN_LIMIT << 4));
      }
      float hr = 0.f, hi = 0.f;
#pragma unroll
      for (int m = 3; m >= 0; m--) {
        const float x = __uint_as_float((uint32_t)cv[m]), y = __uint_as_float((uint32_t)(cv[m] >> 32));
        const float nr = m == 3 ? x : fmaf(qr[i], hr, fmaf(-qi[i], hi, x)), ni = m == 3 ? y : fmaf(qr[i], hi, fmaf(qi[i], hr, y));
        if (ct + 4 * m < tc) { hr = nr; hi = ni; }
      }
      { float x, y; cmul(hr, hi, vr[i], vi[i], x, y); hr = x; hi = y; }
      hr += __shfl_xor_sync(0xffffffffu, hr, 8); hi += __shfl_xor_sync(0xffffffffu, hi, 8);
      hr = __shfl_sync(0xffffffffu, hr, g) + __shfl_sync(0xffffffffu, hr, g + 16); hi = __shfl_sync(0xffffffffu, hi, g) + __shfl_sync(0xffffffffu, hi, g + 16);
      float sr = fmaf(wr[i], hr, fmaf(-wi[i], hi, er[i])), si = fmaf(wr[i], hi, fmaf(wi[i], hr, ei[i]));
#pragma unroll
      for (int i8 = 0; i8 < 4; i8++) {
        asm volatile("pmevent 0;" : "+f"(sr), "+f"(si)::"memory");
        if (i == 0 && i8 == 1) load_carry(1);
#pragma unroll
        for (int s = 8 * i8; s < 8 * i8 + 8; s++) {
          const int ia = 4 * (s >> 1) + (s & 1);
          const float nr = fmaf(-li[i], si, fmaf(lr[i], sr, e[ia + RE])), ni = fmaf(li[i], sr, fmaf(lr[i], si, e[ia + IM]));
          sr = nr; si = ni;
          e[ia + RE] = nr; e[ia + IM] = ni;
        }
        uint32_t hp0[4], hp1[4];
#pragma unroll
        for (int m = 0; m < 4; m++) {
          const float* f = e + 16 * i8 + 4 * m;
          const uint32_t x = pack_bf16(f[RE], f[RE + 1]), y = pack_bf16(f[IM], f[IM + 1]);
          hp0[m] = bfma2(gp, x, bmul2(gms, y)); hp1[m] = bfnma2(gp, y, bmul2(gms, x));
        }
        uint4* o = hp + 512 * (i8 >> 1) + 256 * i + 32 * (i8 & 1);
        stg128(o, make_uint4(hp0[0], hp0[1], hp0[2], hp0[3]));
        stg128(o + 1024, make_uint4(hp1[0], hp1[1], hp1[2], hp1[3]));
      }
    }
    const int trow = 128 * tc + 64 * (w & 1) + 8 * (w >> 1) + g;
    const int dcol = 128 * j + 4 * c;
    asm volatile("bar.arrive %0, 160;" ::"r"(4 + wg) : "memory");
    if (wg == 0) {
      set_ra();
      uint2 xv[32];
      {
        const int gp = 2 * (g & 3) + (g >> 2);
        const uint32_t xa = sb + OFF_RING + (XPOS % STAGES) * STAGE_BYTES + (64 * (w & 1) + 8 * (w >> 1) + gp) * 128 + (c & 1) * 8;
        mbar_wait(bars + B_XI * 8, 0);
        mbar_wait(bars + (B_FULL + XPOS % STAGES) * 8, (XPOS / STAGES) & 1);
#pragma unroll
        for (int u = 0; u < 32; u++) {
          const int J = (u >> 1) & 7;
          asm volatile("ld.shared.v2.u32 {%0,%1}, [%2];" : "=r"(xv[u].x), "=r"(xv[u].y) : "r"(xa + (J >> 2) * 16384 + (u >> 4) * 2048 + (u & 1) * 4096 + (((2 * (J & 3) + (c >> 1)) ^ gp) << 4)) : "memory");
        }
        uint32_t dep = P.zero;
#pragma unroll
        for (int u = 0; u < 32; u++) dep &= xv[u].x;
        bar_sync(3 + dep, 128);
        release(8 * (XPOS % STAGES));
      }
#pragma unroll
      for (int J = 0; J < 8; J++) {
        const uint4 ds = lds128(sb + OFF_DS + 16 * c + 64 * J);
#pragma unroll
        for (int r = 0; r < 4; r++) {
          const int u = 16 * (r >> 1) + 2 * J + (r & 1);
          float* e = d + 8 * (u >> 1) + 2 * (u & 1);
          e[0] = __uint_as_float(bfma2(blo2(xv[u].x), ds.x, 0)); e[1] = __uint_as_float(bfma2(xv[u].x, ds.y, 0));
          e[4] = __uint_as_float(bfma2(blo2(xv[u].y), ds.z, 0)); e[5] = __uint_as_float(bfma2(xv[u].y, ds.w, 0));
        }
      }
      fence_regs<128>(d);
      so = 8 * (33 % STAGES); ph = (33 / STAGES) & 1; po = NOBAR;
      const uint64_t da0 = make_desc(sb + OFF_RING + 16384, 512, 1024, 2), db0 = make_desc(sb + OFF_RING, 16, 1024, 1);
      bar_sync(2, 256);
#pragma unroll 1
      for (int kb = 0; kb < QSW; kb++) block(std::integral_constant<int, 1>(), da0, db0, false, 32 + kb);
#pragma unroll 1
      for (int kb = QSW; kb < 32 - TAILB; kb++) block(std::integral_constant<int, 2>(), da0, db0, false, 32 + kb);
      float* op = P.out + (size_t)trow * 2048 + 1024 + dcol;
      auto mma = [&](int i, int kb, int k0, int k1) {
        const int s = (33 + kb) % STAGES;
        wg_fence();
#pragma unroll
        for (int k = k0; k < k1; k++) wgmma_n128<1>(d + 64 * i, da0 + s * 2048 + 512 * i + 128 * k, db0 + (i ? 0 : P.zero) + s * 2048 + 2 * k, 1);
        wg_commit();
      };
      auto store = [&](int i, int J0, int J1) {
#pragma unroll
        for (int J = J0; J < J1; J++) {
#pragma unroll
          for (int h = 0; h < 2; h++) {
            const float* e = d + 64 * i + 8 * J + 2 * h;
            stg128(op + (size_t)(16 * i + 32 * h) * 2048 + 16 * J, make_uint4(__float_as_uint(e[0]), __float_as_uint(e[1]), __float_as_uint(e[4]), __float_as_uint(e[5])));
          }
        }
        PMFENCE();
      };
      constexpr int K0 = 32 - TAILB;
#pragma unroll
      for (int kb = K0; kb < 32; kb++) {
        mbar_wait(bars + (B_FULL + (33 + kb) % STAGES) * 8, ((33 + kb) / STAGES) & 1);
        if (TAILB == 5 && kb == K0) { mma(0, kb, 0, 2); wg_wait<1>(); release(po); mma(0, kb, 2, 4); }
        else mma(0, kb, 0, 4);
      }
      mma(1, K0, 0, 4);
      wg_wait<1>();
      fence_regs<64>(d);
#pragma unroll
      for (int kb = K0 + 1; kb < 32; kb++) {
        mma(1, kb, 0, 4);
        store(0, T_ST * (kb - K0 - 1), kb == 31 ? 8 : T_ST * (kb - K0));
      }
      wg_wait<0>();
      fence_regs<64>(d + 64);
      store(1, 0, 8);
      if (t == 0) g_epoch[b * 32] = lds32(bars + B_EPOCH * 8);
      return;
    }
    asm volatile("setmaxnreg.dec.sync.aligned.u32 %0;" ::"n"(488 - 2 * GREG));
  }
  {
    int lane;
    asm volatile("mov.u32 %0, %%laneid;" : "=r"(lane));
    const int w = warp & 3, h = wg & 1;
    const int lc = 2 * (lane & 2) + (lane & 1) + ((lane >> 2) & 2);
    const bool own = ((lane >> 2) & 1) == rank, spare = !own && lc < 2;
    const uint32_t ya = (spare ? sb + OFF_IN + 96 + lc * 2064 : sb + OFF_U + (own ? 4 * rank * U_N8 : 4 * (rank ^ 1) * U_N8 - 2 * U_CH) + lc * U_CH) + w * 128 + (lane >> 4) * 16 + h * 64;
    const uint32_t ys = spare ? 512 : U_N8;
    const uint32_t ob0 = sb + (h ? OFF_F1 : OFF_K) + 1024 * w, ob1 = sb + (h ? OFF_VP : OFF_K + 4096) + 1024 * w;
    uint32_t y[2][8];
    uint2 q[4][4];
    auto get_q = [&](int n, int off, int bar, int ph) {
#pragma unroll
      for (int u = 0; u < 2; u++) {
        mbar_wait(bars + (bar + u) * 8, ph);
#pragma unroll
        for (int r = 0; r < 4; r++) q[n + u][r] = lds64(sb + off + 4096 * u + 1024 * w + 256 * r + 8 * lane);
      }
    };
    auto get_y = [&](int n) { ldsm4t(y[n & 1], ya + n * ys); ldsm4t(y[n & 1] + 4, ya + n * ys + 32); };
    if (h) {
#pragma unroll
      for (int n = 0; n < 4; n += 2) {
        get_q(n, OFF_Q, B_QF, n >> 1);
        uint32_t dep = P.zero;
#pragma unroll
        for (int r = 0; r < 8; r++) dep &= q[n + (r >> 2)][r & 3].x;
        bar_sync(6 + dep, 128);
        if (w < 2 && elect_one()) load_q(5 + 2 * w - (n >> 1), OFF_Q, B_QF + n);
        __syncwarp();
      }
#pragma unroll 1
      for (int r = 0; r < 6; r++) mbar_wait(bars + (B_IN + r) * 8, 0);
      bar_sync(9, 256);
    } else get_q(0, OFF_K, B_KF, 0);
    mbar_wait(bars + B_HR * 8, 1);
    mbar_wait(bars + (B_IN + 6) * 8, 0);
    get_y(0);
#pragma unroll
    for (int n = 0; n < 4; n++) {
      uint32_t* o = y[n & 1];
#pragma unroll
      for (int r = 0; r < 4; r++) { o[2 * r] = bmul2(o[2 * r], q[n][r].x); o[2 * r + 1] = bmul2(o[2 * r + 1], q[n][r].y); }
      if (n > 0 && lane == 0) asm volatile("cp.async.bulk.wait_group.read 0;" ::: "memory");
      __syncwarp();
#pragma unroll
      for (int r = 0; r < 4; r++)
        sts128((r & 2 ? ob1 : ob0) + (r & 1) * 512 + lane * 16, make_uint4(o[2 * r] << 16, o[2 * r] & 0xffff0000u, o[2 * r + 1] << 16, o[2 * r + 1] & 0xffff0000u));
      fence_proxy_async_smem();
      __syncwarp();
      if (lane == 0) {
#pragma unroll
        for (int u = 0; u < 2; u++)
          asm volatile("cp.async.bulk.tensor.3d.global.shared::cta.bulk_group [%0, {%2, %3, %4}], [%1];"
                       ::"l"(&mO), "r"(u ? ob1 : ob0), "r"(32 * slot), "r"(32 * rank + 8 * w), "r"(8 * n + 4 * h + 2 * u) : "memory");
        asm volatile("cp.async.bulk.commit_group;" ::: "memory");
      }
      __syncwarp();
      if (n < 3) get_y(n + 1);
      if (n == 1 && !h) get_q(2, OFF_Q, B_QF + 2, 0);
    }
    if (warp == 8 && lane == 0) mbar_arrive_cta(bars + B_ACK * 8, rank ^ 1);
    if (lane == 0) asm volatile("cp.async.bulk.wait_group 0;" ::: "memory");
    mbar_wait(bars + B_ACK * 8, 0);
  }
}

typedef CUresult (*EncodeFn)(CUtensorMap*, CUtensorMapDataType, cuuint32_t, void*, const cuuint64_t*, const cuuint64_t*, const cuuint32_t*,
                             const cuuint32_t*, CUtensorMapInterleave, CUtensorMapSwizzle, CUtensorMapL2promotion, CUtensorMapFloatOOBfill);

bool encode(EncodeFn fn, CUtensorMap* m, int rank, const void* base, const cuuint64_t* dims, const cuuint64_t* strides, const cuuint32_t* box, CUtensorMapSwizzle swz,
            CUtensorMapL2promotion promo = CU_TENSOR_MAP_L2_PROMOTION_L2_128B) {
  const cuuint32_t es[5] = {1, 1, 1, 1, 1};
  return fn(m, CU_TENSOR_MAP_DATA_TYPE_BFLOAT16, rank, const_cast<void*>(base), dims, strides, box, es, CU_TENSOR_MAP_INTERLEAVE_NONE, swz,
            promo, CU_TENSOR_MAP_FLOAT_OOB_FILL_NONE) == CUDA_SUCCESS;
}

}

extern "C" void kernel_launch(void* const* d_in, const int* in_sizes, int n_in, void* d_out, int out_size) {
  (void)in_sizes; (void)n_in; (void)out_size;
  typedef const __nv_bfloat16* In;
  const In q = (In)d_in[0], k = (In)d_in[1], v = (In)d_in[2], ssm_k = (In)d_in[4], x = (In)d_in[6], B_re = (In)d_in[9], B_im = (In)d_in[10], C_re = (In)d_in[11], C_im = (In)d_in[12];
  Params P = {};
  P.shift_k = (In)d_in[3]; P.ssm_D = (In)d_in[5]; P.lam_re = (In)d_in[7]; P.lam_im = (In)d_in[8]; P.log_dt = (In)d_in[13]; P.Dskip = (In)d_in[14];
  P.out = (float*)d_out;
  for (int cl = 0; cl < 64; cl++) P.slot[cl >> 2] |= (cl < 4 ? 4 + cl : cl < 36 ? 8 * ((cl - 4) & 7) + ((cl - 4) >> 3) : 8 * (1 + (cl - 36) % 7) + 4 + (cl - 36) / 7) << (8 * (cl & 3));
  const bool swapB = (uintptr_t)B_im < (uintptr_t)B_re;

  EncodeFn fn = nullptr;
  cudaDriverEntryPointQueryResult qr;
  cudaGetDriverEntryPoint("cuTensorMapEncodeTiled", (void**)&fn, cudaEnableDefault, &qr);
  if (!fn) return;

  CUtensorMap mX, mB, mCre, mCim, mXs, mK, mV, mQ, mS, mO;
  bool ok = true;
  {
    const cuuint64_t dims[4] = {1024, 2, 64, 16}, str[3] = {2048, 32 * 2048, 2 * 2048};
    const cuuint32_t box[4] = {64, 2, 4, 16};
    ok &= encode(fn, &mX, 4, x, dims, str, box, CU_TENSOR_MAP_SWIZZLE_128B);
  }
  {
    const uintptr_t lo = swapB ? (uintptr_t)B_im : (uintptr_t)B_re, hi = swapB ? (uintptr_t)B_re : (uintptr_t)B_im;
    const cuuint64_t dims[4] = {1024, 8, 2, 128}, str[3] = {2048, (cuuint64_t)(hi - lo), 8 * 2048};
    const cuuint32_t box[4] = {64, 8, 2, 4};
    ok &= encode(fn, &mB, 4, (const void*)lo, dims, str, box, CU_TENSOR_MAP_SWIZZLE_128B);
  }
  {
    const cuuint64_t dims[5] = {1024, 2, 4, 2, 64}, str[4] = {2048, 4 * 2048, 2 * 2048, 16 * 2048};
    const cuuint32_t box[5] = {64, 2, 4, 2, 4};
    ok &= encode(fn, &mCre, 5, C_re, dims, str, box, CU_TENSOR_MAP_SWIZZLE_128B);
    ok &= encode(fn, &mCim, 5, C_im, dims, str, box, CU_TENSOR_MAP_SWIZZLE_128B);
  }
  {
    const cuuint64_t dims[4] = {1024, 2, 4, 256}, str[3] = {4 * 2048, 2048, 8 * 2048};
    const cuuint32_t box[4] = {64, 2, 4, 16};
    ok &= encode(fn, &mXs, 4, x, dims, str, box, CU_TENSOR_MAP_SWIZZLE_128B);
  }
  {
    const cuuint64_t dims[3] = {1024, 64, 32}, str[2] = {32 * 2048, 2048};
    const cuuint32_t box[3] = {16, 32, 4};
    const cuuint64_t dimq[4] = {1024, 8, 32, 8}, strq[3] = {32 * 2048, 2048, 256 * 2048};
    const cuuint32_t boxq[4] = {16, 8, 4, 4};
    ok &= encode(fn, &mQ, 4, q, dimq, strq, boxq, CU_TENSOR_MAP_SWIZZLE_NONE);
    ok &= encode(fn, &mK, 3, k, dims, str, box, CU_TENSOR_MAP_SWIZZLE_32B);
    ok &= encode(fn, &mV, 3, v, dims, str, box, CU_TENSOR_MAP_SWIZZLE_32B);
  }
  {
    const cuuint64_t dims[2] = {32, 65536}, str[1] = {64};
    const cuuint32_t box[2] = {32, 64};
    ok &= encode(fn, &mS, 2, ssm_k, dims, str, box, CU_TENSOR_MAP_SWIZZLE_64B);
  }
  {
    const cuuint64_t dims[3] = {2048, 64, 32}, str[2] = {32 * 8192, 8192};
    const cuuint32_t box[3] = {32, 8, 2};
    ok &= encode(fn, &mO, 3, d_out, dims, str, box, CU_TENSOR_MAP_SWIZZLE_NONE);
  }
  if (!ok) return;
  auto kern = swapB ? fused_kernel<1> : fused_kernel<0>;
  cudaFuncSetAttribute(kern, cudaFuncAttributeMaxDynamicSharedMemorySize, SMEM_BYTES);
  kern<<<NCTA, 512, SMEM_BYTES, cudaStreamPerThread>>>(P, mX, mB, mCre, mCim, mXs, mK, mV, mQ, mS, mO);
}
```

```cpp
#include <cuda_runtime.h>
#include <cuda_bf16.h>
#include <cuda.h>
#include <stdint.h>
#include <type_traits>

namespace {

constexpr int D_DIM = 1024;
constexpr int NCTA = 128;

constexpr int STAGES = 5, STAGE_BYTES = 32768;
constexpr int OFF_RING = 0;
constexpr int OFF_F1 = STAGES * STAGE_BYTES, OFF_F2 = OFF_F1 + 4096, OFF_K = OFF_F2 + 2048, OFF_VP = OFF_K + 8192, OFF_Q = OFF_VP + 4096, OFF_IN = OFF_Q + 8192;
constexpr int OFF_KV = OFF_K;
constexpr int U_CH = 528, U_N8 = 8 * U_CH, OFF_U = OFF_IN + U_N8;
constexpr int OFF_COEF = OFF_U + 8 * U_N8;
constexpr int OFF_DS = OFF_COEF + 2048, OFF_D = OFF_DS + 512;
constexpr int OFF_BAR = OFF_D + 64;
constexpr int SMEM_BYTES = OFF_BAR + 512;
static_assert(SMEM_BYTES <= 232448 && OFF_K % 1024 == 0 && (OFF_U + 3 * U_N8) % 512 == 0 && (4 * U_N8) % 512 == 0, "smem map");
constexpr int B_FULL = 0, B_XI = 5, B_HR = 6, B_HP = 7, B_KVF = 8, B_KF = 11, B_KE = 13, B_QF = 15, B_IN = 19, B_UF = 27, B_Y = 31, B_ACK = 36,
              B_EMPTY = 38, B_COEF = 43, B_KVE = 44, B_NONE = 47, B_EPOCH = 48;
constexpr int QD1 = 8;
constexpr int QD2 = 2;
constexpr int QD3 = 8;
constexpr int QSW = 16;
constexpr int HEAD = 3;
constexpr int ST_T0 = 200;
constexpr int ST_DELAY = 300;
constexpr int XPOS = 32;
constexpr int K_T0 = 800;
constexpr int KV_T0 = 1500;
constexpr int KV_DT = 560;
constexpr int KV_DV = 100;
constexpr int POLL_NS = 30;
constexpr int GREEDY = 1;
constexpr int TAILB = 5;
constexpr int GREG = 176;
constexpr int COEF_T0 = 2500;
constexpr int T_ST = 2;
constexpr int PFC_T0 = 13500;
constexpr int PFC_T1 = 1500;
constexpr int PFC_DT = 400;
constexpr int CFM = 0x40f1;
constexpr int SPIN_LIMIT = 1 << 14;

struct Params {
  unsigned slot[16];
  unsigned zero;
  const __nv_bfloat16 *shift_k, *ssm_D, *lam_re, *lam_im, *log_dt, *Dskip;
  float* out;
};

__device__ __align__(1024) uint4 g_h[16 * 32 * 1024];
__device__ __align__(128) uint2 g_carry[32 * 16 * 32];
__device__ unsigned g_flagH[2 * 16 * 32];
__device__ unsigned g_epoch[NCTA * 32];

__device__ __forceinline__ uint64_t make_desc(uint32_t addr, uint32_t lbo, uint32_t sbo, uint32_t swz) {
  return (uint64_t)((addr & 0x3FFFF) >> 4) | ((uint64_t)(lbo >> 4) << 16) | ((uint64_t)(sbo >> 4) << 32) | ((uint64_t)swz << 62);
}
__device__ __forceinline__ void wg_fence() { asm volatile("wgmma.fence.sync.aligned;" ::: "memory"); }
__device__ __forceinline__ void wg_commit() { asm volatile("wgmma.commit_group.sync.aligned;" ::: "memory"); }
template <int N> __device__ __forceinline__ void wg_wait() { asm volatile("wgmma.wait_group.sync.aligned %0;" ::"n"(N) : "memory"); }
__device__ __forceinline__ void mbar_init(uint32_t bar, int cnt) { asm volatile("mbarrier.init.shared::cta.b64 [%0], %1;" ::"r"(bar), "r"(cnt) : "memory"); }
__device__ __forceinline__ void mbar_expect(uint32_t bar, uint32_t bytes) { asm volatile("mbarrier.arrive.expect_tx.shared::cta.b64 _, [%0], %1;" ::"r"(bar), "r"(bytes) : "memory"); }
__device__ __forceinline__ bool mbar_try(uint32_t bar, uint32_t parity) {
  uint32_t ok;
  asm volatile("{\n.reg .pred p;\nmbarrier.try_wait.parity.shared::cta.b64 p, [%1], %2;\nselp.u32 %0, 1, 0, p;\n}\n" : "=r"(ok) : "r"(bar), "r"(parity) : "memory");
  return ok;
}
__device__ __forceinline__ void mbar_wait(uint32_t bar, uint32_t parity) {
  if (__builtin_expect(!mbar_try(bar, parity), 0)) {
#pragma unroll 1
    for (int n = 0; n < SPIN_LIMIT && !mbar_try(bar, parity); n++) {}
  }
}
__device__ __forceinline__ void mbar_arrive(uint32_t bar) { asm volatile("mbarrier.arrive.shared::cta.b64 _, [%0];" ::"r"(bar) : "memory"); }
__device__ __forceinline__ void mbar_arrive_cta(uint32_t bar, uint32_t cta) {
  asm volatile("{\n.reg .b32 ra;\nmapa.shared::cluster.u32 ra, %0, %1;\nmbarrier.arrive.shared::cluster.b64 _, [ra];\n}\n" ::"r"(bar), "r"(cta) : "memory");
}
__device__ __forceinline__ bool elect_one() {
  uint32_t p;
  asm volatile("{\n.reg .pred P;\nelect.sync _|P, 0xffffffff;\nselp.u32 %0, 1, 0, P;\n}\n" : "=r"(p));
  return p != 0;
}
__device__ __forceinline__ void bar_sync(int id, int n) { asm volatile("bar.sync %0, %1;" ::"r"(id), "r"(n) : "memory"); }
#define TMA_LD(dim) "cp.async.bulk.tensor." dim ".shared::cluster.global.mbarrier::complete_tx::bytes"
__device__ __forceinline__ void tma2d(uint32_t dst, const CUtensorMap* m, int c0, int c1, uint32_t bar) {
  asm volatile(TMA_LD("2d") " [%0], [%1, {%3, %4}], [%2];" ::"r"(dst), "l"(m), "r"(bar), "r"(c0), "r"(c1) : "memory");
}
__device__ __forceinline__ void tma3d(uint32_t dst, const CUtensorMap* m, int c0, int c1, int c2, uint32_t bar) {
  asm volatile(TMA_LD("3d") " [%0], [%1, {%3, %4, %5}], [%2];" ::"r"(dst), "l"(m), "r"(bar), "r"(c0), "r"(c1), "r"(c2) : "memory");
}
__device__ __forceinline__ void tma4d(uint32_t dst, const CUtensorMap* m, int c0, int c1, int c2, int c3, uint32_t bar) {
  asm volatile(TMA_LD("4d") " [%0], [%1, {%3, %4, %5, %6}], [%2];" ::"r"(dst), "l"(m), "r"(bar), "r"(c0), "r"(c1), "r"(c2), "r"(c3) : "memory");
}
__device__ __forceinline__ void tma4d_mc(uint32_t dst, const CUtensorMap* m, int c0, int c1, int c2, int c3, uint32_t bar) {
  asm volatile(TMA_LD("4d") ".multicast::cluster [%0], [%1, {%3, %4, %5, %6}], [%2], %7;" ::"r"(dst), "l"(m), "r"(bar), "r"(c0), "r"(c1), "r"(c2), "r"(c3), "h"((uint16_t)3) : "memory");
}
__device__ __forceinline__ void tma5d_mc(uint32_t dst, const CUtensorMap* m, int c0, int c1, int c2, int c3, int c4, uint32_t bar) {
  asm volatile(TMA_LD("5d") ".multicast::cluster [%0], [%1, {%3, %4, %5, %6, %7}], [%2], %8;" ::"r"(dst), "l"(m), "r"(bar), "r"(c0), "r"(c1), "r"(c2), "r"(c3), "r"(c4), "h"((uint16_t)3) : "memory");
}
__device__ __forceinline__ void bulk_load(uint32_t dst, const void* src, uint32_t bytes, uint32_t bar) {
  asm volatile("cp.async.bulk.shared::cluster.global.mbarrier::complete_tx::bytes [%0], [%1], %2, [%3];" ::"r"(dst), "l"(src), "r"(bytes), "r"(bar) : "memory");
}
__device__ __forceinline__ void bulk_send(uint32_t dst, uint32_t src, uint32_t bytes, uint32_t bar, uint32_t cta) {
  asm volatile("{\n.reg .b32 rd, rb;\nmapa.shared::cluster.u32 rd, %0, %3;\nmapa.shared::cluster.u32 rb, %2, %3;\n"
               "cp.async.bulk.shared::cluster.shared::cta.mbarrier::complete_tx::bytes [rd], [%1], %4, [rb];\n}\n"
               ::"r"(dst), "r"(src), "r"(bar), "r"(cta), "r"(bytes) : "memory");
}
__device__ __forceinline__ void fence_proxy_async_smem() { asm volatile("fence.proxy.async.shared::cta;" ::: "memory"); }
__device__ __forceinline__ void fence_proxy_async_global() { asm volatile("fence.proxy.async.global;" ::: "memory"); }
__device__ __forceinline__ uint32_t clk32() { uint32_t c; asm volatile("mov.u32 %0, %%clock;" : "=r"(c)::"memory"); return c; }
__device__ __forceinline__ void wait_until(uint32_t t0, uint32_t dt) { while (clk32() - t0 < dt) __nanosleep(32); }
__device__ __forceinline__ void spin_until(uint32_t t0, uint32_t dt) { while (clk32() - t0 < dt) {} }
__device__ __forceinline__ void prefetch_map(const CUtensorMap* m) { asm volatile("prefetch.tensormap [%0];" ::"l"(m) : "memory"); }
__device__ __forceinline__ void prefetch_line(const void* p) { asm volatile("prefetch.global.L2 [%0];" ::"l"(p) : "memory"); }
__device__ __forceinline__ unsigned ld_acquire(const unsigned* p) { unsigned v; asm volatile("ld.acquire.gpu.global.u32 %0, [%1];" : "=r"(v) : "l"(p) : "memory"); return v; }
__device__ __forceinline__ unsigned ld_relaxed(const unsigned* p) { unsigned v; asm volatile("ld.relaxed.gpu.global.u32 %0, [%1];" : "=r"(v) : "l"(p) : "memory"); return v; }
__device__ __forceinline__ uint32_t lds32(uint32_t a) { uint32_t v; asm volatile("ld.shared.u32 %0, [%1];" : "=r"(v) : "r"(a)); return v; }
__device__ __forceinline__ uint2 lds64(uint32_t a) { uint2 v; asm volatile("ld.shared.v2.u32 {%0,%1}, [%2];" : "=r"(v.x), "=r"(v.y) : "r"(a) : "memory"); return v; }
__device__ __forceinline__ uint4 lds128(uint32_t a) { uint4 v; asm volatile("ld.shared.v4.u32 {%0,%1,%2,%3}, [%4];" : "=r"(v.x), "=r"(v.y), "=r"(v.z), "=r"(v.w) : "r"(a) : "memory"); return v; }
__device__ __forceinline__ void sts32(uint32_t a, uint32_t v) { asm volatile("st.shared.u32 [%0], %1;" ::"r"(a), "r"(v) : "memory"); }
__device__ __forceinline__ void sts128(uint32_t a, uint4 v) { asm volatile("st.shared.v4.u32 [%0], {%1,%2,%3,%4};" ::"r"(a), "r"(v.x), "r"(v.y), "r"(v.z), "r"(v.w) : "memory"); }
__device__ __forceinline__ void ldsm4(uint32_t* r, uint32_t a) { asm volatile("ldmatrix.sync.aligned.m8n8.x4.shared.b16 {%0,%1,%2,%3}, [%4];" : "=r"(r[0]), "=r"(r[1]), "=r"(r[2]), "=r"(r[3]) : "r"(a) : "memory"); }
__device__ __forceinline__ void ldsm4t(uint32_t* r, uint32_t a) { asm volatile("ldmatrix.sync.aligned.m8n8.x4.trans.shared.b16 {%0,%1,%2,%3}, [%4];" : "=r"(r[0]), "=r"(r[1]), "=r"(r[2]), "=r"(r[3]) : "r"(a) : "memory"); }
__device__ __forceinline__ void stsm4t(uint32_t a, uint32_t r0, uint32_t r1, uint32_t r2, uint32_t r3) {
  asm volatile("stmatrix.sync.aligned.m8n8.x4.trans.shared.b16 [%0], {%1,%2,%3,%4};" ::"r"(a), "r"(r0), "r"(r1), "r"(r2), "r"(r3) : "memory");
}
__device__ __forceinline__ uint4 ldg128_nc(const void* p) { uint4 v; asm volatile("ld.global.nc.L1::no_allocate.v4.u32 {%0,%1,%2,%3}, [%4];" : "=r"(v.x), "=r"(v.y), "=r"(v.z), "=r"(v.w) : "l"(p)); return v; }
__device__ __forceinline__ void stg128(void* p, uint4 v) { asm volatile("st.global.L1::no_allocate.v4.u32 [%0], {%1,%2,%3,%4};" ::"l"(p), "r"(v.x), "r"(v.y), "r"(v.z), "r"(v.w) : "memory"); }
__device__ __forceinline__ uint32_t pack_bf16(float lo, float hi) { uint32_t r; asm("cvt.rn.bf16x2.f32 %0, %1, %2;" : "=r"(r) : "f"(hi), "f"(lo)); return r; }
__device__ __forceinline__ uint32_t bmul2(uint32_t a, uint32_t b) { uint32_t r; asm("mul.rn.bf16x2 %0, %1, %2;" : "=r"(r) : "r"(a), "r"(b)); return r; }
__device__ __forceinline__ uint32_t bfma2(uint32_t a, uint32_t b, uint32_t c) { uint32_t r; asm("fma.rn.bf16x2 %0, %1, %2, %3;" : "=r"(r) : "r"(a), "r"(b), "r"(c)); return r; }
__device__ __forceinline__ uint32_t blo2(uint32_t a) { uint32_t r; asm("{\n.reg .b16 l, h;\nmov.b32 {l, h}, %1;\nmov.b32 %0, {l, l};\n}" : "=r"(r) : "r"(a)); return r; }
__device__ __forceinline__ float bf2f(__nv_bfloat16 v) { return __bfloat162float(v); }

#define R8(d, o) "+f"(d[o]), "+f"(d[o + 1]), "+f"(d[o + 2]), "+f"(d[o + 3]), "+f"(d[o + 4]), "+f"(d[o + 5]), "+f"(d[o + 6]), "+f"(d[o + 7])
#define R16(d, o) R8(d, o), R8(d, o + 8)
#define R64(d, o) R16(d, o), R16(d, o + 16), R16(d, o + 32), R16(d, o + 48)
template <int TA> __device__ __forceinline__ void wgmma_n128(float* d, uint64_t da, uint64_t db, int scale_d) {
  asm volatile("{\n.reg .pred p;\nsetp.ne.b32 p, %66, 0;\n"
    "wgmma.mma_async.sync.aligned.m64n128k16.f32.bf16.bf16 {"
    "%0,%1,%2,%3,%4,%5,%6,%7,%8,%9,%10,%11,%12,%13,%14,%15,%16,%17,%18,%19,%20,%21,%22,%23,%24,%25,%26,%27,%28,%29,%30,%31,"
    "%32,%33,%34,%35,%36,%37,%38,%39,%40,%41,%42,%43,%44,%45,%46,%47,%48,%49,%50,%51,%52,%53,%54,%55,%56,%57,%58,%59,%60,%61,%62,%63"
    "}, %64, %65, p, 1, 1, %67, 0;\n}\n"
    : R64(d, 0)
    : "l"(da), "l"(db), "r"(scale_d), "n"(TA));
}
template <int N> __device__ __forceinline__ void fence_regs(float* d) {
#pragma unroll
  for (int i = 0; i < N; i++) asm volatile("" : "+f"(d[i])::"memory");
}
#define PMFENCE() asm volatile("pmevent 0;" ::: "memory")
__device__ __forceinline__ void cmul(float ar, float ai, float br, float bi, float& cr, float& ci) {
  cr = ar * br - ai * bi; ci = ar * bi + ai * br;
}
__device__ __forceinline__ void csq(float& r, float& i) { const float x = fmaf(r, r, -i * i), y = r * i; r = x; i = y + y; }

#define W8(d, o) "=f"(d[o]), "=f"(d[o + 1]), "=f"(d[o + 2]), "=f"(d[o + 3]), "=f"(d[o + 4]), "=f"(d[o + 5]), "=f"(d[o + 6]), "=f"(d[o + 7])
#define L16 "{%0,%1,%2,%3,%4,%5,%6,%7,%8,%9,%10,%11,%12,%13,%14,%15}"
#define L32 "{%0,%1,%2,%3,%4,%5,%6,%7,%8,%9,%10,%11,%12,%13,%14,%15,%16,%17,%18,%19,%20,%21,%22,%23,%24,%25,%26,%27,%28,%29,%30,%31}"
template <int ACC, int TB> __device__ __forceinline__ void rs_n32(float* d, const uint32_t* a, uint64_t db) {
  if constexpr (ACC) asm volatile("wgmma.mma_async.sync.aligned.m64n32k16.f32.bf16.bf16 " L16 ", {%16,%17,%18,%19}, %20, 1, 1, 1, %21;" : R16(d, 0) : "r"(a[0]), "r"(a[1]), "r"(a[2]), "r"(a[3]), "l"(db), "n"(TB));
  else asm volatile("wgmma.mma_async.sync.aligned.m64n32k16.f32.bf16.bf16 " L16 ", {%16,%17,%18,%19}, %20, 0, 1, 1, %21;" : W8(d, 0), W8(d, 8) : "r"(a[0]), "r"(a[1]), "r"(a[2]), "r"(a[3]), "l"(db), "n"(TB));
}
template <int ACC, int TB> __device__ __forceinline__ void ss_n64(float* d, uint64_t da, uint64_t db) {
  if constexpr (ACC) asm volatile("wgmma.mma_async.sync.aligned.m64n64k16.f32.bf16.bf16 " L32 ", %32, %33, 1, 1, 1, 0, %34;" : R16(d, 0), R16(d, 16) : "l"(da), "l"(db), "n"(TB));
  else asm volatile("wgmma.mma_async.sync.aligned.m64n64k16.f32.bf16.bf16 " L32 ", %32, %33, 0, 1, 1, 0, %34;" : W8(d, 0), W8(d, 8), W8(d, 16), W8(d, 24) : "l"(da), "l"(db), "n"(TB));
}
template <int ACC> __device__ __forceinline__ void ss_n32_tt(float* d, uint64_t da, uint64_t db) {
  if constexpr (ACC) asm volatile("wgmma.mma_async.sync.aligned.m64n32k16.f32.bf16.bf16 " L16 ", %16, %17, 1, 1, 1, 1, 1;" : R16(d, 0) : "l"(da), "l"(db));
  else asm volatile("wgmma.mma_async.sync.aligned.m64n32k16.f32.bf16.bf16 " L16 ", %16, %17, 0, 1, 1, 1, 1;" : W8(d, 0), W8(d, 8) : "l"(da), "l"(db));
}
__device__ __forceinline__ void stsm4(uint32_t a, uint32_t r0, uint32_t r1, uint32_t r2, uint32_t r3) {
  asm volatile("stmatrix.sync.aligned.m8n8.x4.shared.b16 [%0], {%1,%2,%3,%4};" ::"r"(a), "r"(r0), "r"(r1), "r"(r2), "r"(r3) : "memory");
}
template <int N> __device__ __forceinline__ void fence_u32(uint32_t* d) {
#pragma unroll
  for (int i = 0; i < N; i++) asm volatile("" : "+r"(d[i])::"memory");
}
__device__ __forceinline__ void pack32(uint32_t* f, const float* z) {
#pragma unroll
  for (int i = 0; i < 16; i++) f[i] = pack_bf16(z[2 * i], z[2 * i + 1]);
}
template <int INV> __device__ __forceinline__ void twiddle(uint32_t* f, const uint32_t* tp, const uint32_t* ts) {
#pragma unroll
  for (int i = 0; i < 8; i++) {
    uint32_t x = f[2 * i + INV], y = f[2 * i + 1 - INV];
    x = bfma2(tp[i & 3], y, x); y = bfma2(ts[i & 3], x, y); x = bfma2(tp[i & 3], y, x);
    f[2 * i + INV] = x; f[2 * i + 1 - INV] = y;
  }
}
__device__ __forceinline__ uint32_t bfnma2(uint32_t a, uint32_t b, uint32_t c) { uint32_t r; asm("{\n.reg .b32 t;\nmul.bf16x2 t, %1, %2;\nsub.bf16x2 %0, %3, t;\n}" : "=r"(r) : "r"(a), "r"(b), "r"(c)); return r; }
__device__ __forceinline__ uint32_t bfms2(uint32_t a, uint32_t b, uint32_t c) { uint32_t r; asm("{\n.reg .b32 t;\nmul.bf16x2 t, %1, %2;\nsub.bf16x2 %0, t, %3;\n}" : "=r"(r) : "r"(a), "r"(b), "r"(c)); return r; }
template <int ADD> __device__ __forceinline__ void bimac(uint32_t* o, const uint32_t* a, const uint32_t* b, const uint32_t* c) {
#pragma unroll
  for (int J = 0; J < 2; J++) {
    const uint32_t Pr = a[2 * J], Pi = a[2 * J + 1], Qr = a[2 * J + 4], Qi = a[2 * J + 5], pr = b[2 * J], pi = b[2 * J + 1], qr = b[2 * J + 4], qi = b[2 * J + 5];
    uint32_t x0, x1, x2, x3;
    if (ADD == 0) { x0 = bmul2(Pr, pr); x1 = bmul2(Pr, pi); x2 = bmul2(Pr, qr); x3 = bmul2(Pr, qi); }
    if (ADD == 1) { x0 = bfma2(Pr, pr, c[2 * J]); x1 = bfma2(Pr, pi, c[2 * J + 1]); x2 = bfma2(Pr, qr, c[2 * J + 4]); x3 = bfma2(Pr, qi, c[2 * J + 5]); }
    if (ADD == 2) { x0 = bfma2(Pr, pr, c[2 * J + 1]); x1 = bfms2(Pr, pi, c[2 * J]); x2 = bfma2(Pr, qr, c[2 * J + 5]); x3 = bfms2(Pr, qi, c[2 * J + 4]); }
    x0 = bfnma2(Pi, pi, x0); x1 = bfma2(Pi, pr, x1); x2 = bfnma2(Pi, qi, x2); x3 = bfma2(Pi, qr, x3);
    x0 = bfnma2(Qr, qr, x0); x1 = bfnma2(Qr, qi, x1); x2 = bfma2(Qr, pr, x2); x3 = bfma2(Qr, pi, x3);
    x0 = bfma2(Qi, qi, x0); x1 = bfnma2(Qi, qr, x1); x2 = bfnma2(Qi, pi, x2); x3 = bfma2(Qi, pr, x3);
    o[2 * J] = x0; o[2 * J + 1] = x1; o[2 * J + 4] = x2; o[2 * J + 5] = x3;
  }
}
__device__ __forceinline__ void sincos8k(int n, float& s, float& c) {
  const float x = (float)((n << 19) >> 19) * (6.283185307179586f / 8192.f);
  s = __sinf(x); c = __cosf(x);
}
__device__ __forceinline__ void fft_tables(uint32_t f1a, uint32_t f2a, int w, int lane, uint32_t* tp, uint32_t* ts, float& d0r, float& d0i) {
  const int c = lane & 3, f1 = 8 * w + (lane >> 2);
#pragma unroll 1
  for (int J = 3; J >= 0; J--) {
    const int a = 8 * J + 2 * c;
    float s0, c0, s1, c1;
    sincos8k(64 * (4 * f1 + 1) * a + 31 * (4 * f1 - 63), d0i, d0r); sincos8k(64 * (4 * f1 + 1) * (a + 1) + 31 * (4 * f1 - 63), s1, c1);
    d0r *= 0.125f; d0i *= 0.125f;
    sts32(f1a + w * 1024 + J * 128 + lane * 4, pack_bf16(d0r, 0.125f * c1)); sts32(f1a + w * 1024 + 512 + J * 128 + lane * 4, pack_bf16(d0i, 0.125f * s1));
    sincos8k(128 * (2 * (a & 15) + 1) * f1 - 128 * (a & 16), s0, c0); sincos8k(128 * (2 * (a & 15) + 3) * f1 - 128 * (a & 16), s1, c1);
    sts32(f2a + w * 512 + J * 128 + lane * 4, pack_bf16(c0, c1));
    sincos8k((4 * f1 - 63) * (2 * a - 31), s0, c0); sincos8k((4 * f1 - 63) * (2 * a - 29), s1, c1);
#pragma unroll
    for (int i = 3; i > 0; i--) { ts[i] = ts[i - 1]; tp[i] = tp[i - 1]; }
    ts[0] = pack_bf16(s0, s1); tp[0] = pack_bf16(-__fdividef(s0, 1.f + c0), -__fdividef(s1, 1.f + c1));
  }
  if (c != 0) d0r = d0i = 0.f;
}

__device__ __forceinline__ void ss_n16(float* d, uint64_t da, uint64_t db) {
  asm volatile("wgmma.mma_async.sync.aligned.m64n16k16.f32.bf16.bf16 {%0,%1,%2,%3,%4,%5,%6,%7}, %8, %9, 0, 1, 1, 0, 0;" : W8(d, 0) : "l"(da), "l"(db));
}
template <int N> __device__ __forceinline__ void rename_regs(float* d) {
#pragma unroll
  for (int i = 0; i < N; i++) { float t; asm volatile("mov.b32 %0, %1;" : "=f"(t) : "f"(d[i]) : "memory"); d[i] = t; }
}

template <int SWAPB>
__global__ void __cluster_dims__(2, 1, 1) __launch_bounds__(512, 1)
fused_kernel(const __grid_constant__ Params P, const __grid_constant__ CUtensorMap mX, const __grid_constant__ CUtensorMap mB,
             const __grid_constant__ CUtensorMap mCre, const __grid_constant__ CUtensorMap mCim, const __grid_constant__ CUtensorMap mXs,
             const __grid_constant__ CUtensorMap mK, const __grid_constant__ CUtensorMap mV, const __grid_constant__ CUtensorMap mQ, const __grid_constant__ CUtensorMap mS,
             const __grid_constant__ CUtensorMap mO) {
  extern __shared__ __align__(1024) uint8_t smem_raw[];
  const uint32_t sb = (uint32_t)__cvta_generic_to_shared(smem_raw);
  const uint32_t bars = sb + OFF_BAR;
  const int slot = (P.slot[blockIdx.x >> 3] >> (4 * (blockIdx.x & 6))) & 63, rank = blockIdx.x & 1;
  const int j = slot & 7, tc = 2 * (slot >> 3) + rank, b = 2 * slot + rank;
  const int tid = threadIdx.x;
  const int warp = __shfl_sync(0xffffffffu, tid >> 5, 0);
  const int wg = warp >> 2;
  const uint32_t c_start = clk32();
  auto kblock = [&](int n) { return ((n & 14) == 0 || (n & 14) == 2 * j ? n ^ (2 * j) : n) & 31; };
  auto send_y = [&](int r) {
    const uint32_t src = sb + OFF_U + 4 * (rank ^ 1) * U_N8 + r * U_CH, dst = r >= 2 ? sb + OFF_U + 4 * rank * U_N8 + (r - 2) * U_CH : sb + OFF_IN + 96 + r * 2064;
#pragma unroll 1
    for (int n = 0; n < 4; n++) bulk_send(dst + n * (r >= 2 ? U_N8 : 512), src + n * U_N8, 512, bars + (B_IN + r) * 8, rank ^ 1);
  };
  auto load_q = [&](int i, int off, int bar) {
    const uint32_t fb = bars + bar * 8 + 4 * (i & 2);
    mbar_expect(fb, 4096); tma4d(sb + off + 2048 * (i & 2), &mQ, 16 * slot, 0, 4 * i, 4 * rank, fb);
  };
  auto head = [&](int n) {
    const uint32_t fb = bars + (B_FULL + n) * 8, dst = sb + OFF_RING + n * STAGE_BYTES;
    mbar_expect(fb, STAGE_BYTES);
    tma4d(dst + 16384, &mX, 64 * n, 0, 4 * tc, 0, fb);
    tma4d(dst, &mB, 64 * n, 0, 0, 8 * j, fb);
    tma4d(dst + 8192, &mB, 64 * n, 0, 0, 8 * j + 4, fb);
  };
  if (warp == 0 && elect_one()) {
#pragma unroll
    for (int s = 0; s < STAGES; s++) mbar_init(bars + (B_FULL + s) * 8, 1);
    head(0);
    asm volatile("fence.mbarrier_init.release.cluster;" ::: "memory");
  }
  if (wg == 3 && elect_one()) {
    if (warp < 15) {
#pragma unroll
      for (int s = 0; s < 11; s++) mbar_init(bars + 8 * B_XI + (warp & 3) * 88 + 8 * s, 1);
    } else {
#pragma unroll
      for (int s = B_EMPTY; s <= B_NONE; s++) mbar_init(bars + 8 * s, s < B_COEF ? 2 : s == B_COEF ? 128 : 4);
    }
    asm volatile("fence.mbarrier_init.release.cluster;" ::: "memory");
  }
  __syncwarp();
  asm volatile("barrier.cluster.arrive.relaxed.aligned;" ::: "memory");
  if (warp == 0 && elect_one()) {
#pragma unroll 1
    for (int n = 1; n < HEAD; n++) { spin_until(c_start, ST_T0 + n * ST_DELAY); head(n); }
  }
  __syncwarp();
#define CLUSTER_WAIT() asm volatile("barrier.cluster.wait.aligned;" ::: "memory")

  if (wg == 3) {
    asm volatile("setmaxnreg.dec.sync.aligned.u32 24;");
    CLUSTER_WAIT();
    if (warp < 14) {
      if (elect_one()) {
        uint32_t so = 8 * (HEAD % STAGES), ph = HEAD < STAGES;
        auto step = [&](auto issue) {
          mbar_wait(bars + B_EMPTY * 8 + so, ph);
          issue(sb + OFF_RING + (so << 12), bars + B_FULL * 8 + so);
          so += 8;
          if (so == 8 * STAGES) { so = 0; ph ^= 1; }
        };
        if (warp == 12) {
          auto g1 = [&](int n0, int n1, int grp) {
#pragma unroll 1
            for (int n = n0; n < n1; n++) step([&](uint32_t dst, uint32_t fb) { mbar_expect(fb, STAGE_BYTES); tma4d_mc(dst + rank * 8192, &mB, n * 64, 0, 0, grp + 4 * rank, fb); });
          };
#pragma unroll 1
          for (int n = HEAD; n < STAGES; n++) { spin_until(c_start, ST_T0 + n * ST_DELAY); g1(n, n + 1, 8 * j); }
          g1(STAGES, 16, 8 * j);
          g1(0, XPOS - 16, 8 * j + 64);
          step([&](uint32_t dst, uint32_t fb) { mbar_expect(fb, STAGE_BYTES); tma4d(dst, &mXs, 128 * j, 0, 4 * tc, 0, fb); });
#pragma unroll 1
          for (int n = 0; n < 32; n += 2) {
            const int col = kblock(n) * 32;
#pragma unroll
            for (int part = 0; part < 2; part++)
              step([&](uint32_t dst, uint32_t fb) { mbar_expect(fb, STAGE_BYTES); tma5d_mc(dst + rank * 8192, part ? &mCim : &mCre, col, 0, 0, 0, 8 * j + 4 * rank, fb); });
          }
        } else {
          auto g1 = [&](int n0, int n1, int nb) {
#pragma unroll 1
            for (int n = n0; n < n1; n++) step([&](uint32_t dst, uint32_t fb) { tma4d(dst + 16384, &mX, n * 64, 0, 4 * tc, 0, fb); });
          };
          auto g2 = [&](int n0, int n1) {
#pragma unroll 1
            for (int n = n0; n < n1; n++) step([&](uint32_t dst, uint32_t fb) { bulk_load(dst + 16384, g_h + (32 * tc + kblock(n)) * 1024, 16384, fb); });
          };
#pragma unroll 1
          for (int n = HEAD; n < STAGES; n++) { spin_until(c_start, ST_T0 + n * ST_DELAY); g1(n, n + 1, 0); }
          g1(STAGES, 16, 0);
          g1(0, XPOS - 16, 16);
          step([&](uint32_t dst, uint32_t fb) { tma4d(dst + 16384, &mXs, 128 * j + 64, 0, 4 * tc, 0, fb); });
#pragma unroll 1
          for (int v = 0; v < 2; v++) {
            mbar_wait(bars + B_HP * 8, v);
            fence_proxy_async_global();
            g2(16 * v, 16 * v + 2);
            mbar_wait(bars + B_HR * 8, v);
            fence_proxy_async_global();
            g2(16 * v + 2, 16 * v + 16);
          }
        }
      }
    } else if (warp == 15) {
      mbar_wait(bars + B_COEF * 8, 0);
      const unsigned epoch = lds32(bars + B_EPOCH * 8);
#pragma unroll 1
      for (int v = 0; v < 2; v++) {
        unsigned* fp = &g_flagH[(16 * v + tc) * 32];
        if (elect_one()) {
          wait_until(v ? clk32() : c_start, (v ? PFC_T1 : PFC_T0) + (slot >> 3) * PFC_DT);
#pragma unroll
          for (int part = 0; part < 2; part++)
            asm volatile("cp.async.bulk.prefetch.tensor.5d.L2.global [%0, {%1, %2, %2, %2, %3}];" ::"l"(part ? &mCim : &mCre), "r"(512 * v + 8 * (slot & 56)), "r"(0), "r"(8 * j + 4 * rank) : "memory");
        }
        __syncwarp();
        bar_sync(4 + v, 160);
        if (elect_one()) {
          asm volatile("red.release.gpu.global.add.u32 [%0], 1;" ::"l"(fp) : "memory");
          mbar_arrive(bars + B_HP * 8);
          int it = 0;
          while (ld_acquire(fp) != 8 * epoch && ++it < (SPIN_LIMIT << 4)) __nanosleep(POLL_NS);
          mbar_arrive(bars + B_HR * 8);
        }
        __syncwarp();
      }
    } else if (elect_one()) {
      const int ch0 = 16 * slot;
      auto load_k = [&](int s, uint32_t dst) { const uint32_t fb = bars + (B_KF + (s & 1)) * 8; mbar_expect(fb, 4096); tma2d(dst, &mS, 0, 64 * (8 * b + s), fb); };
      prefetch_map(&mS); prefetch_map(&mK); prefetch_map(&mV);
      wait_until(c_start, K_T0);
      load_k(0, sb + OFF_U + (4 * rank + 3) * U_N8); load_k(1, sb + OFF_U + (4 * rank + 3) * U_N8 - 4096);
      {
        uint32_t so = 16, ph = 1;
#pragma unroll 1
        for (int e = 0; e < 9; e++) {
          const uint32_t fb = bars + B_KVF * 8 + so, dst = sb + OFF_KV + (so << 10);
          wait_until(c_start, KV_T0 + (e ? 2 * e - 1 : 0) * KV_DT);
          mbar_wait(bars + B_KVE * 8 + so, ph);
          const uint32_t c1 = clk32();
          mbar_expect(fb, e ? 8192 : 4096);
          tma3d(dst, &mK, ch0, 32 * rank - (e == 0), (4 * e - 4) & 31, fb);
          if (e > 0) { wait_until(c1, KV_DV); tma3d(dst + 4096, &mV, ch0, 32 * rank, 4 * e - 4, fb); }
          so += 8;
          if (so == 24) so = 0;
          if (so == 16) ph ^= 1;
        }
      }
      prefetch_map(&mCre); prefetch_map(&mCim); prefetch_map(&mXs); prefetch_map(&mQ); prefetch_map(&mO);
      mbar_wait(bars + B_KVE * 8, 0);
      load_k(2, sb + OFF_K); load_k(3, sb + OFF_K + 4096);
      mbar_wait(bars + (B_UF + 3) * 8, 0);
#pragma unroll 1
      for (int ch = 0; ch < 7; ch++) {
        if (ch > 0) {
          mbar_wait(bars + (B_Y + (ch & 3)) * 8, ch >> 2);
          if (ch > 2) mbar_wait(bars + (B_IN + ch - 3) * 8, 0);
          send_y(ch - 1);
        }
        if (ch < 6) {
          mbar_wait(bars + (B_KE + (ch & 1)) * 8, (ch >> 1) & 1);
          if (ch < 4) load_k(ch + 4, sb + OFF_K + (ch & 1) * 4096);
          if (ch == 3) asm volatile("cp.async.bulk.prefetch.tensor.4d.L2.global [%0, {%1, %2, %3, %4}];" ::"l"(&mQ), "r"(16 * (slot & ~3)), "r"(0), "r"(16 + 4 * (slot & 3)), "r"(4 * rank) : "memory");
          if (ch == 2) load_q(1, OFF_Q, B_QF);
          if (ch >= 4) load_q(2 * (ch & 1), OFF_K, B_KF);
          if (ch == 4) { mbar_wait(bars + B_XI * 8, 0); load_q(3, OFF_Q, B_QF); }
        }
      }
    }
    return;
  } else if (wg == 2) {
    asm volatile("setmaxnreg.inc.sync.aligned.u32 %0;" ::"n"(488 - 2 * GREG));
    const int t = tid & 127, w = warp & 3, lane = t & 31, g = lane >> 2, c = lane & 3;
    const uint4 s2[2] = {ldg128_nc(P.shift_k + (8 * b + 2 * c) * 4), ldg128_nc(P.shift_k + (8 * (b ^ 1) + 2 * c) * 4)};
    const uint32_t dskip = __bfloat16_as_ushort(P.ssm_D[8 * b + (t & 7)]);
    uint32_t tp[4] = {}, ts[4] = {};
    float d0r, d0i;
    fft_tables(sb + OFF_F1, sb + OFF_F2, w, lane, tp, ts, d0r, d0i);
    CLUSTER_WAIT();
    if (t < 12) mbar_expect(bars + (B_IN + t) * 8, t < 6 ? 2048 : t < 8 ? 4 * (U_CH + 512) : U_N8);
    if (t < 8) sts32(sb + OFF_D + 4 * t, dskip << 16);
    const uint64_t dF1a = make_desc(sb + OFF_F1, 128, 512, 0), dF1b = make_desc(sb + OFF_F1, 512, 128, 0);
    const uint64_t dF2f = make_desc(sb + OFF_F2, 512, 128, 0), dF2i = make_desc(sb + OFF_F2, 128, 512, 0);
    auto T1k = [&](float* z, uint64_t dk) { wg_fence(); ss_n64<0, 1>(z, dF1a, dk); ss_n64<1, 1>(z, dF1a + 16, dk + 64); wg_commit(); };
    auto T1u = [&](float* z, uint64_t du) { wg_fence(); ss_n64<0, 0>(z, dF1a, du); ss_n64<1, 0>(z, dF1a + 16, du + 16); wg_commit(); };
    auto T2 = [&](float* s, const uint32_t* f) {
      wg_fence();
      rs_n32<0, 1>(s, f, dF2f); rs_n32<0, 1>(s + 16, f + 8, dF2f); rs_n32<1, 1>(s, f + 4, dF2f + 64); rs_n32<1, 1>(s + 16, f + 12, dF2f + 64);
      wg_commit();
    };
    auto product = [&](uint32_t* pr, const uint32_t* kh, const uint32_t* uh) {
      bimac<0>(pr, kh, uh, pr); bimac<2>(pr + 8, kh + 8, uh, pr); bimac<1>(pr + 8, kh, uh + 8, pr + 8);
      fence_u32<16>(pr);
    };
    float zk[32] = {};
    uint32_t pr[16];
    {
      uint32_t kh0[16];
      {
        float z0[32], sk[32];
        uint32_t fk[16];
        const uint64_t dk = make_desc(sb + OFF_U + (4 * rank + 3) * U_N8, 2048, 512, 2);
        fence_proxy_async_smem();
        bar_sync(7, 128);
        mbar_wait(bars + B_KF * 8, 0);
        T1k(z0, dk);
        mbar_wait(bars + (B_KF + 1) * 8, 0);
        T1k(zk, dk - 256);
        wg_wait<0>(); fence_regs<32>(z0); fence_regs<32>(zk);
        const float dd = __uint_as_float(lds32(sb + OFF_D));
        z0[0] = fmaf(d0r, dd, z0[0]); z0[2] = fmaf(d0i, dd, z0[2]);
        pack32(fk, z0); twiddle<0>(fk, tp, ts); fence_u32<16>(fk);
        T2(sk, fk);
        wg_wait<0>(); fence_regs<32>(sk); fence_u32<16>(fk);
        pack32(kh0, sk); fence_u32<16>(kh0);
      }
      {
        uint32_t sk[2][4], kx[2][8];
#pragma unroll
        for (int o = 0; o < 2; o++) {
          sk[o][0] = __byte_perm(s2[o].x, s2[o].z, 0x5410); sk[o][1] = __byte_perm(s2[o].x, s2[o].z, 0x7632);
          sk[o][2] = __byte_perm(s2[o].y, s2[o].w, 0x5410); sk[o][3] = __byte_perm(s2[o].y, s2[o].w, 0x7632);
        }
        const uint32_t la = sb + OFF_KV + (lane >> 3) * 1024 + (8 * w + (lane & 7)) * 32 + ((rank ^ ((lane >> 2) & 1)) << 4);
        const uint32_t uo = (lane & 7) * U_CH + w * 128 + (lane >> 3) * 16;
        mbar_wait(bars + (B_KVF + 2) * 8, 0);
        ldsm4(kx[0], la + 16384); ldsm4(kx[1], (la ^ 16) + 16384);
        if (lane == 0) mbar_arrive(bars + (B_KVE + 2) * 8 + (kx[0][1] & kx[1][1] & P.zero));
        uint32_t so = 0, ph = 0;
#pragma unroll 1
        for (int n = 0; n < 4; n++) {
          const uint32_t own = sb + OFF_U + (4 * rank + n) * U_N8, box = n < 3 ? sb + OFF_U + (4 * (rank ^ 1) + n + 1) * U_N8 : sb + OFF_IN;
#pragma unroll
          for (int e = 0; e < 2; e++) {
            uint32_t vx[2][4];
            mbar_wait(bars + B_KVF * 8 + so, ph);
#pragma unroll
            for (int o = 0; o < 2; o++) { ldsm4(kx[o] + 4, (la ^ (16 * o)) + (so << 10)); ldsm4(vx[o], (la ^ (16 * o)) + (so << 10) + 4096); }
            if (lane == 0) mbar_arrive(bars + B_KVE * 8 + so + (kx[0][4] & kx[1][4] & vx[0][0] & vx[1][0] & P.zero));
#pragma unroll
            for (int o = 0; o < 2; o++) {
#pragma unroll
              for (int i = 0; i < 4; i++) vx[o][i] = bmul2(bfma2(kx[o][i + 4], sk[o][0], bfma2(kx[o][i + 3], sk[o][1], bfma2(kx[o][i + 2], sk[o][2], bmul2(kx[o][i + 1], sk[o][3])))), vx[o][i]);
              stsm4t((o ? box : own) + uo + e * 64, vx[o][0], vx[o][1], vx[o][2], vx[o][3]);
              kx[o][1] = kx[o][5]; kx[o][2] = kx[o][6]; kx[o][3] = kx[o][7];
            }
            so += 8;
            if (so == 24) so = 0;
            if (so == 16) ph ^= 1;
          }
          fence_proxy_async_smem();
          bar_sync(7, 128);
          if (w == 0 && elect_one()) {
            if (n > 0) mbar_wait(bars + B_UF * 8 + 8 * (n - 1), 0);
            bulk_send(own, box, U_N8, bars + B_UF * 8 + 8 * n, rank ^ 1);
          }
          __syncwarp();
        }
      }
      float zu[32], su[32];
      uint32_t fu[16], uh[16];
#pragma unroll
      for (int n = 0; n < 4; n++) mbar_wait(bars + (B_UF + n) * 8, 0);
      T1u(zu, make_desc(sb + OFF_U, 128, U_N8, 0));
      wg_wait<0>(); fence_regs<32>(zu);
      pack32(fu, zu); twiddle<0>(fu, tp, ts); fence_u32<16>(fu);
      T2(su, fu);
      wg_wait<0>(); fence_regs<32>(su); fence_u32<16>(fu);
      pack32(uh, su);
      product(pr, kh0, uh);
    }
    {
#define CF(i) do { if ((CFM >> (i)) & 1) PMFENCE(); } while (0)
      const uint32_t vs = w < 2 ? 512 : U_N8;
      uint32_t va = (w < 2 ? sb + OFF_VP : sb + OFF_U) + ((lane >> 4) & 1) * vs + (w & 1) * 256 + (lane & 15) * 16;
      uint32_t ya = sb + OFF_U + (2 * w + ((lane >> 3) & 1)) * U_N8 + (lane >> 4) * 128 + (lane & 7) * 16;
      uint64_t du = make_desc(sb + OFF_U, 128, U_N8, 0), dk = make_desc(sb + OFF_K, 2048, 512, 2);
      const uint64_t dv = make_desc(sb + OFF_VP, 128, 512, 0);
      uint32_t yp[8] = {};
      uint32_t yq = sb + OFF_Q + lane * 16;
      auto store_y = [&]() { stsm4(yq, yp[0], yp[1], yp[2], yp[3]); stsm4(yq + 256, yp[4], yp[5], yp[6], yp[7]); };
      auto step = [&](int ch, auto fwd) {
        constexpr bool FWD = decltype(fwd)::value;
        float zu[32], sk[32], su[32], v[32], y[16];
        uint32_t kh[16], uh[16], fk[16], fu[16], fv[16];
        wg_fence();
        rs_n32<0, 0>(v, pr, dF2i); rs_n32<0, 0>(v + 16, pr + 8, dF2i); rs_n32<1, 0>(v, pr + 4, dF2i + 16); rs_n32<1, 0>(v + 16, pr + 12, dF2i + 16);
        wg_commit();
        CF(0);
        store_y();
        if (FWD) {
          const float dd = __uint_as_float(lds32(sb + OFF_D + 4 * (ch + 1)));
          zk[0] = fmaf(d0r, dd, zk[0]); zk[2] = fmaf(d0i, dd, zk[2]);
          pack32(fk, zk); twiddle<0>(fk, tp, ts); fence_u32<16>(fk);
          T2(sk, fk);
          CF(2);
          mbar_wait(bars + (B_KF + (ch & 1)) * 8, ((ch >> 1) & 1) ^ 1);
          wg_wait<1>();
        } else {
#pragma unroll
          for (int r = 3; r < 6; r++) mbar_wait(bars + (B_IN + r) * 8, 0);
          wg_wait<0>();
        }
        fence_regs<32>(v); fence_u32<16>(pr);
        pack32(fv, v); fence_u32<16>(fv);
        CF(4);
        if (FWD) T1u(zu, du + U_CH / 16);
        CF(5);
        if (FWD) { wg_wait<1>(); fence_regs<32>(sk); fence_u32<16>(fk); pack32(kh, sk); }
        twiddle<1>(fv, tp, ts);
#pragma unroll
        for (int i = 0; i < 4; i++) stsm4(va + 2 * i * vs, fv[4 * i], fv[4 * i + 1], fv[4 * i + 2], fv[4 * i + 3]);
        if (FWD) {
          fence_u32<16>(kh);
          CF(7);
          T1k(zk, dk);
          CF(8);
          wg_wait<1>(); fence_regs<32>(zu);
          pack32(fu, zu); twiddle<0>(fu, tp, ts); fence_u32<16>(fu);
          T2(su, fu);
          CF(10);
        }
        fence_proxy_async_smem();
        bar_sync(7, 128);
        wg_fence();
        ss_n32_tt<0>(y, dv, dF1b); ss_n32_tt<1>(y, dv + 16, dF1b + 64); ss_n32_tt<1>(y, du, dF1b + 128); ss_n32_tt<1>(y, du + 16, dF1b + 192);
        wg_commit();
        if (FWD && t == 0) mbar_arrive(bars + (B_Y + (ch & 3)) * 8);
        CF(12);
        if (FWD) {
          wg_wait<1>(); fence_regs<32>(su); fence_u32<16>(fu); fence_regs<32>(zk);
          if (t == 0) mbar_arrive(bars + (B_KE + (ch & 1)) * 8);
          pack32(uh, su);
          bimac<0>(pr, kh, uh, pr); bimac<2>(pr + 8, kh + 8, uh, pr); fence_u32<16>(pr);
          CF(14);
          wg_wait<0>(); fence_regs<16>(y);
          bimac<1>(pr + 8, kh, uh + 8, pr + 8); fence_u32<8>(pr + 8);
          du += U_CH / 16; dk += (ch & 1) ? -256 : 256;
          if (w >= 2) va += U_CH;
        }
        if (!FWD) { wg_wait<0>(); fence_regs<16>(y); }
#pragma unroll
        for (int i = 0; i < 8; i++) yp[i] = pack_bf16(y[2 * i], y[2 * i + 1]);
        fence_u32<8>(yp);
        yq = ya;
        ya += U_CH;
      };
#pragma unroll 1
      for (int ch = 0; ch < 7; ch++) step(ch, std::true_type());
      step(7, std::false_type());
      store_y();
    }
    fence_proxy_async_smem();
    bar_sync(7, 128);
    if (elect_one()) bulk_send(sb + OFF_U + (4 * rank + w) * U_N8 + 4 * U_CH, sb + OFF_U + (4 * (rank ^ 1) + w) * U_N8 + 6 * U_CH, U_CH + 512, bars + (B_IN + 6) * 8, rank ^ 1);
    __syncwarp();
    asm volatile("bar.arrive 9, 256;" ::: "memory");
  } else {
    asm volatile("setmaxnreg.inc.sync.aligned.u32 %0;" ::"n"(GREG));
    const int t = tid & 127, w = warp & 3, lane = t & 31, g = lane >> 2, c = lane & 3;
    if (wg == 1) {
      wait_until(c_start, COEF_T0);
      const int p = 64 * j + (t & 63) + 8 * (t & 64);
      const float Lr = bf2f(P.lam_re[p]), Li = bf2f(P.lam_im[p]);
      const uint32_t ds = __bfloat16_as_ushort(P.Dskip[128 * j + t]);
      const unsigned epoch = ld_relaxed(&g_epoch[b * 32]) + 1;
      const float dt = bf2f(__float2bfloat16_rn(expf(bf2f(P.log_dt[p]))));
      const float e = expf(dt * Lr);
      float sn, cs;
      {
        const double z = (double)(dt * Li) * 0.15915494309189535;
        sincospif(2.f * (float)(z - rint(z)), &sn, &cs);
      }
      const float lr = e * cs, li = e * sn;
      const float nr = lr - 1.0f, ni = li;
      const bool big = fabsf(Lr) >= fabsf(Li);
      const float la = big ? Lr : Li, lb = big ? Li : Lr, r = __fdiv_rn(lb, la), inv = __frcp_rn(fmaf(lb, r, la));
      const float br = (big ? fmaf(ni, r, nr) : fmaf(nr, r, ni)) * inv, bi = (big ? fmaf(-nr, r, ni) : fmaf(ni, r, -nr)) * inv;
      sts128(sb + OFF_COEF + t * 16, make_uint4(__float_as_uint(lr), __float_as_uint(li), pack_bf16(2.f * br, 2.f * br), pack_bf16(-2.f * bi, -2.f * bi)));
      sts32(sb + OFF_DS + 4 * t, ds << 16);
      if (t == 0) sts32(bars + B_EPOCH * 8, epoch);
    }
    CLUSTER_WAIT();
    if (wg == 1) mbar_arrive(bars + B_COEF * 8);
    float d[128];
    uint32_t so = 0, ph = 0, po = 0;
    uint32_t ra;
    auto set_ra = [&]() { asm volatile("mapa.shared::cluster.u32 %0, %1, %2;" : "=r"(ra) : "r"(bars + B_EMPTY * 8), "r"((t & 1) ? rank ^ 1 : rank)); };
    set_ra();
    auto release = [&](uint32_t off) { if (t < 2) asm volatile("mbarrier.arrive.shared::cluster.b64 _, [%0];" ::"r"(ra + off) : "memory"); };
    constexpr uint32_t NOBAR = 8 * (B_NONE - B_EMPTY);
    auto block = [&](auto ta, uint64_t da0, uint64_t db0, bool zero, int nn) {
      constexpr int PH = decltype(ta)::value, TA = PH > 0, KS = TA ? 128 : 2, QD = PH == 0 ? QD1 : PH == 1 ? QD2 : QD3;
      mbar_wait(bars + B_FULL * 8 + so, ph);
      const uint64_t da = da0 + (so << 8), db = db0 + (so << 8);
      wg_fence();
      wgmma_n128<TA>(d, da, db, !zero);
      wgmma_n128<TA>(d + 64, da + 512, db, !zero);
      wg_commit();
      wg_wait<1>();
      release(po);
#pragma unroll
      for (int k = 1; k < 4; k++) {
        if (QD == 2 || (QD == 4 && k == 2)) wg_fence();
        wgmma_n128<TA>(d, da + KS * k, db + 2 * k, 1);
        wgmma_n128<TA>(d + 64, da + 512 + KS * k, db + 2 * k, 1);
        if (QD == 2 || (QD == 4 && k == 1)) wg_commit();
        if ((QD == 2 && k < 3) || (QD == 4 && k == 1)) wg_wait<1>();
      }
      if (QD != 2) wg_commit();
      po = so;
      so += 8;
      if (so == 8 * STAGES) { so = 0; ph ^= 1; }
    };
    {
      so = wg ? 8 * (16 % STAGES) : 0; ph = wg ? (16 / STAGES) & 1 : 0; po = NOBAR;
      const uint64_t da0 = make_desc(sb + OFF_RING, 16, 1024, 1), db0 = make_desc(sb + OFF_RING + 16384, 16, 1024, 1);
      if (wg == 1) bar_sync(1, 256);
#pragma unroll 1
      for (int kb = 0; kb < 16; kb++) {
        block(std::integral_constant<int, 0>(), da0, db0, kb == 0, 16 * wg + kb);
      }
      asm volatile("bar.arrive %0, 256;" ::"r"(1 + wg) : "memory");
    }
    mbar_wait(bars + B_COEF * 8, 0);
    const uint32_t ca = sb + OFF_COEF + (64 * wg + 8 * w + g) * 16;
    const uint32_t tag = __shfl_sync(0xffffffffu, lds32(bars + B_EPOCH * 8) & 3, 0);
    constexpr int RE = SWAPB ? 2 : 0, IM = 2 - RE;
    const int ct = lane >> 3;
    const uint2* cp = g_carry + __shfl_sync(0xffffffffu, ((16 * wg + 2 * j) * 16 + tc - 1 - ct) * 32 + 8 * w + (lane & 7), lane);
    unsigned long long cv[4];
    auto load_carry = [&](int i) {
#pragma unroll
      for (int m = 0; m < 4; m++)
        asm volatile("{\n.reg .pred p;\nsetp.lt.s32 p, %2, %3;\n@p ld.relaxed.gpu.global.b64 %0, [%1];\n}\n" : "=l"(cv[m]) : "l"(cp + 512 * i - 128 * m), "r"(ct + 4 * m), "r"(tc) : "memory");
    };
    float lr[2], li[2], pr[2], pi[2], wr[2], wi[2], vr[2], vi[2], qr[2], qi[2], er[2], ei[2], gr[2], gi[2];
    auto powers = [&](int i) {
      const uint2 cf = lds64(ca + 512 * i);
      pr[i] = lr[i] = __uint_as_float(cf.x); pi[i] = li[i] = __uint_as_float(cf.y);
#pragma unroll
      for (int s = 0; s < 4; s++) csq(pr[i], pi[i]);
      gr[i] = pr[i]; gi[i] = pi[i];
      csq(pr[i], pi[i]);
      qr[i] = pr[i]; qi[i] = pi[i];
      csq(qr[i], qi[i]);
      er[i] = qr[i]; ei[i] = qi[i];
      wr[i] = (c & 1) ? pr[i] : 1.f; wi[i] = (c & 1) ? pi[i] : 0.f;
      if (c & 2) { float x, y; cmul(wr[i], wi[i], qr[i], qi[i], x, y); wr[i] = x; wi[i] = y; }
      vr[i] = wr[i]; vi[i] = wi[i];
      csq(vr[i], vi[i]); csq(vr[i], vi[i]);
      csq(qr[i], qi[i]); csq(qr[i], qi[i]); csq(qr[i], qi[i]);
      const int src = 4 * (lane & 7) + ct;
      vr[i] = __shfl_sync(0xffffffffu, vr[i], src); vi[i] = __shfl_sync(0xffffffffu, vi[i], src);
      qr[i] = __shfl_sync(0xffffffffu, qr[i], src); qi[i] = __shfl_sync(0xffffffffu, qi[i], src);
      asm volatile("" : "+f"(wr[i]), "+f"(wi[i]), "+f"(pr[i]), "+f"(pi[i]), "+f"(er[i]), "+f"(ei[i]));
    };
    powers(0);
    PMFENCE();
    wg_wait<0>();
    fence_regs<128>(d);
    release(po);
#pragma unroll
    for (int i = 0; i < 2; i++) {
      const float* e = d + 64 * i;
      auto chain = [&](int s0, int s1, float& sr, float& si) {
        sr = e[2 * s0 + RE]; si = e[2 * s0 + IM];
#pragma unroll
        for (int s = s0 + 1; s < s1; s++) {
          const int ia = 4 * (s >> 1) + (s & 1);
          const float nr = fmaf(-li[i], si, fmaf(lr[i], sr, e[ia + RE])), ni = fmaf(li[i], sr, fmaf(lr[i], si, e[ia + IM]));
          sr = nr; si = ni;
        }
      };
      float sr, si;
      if (i == 1) powers(1);
      if ((GREEDY >> i) & 1) {
        float ar, ai;
        chain(0, 16, ar, ai); chain(16, 32, sr, si);
        sr = fmaf(gr[i], ar, fmaf(-gi[i], ai, sr)); si = fmaf(gr[i], ai, fmaf(gi[i], ar, si));
      } else chain(0, 32, sr, si);
      if (i == 1) { asm volatile("pmevent 0;" : "+f"(sr), "+f"(si)::"memory"); load_carry(0); }
      float ur = __shfl_up_sync(0xffffffffu, sr, 1, 4), ui = __shfl_up_sync(0xffffffffu, si, 1, 4);
      if (c >= 1) { sr = fmaf(pr[i], ur, fmaf(-pi[i], ui, sr)); si = fmaf(pr[i], ui, fmaf(pi[i], ur, si)); }
      ur = __shfl_up_sync(0xffffffffu, sr, 2, 4); ui = __shfl_up_sync(0xffffffffu, si, 2, 4);
      if (c >= 2) { sr = fmaf(er[i], ur, fmaf(-ei[i], ui, sr)); si = fmaf(er[i], ui, fmaf(ei[i], ur, si)); }
      ur = __shfl_sync(0xffffffffu, sr, 4 * lane + 3); ui = __shfl_sync(0xffffffffu, si, 4 * lane + 3);
      asm volatile("{\n.reg .pred p;\n.reg .b64 v;\nsetp.lt.u32 p, %3, 8;\nmov.b64 v, {%1,%2};\n@p st.relaxed.gpu.global.b64 [%0], v;\n}\n"
                   ::"l"(cp + 512 * i + 32), "r"((__float_as_uint(ur) & ~3u) | tag), "r"(__float_as_uint(ui)), "r"(lane) : "memory");
      PMFENCE();
      er[i] = __shfl_up_sync(0xffffffffu, sr, 1, 4); ei[i] = __shfl_up_sync(0xffffffffu, si, 1, 4);
      if (c == 0) er[i] = ei[i] = 0.f;
    }
    uint4* hp = g_h + (32 * tc + 16 * wg + 2 * j) * 1024 + 64 * w + 4 * g + (c ^ (g >> 1));
#pragma unroll
    for (int i = 0; i < 2; i++) {
      float* e = d + 64 * i;
      const uint2 cf = lds64(ca + 512 * i + 8);
      const uint32_t gp = cf.x, gms = cf.y;
      PMFENCE();
      auto ready = [&]() {
        uint32_t bad = 0;
#pragma unroll
        for (int m = 0; m < 4; m++) if (ct + 4 * m < tc) bad |= (uint32_t)cv[m] ^ tag;
        return __all_sync(0xffffffffu, (bad & 3) == 0);
      };
      if (!ready()) {
        int n = 0;
#pragma unroll 1
        do load_carry(i); while (!ready() && ++n <= (SPIN_LIMIT << 4));
      }
      float hr = 0.f, hi = 0.f;
#pragma unroll
      for (int m = 3; m >= 0; m--) {
        const float x = __uint_as_float((uint32_t)cv[m]), y = __uint_as_float((uint32_t)(cv[m] >> 32));
        const float nr = m == 3 ? x : fmaf(qr[i], hr, fmaf(-qi[i], hi, x)), ni = m == 3 ? y : fmaf(qr[i], hi, fmaf(qi[i], hr, y));
        if (ct + 4 * m < tc) { hr = nr; hi = ni; }
      }
      { float x, y; cmul(hr, hi, vr[i], vi[i], x, y); hr = x; hi = y; }
      hr += __shfl_xor_sync(0xffffffffu, hr, 8); hi += __shfl_xor_sync(0xffffffffu, hi, 8);
      hr = __shfl_sync(0xffffffffu, hr, g) + __shfl_sync(0xffffffffu, hr, g + 16); hi = __shfl_sync(0xffffffffu, hi, g) + __shfl_sync(0xffffffffu, hi, g + 16);
      float sr = fmaf(wr[i], hr, fmaf(-wi[i], hi, er[i])), si = fmaf(wr[i], hi, fmaf(wi[i], hr, ei[i]));
#pragma unroll
      for (int i8 = 0; i8 < 4; i8++) {
        asm volatile("pmevent 0;" : "+f"(sr), "+f"(si)::"memory");
        if (i == 0 && i8 == 1) load_carry(1);
#pragma unroll
        for (int s = 8 * i8; s < 8 * i8 + 8; s++) {
          const int ia = 4 * (s >> 1) + (s & 1);
          const float nr = fmaf(-li[i], si, fmaf(lr[i], sr, e[ia + RE])), ni = fmaf(li[i], sr, fmaf(lr[i], si, e[ia + IM]));
          sr = nr; si = ni;
          e[ia + RE] = nr; e[ia + IM] = ni;
        }
        uint32_t hp0[4], hp1[4];
#pragma unroll
        for (int m = 0; m < 4; m++) {
          const float* f = e + 16 * i8 + 4 * m;
          const uint32_t x = pack_bf16(f[RE], f[RE + 1]), y = pack_bf16(f[IM], f[IM + 1]);
          hp0[m] = bfma2(gp, x, bmul2(gms, y)); hp1[m] = bfnma2(gp, y, bmul2(gms, x));
        }
        uint4* o = hp + 512 * (i8 >> 1) + 256 * i + 32 * (i8 & 1);
        stg128(o, make_uint4(hp0[0], hp0[1], hp0[2], hp0[3]));
        stg128(o + 1024, make_uint4(hp1[0], hp1[1], hp1[2], hp1[3]));
      }
    }
    const int trow = 128 * tc + 64 * (w & 1) + 8 * (w >> 1) + g;
    const int dcol = 128 * j + 4 * c;
    asm volatile("bar.arrive %0, 160;" ::"r"(4 + wg) : "memory");
    if (wg == 0) {
      set_ra();
      {
        const uint32_t dt = sb + OFF_Q + 4096;
        mbar_wait(bars + (B_UF + 3) * 8, 0);
        const int n = t & 15, k = 2 * (n & 6) + 2 * (n >> 3) + (n & 1);
        const uint32_t dv = lds32(sb + OFF_DS + (t & ~15) * 4 + 4 * k) >> (16 - 16 * (k & 1));
#pragma unroll
        for (int u = 0; u < 2; u++) {
          const int m = (k >> 1) - 4 * u;
          sts128(dt + (t >> 4) * 512 + u * 256 + n * 16, make_uint4(m == 0 ? dv : 0, m == 1 ? dv : 0, m == 2 ? dv : 0, m == 3 ? dv : 0));
        }
        fence_proxy_async_smem();
        bar_sync(2, 256);
        mbar_wait(bars + (B_FULL + XPOS % STAGES) * 8, (XPOS / STAGES) & 1);
        const uint64_t dx = make_desc(sb + OFF_RING + (XPOS % STAGES) * STAGE_BYTES, 16, 1024, 1), dd = make_desc(dt, 256, 128, 0);
        wg_fence();
#pragma unroll
        for (int u = 0; u < 16; u++) ss_n16(d + 8 * u, dx + ((u >> 2) & 1) * 1024 + (u >> 3) * 512 + (u & 3) * 2, dd + (u & 7) * 32);
        wg_commit();
        wg_wait<0>();
        rename_regs<128>(d);
        release(8 * (XPOS % STAGES));
        if (t == 0) mbar_arrive(bars + B_XI * 8);
      }
      so = 8 * (33 % STAGES); ph = (33 / STAGES) & 1; po = NOBAR;
      const uint64_t da0 = make_desc(sb + OFF_RING + 16384, 512, 1024, 2), db0 = make_desc(sb + OFF_RING, 16, 1024, 1);
#pragma unroll 1
      for (int kb = 0; kb < QSW; kb++) block(std::integral_constant<int, 1>(), da0, db0, false, 32 + kb);
#pragma unroll 1
      for (int kb = QSW; kb < 32 - TAILB; kb++) block(std::integral_constant<int, 2>(), da0, db0, false, 32 + kb);
      float* op = P.out + (size_t)trow * 2048 + 1024 + dcol;
      auto mma = [&](int i, int kb, int k0, int k1) {
        const int s = (33 + kb) % STAGES;
        wg_fence();
#pragma unroll
        for (int k = k0; k < k1; k++) wgmma_n128<1>(d + 64 * i, da0 + s * 2048 + 512 * i + 128 * k, db0 + (i ? 0 : P.zero) + s * 2048 + 2 * k, 1);
        wg_commit();
      };
      auto store = [&](int i, int J0, int J1) {
#pragma unroll
        for (int J = J0; J < J1; J++) {
#pragma unroll
          for (int h = 0; h < 2; h++) {
            const float* e = d + 64 * i + 8 * J + 2 * h;
            stg128(op + (size_t)(16 * i + 32 * h) * 2048 + 16 * J, make_uint4(__float_as_uint(e[0]), __float_as_uint(e[1]), __float_as_uint(e[4]), __float_as_uint(e[5])));
          }
        }
        PMFENCE();
      };
      constexpr int K0 = 32 - TAILB;
#pragma unroll
      for (int kb = K0; kb < 32; kb++) {
        mbar_wait(bars + (B_FULL + (33 + kb) % STAGES) * 8, ((33 + kb) / STAGES) & 1);
        if (TAILB == 5 && kb == K0) { mma(0, kb, 0, 2); wg_wait<1>(); release(po); mma(0, kb, 2, 4); }
        else mma(0, kb, 0, 4);
      }
      mma(1, K0, 0, 4);
      wg_wait<1>();
      fence_regs<64>(d);
#pragma unroll
      for (int kb = K0 + 1; kb < 32; kb++) {
        mma(1, kb, 0, 4);
        store(0, T_ST * (kb - K0 - 1), kb == 31 ? 8 : T_ST * (kb - K0));
      }
      wg_wait<0>();
      fence_regs<64>(d + 64);
      store(1, 0, 8);
      if (t == 0) g_epoch[b * 32] = lds32(bars + B_EPOCH * 8);
      return;
    }
    asm volatile("setmaxnreg.dec.sync.aligned.u32 %0;" ::"n"(488 - 2 * GREG));
  }
  {
    int lane;
    asm volatile("mov.u32 %0, %%laneid;" : "=r"(lane));
    const int w = warp & 3, h = wg & 1;
    const int lc = 2 * (lane & 2) + (lane & 1) + ((lane >> 2) & 2);
    const bool own = ((lane >> 2) & 1) == rank, spare = !own && lc < 2;
    const uint32_t ya = (spare ? sb + OFF_IN + 96 + lc * 2064 : sb + OFF_U + (own ? 4 * rank * U_N8 : 4 * (rank ^ 1) * U_N8 - 2 * U_CH) + lc * U_CH) + w * 128 + (lane >> 4) * 16 + h * 64;
    const uint32_t ys = spare ? 512 : U_N8;
    const uint32_t ob0 = sb + (h ? OFF_F1 : OFF_K) + 1024 * w, ob1 = sb + (h ? OFF_VP : OFF_K + 4096) + 1024 * w;
    uint32_t y[2][8];
    uint2 q[4][4];
    auto get_q = [&](int n, int off, int bar, int ph) {
#pragma unroll
      for (int u = 0; u < 2; u++) {
        mbar_wait(bars + (bar + u) * 8, ph);
#pragma unroll
        for (int r = 0; r < 4; r++) q[n + u][r] = lds64(sb + off + 4096 * u + 1024 * w + 256 * r + 8 * lane);
      }
    };
    auto get_y = [&](int n) { ldsm4t(y[n & 1], ya + n * ys); ldsm4t(y[n & 1] + 4, ya + n * ys + 32); };
    if (h) {
#pragma unroll
      for (int n = 0; n < 4; n += 2) {
        get_q(n, OFF_Q, B_QF, n >> 1);
        uint32_t dep = P.zero;
#pragma unroll
        for (int r = 0; r < 8; r++) dep &= q[n + (r >> 2)][r & 3].x;
        bar_sync(6 + dep, 128);
        if (w < 2 && elect_one()) load_q(5 + 2 * w - (n >> 1), OFF_Q, B_QF + n);
        __syncwarp();
      }
#pragma unroll 1
      for (int r = 0; r < 6; r++) mbar_wait(bars + (B_IN + r) * 8, 0);
      bar_sync(9, 256);
    } else get_q(0, OFF_K, B_KF, 0);
    mbar_wait(bars + B_HR * 8, 1);
    mbar_wait(bars + (B_IN + 6) * 8, 0);
    get_y(0);
#pragma unroll
    for (int n = 0; n < 4; n++) {
      uint32_t* o = y[n & 1];
#pragma unroll
      for (int r = 0; r < 4; r++) { o[2 * r] = bmul2(o[2 * r], q[n][r].x); o[2 * r + 1] = bmul2(o[2 * r + 1], q[n][r].y); }
      if (n > 0 && lane == 0) asm volatile("cp.async.bulk.wait_group.read 0;" ::: "memory");
      __syncwarp();
#pragma unroll
      for (int r = 0; r < 4; r++)
        sts128((r & 2 ? ob1 : ob0) + (r & 1) * 512 + lane * 16, make_uint4(o[2 * r] << 16, o[2 * r] & 0xffff0000u, o[2 * r + 1] << 16, o[2 * r + 1] & 0xffff0000u));
      fence_proxy_async_smem();
      __syncwarp();
      if (lane == 0) {
#pragma unroll
        for (int u = 0; u < 2; u++)
          asm volatile("cp.async.bulk.tensor.3d.global.shared::cta.bulk_group [%0, {%2, %3, %4}], [%1];"
                       ::"l"(&mO), "r"(u ? ob1 : ob0), "r"(32 * slot), "r"(32 * rank + 8 * w), "r"(8 * n + 4 * h + 2 * u) : "memory");
        asm volatile("cp.async.bulk.commit_group;" ::: "memory");
      }
      __syncwarp();
      if (n < 3) get_y(n + 1);
      if (n == 1 && !h) get_q(2, OFF_Q, B_QF + 2, 0);
    }
    if (warp == 8 && lane == 0) mbar_arrive_cta(bars + B_ACK * 8, rank ^ 1);
    if (lane == 0) asm volatile("cp.async.bulk.wait_group 0;" ::: "memory");
    mbar_wait(bars + B_ACK * 8, 0);
  }
}

typedef CUresult (*EncodeFn)(CUtensorMap*, CUtensorMapDataType, cuuint32_t, void*, const cuuint64_t*, const cuuint64_t*, const cuuint32_t*,
                             const cuuint32_t*, CUtensorMapInterleave, CUtensorMapSwizzle, CUtensorMapL2promotion, CUtensorMapFloatOOBfill);

bool encode(EncodeFn fn, CUtensorMap* m, int rank, const void* base, const cuuint64_t* dims, const cuuint64_t* strides, const cuuint32_t* box, CUtensorMapSwizzle swz,
            CUtensorMapL2promotion promo = CU_TENSOR_MAP_L2_PROMOTION_L2_128B) {
  const cuuint32_t es[5] = {1, 1, 1, 1, 1};
  return fn(m, CU_TENSOR_MAP_DATA_TYPE_BFLOAT16, rank, const_cast<void*>(base), dims, strides, box, es, CU_TENSOR_MAP_INTERLEAVE_NONE, swz,
            promo, CU_TENSOR_MAP_FLOAT_OOB_FILL_NONE) == CUDA_SUCCESS;
}

}

extern "C" void kernel_launch(void* const* d_in, const int* in_sizes, int n_in, void* d_out, int out_size) {
  (void)in_sizes; (void)n_in; (void)out_size;
  typedef const __nv_bfloat16* In;
  const In q = (In)d_in[0], k = (In)d_in[1], v = (In)d_in[2], ssm_k = (In)d_in[4], x = (In)d_in[6], B_re = (In)d_in[9], B_im = (In)d_in[10], C_re = (In)d_in[11], C_im = (In)d_in[12];
  Params P = {};
  P.shift_k = (In)d_in[3]; P.ssm_D = (In)d_in[5]; P.lam_re = (In)d_in[7]; P.lam_im = (In)d_in[8]; P.log_dt = (In)d_in[13]; P.Dskip = (In)d_in[14];
  P.out = (float*)d_out;
  for (int cl = 0; cl < 64; cl++) P.slot[cl >> 2] |= (cl < 4 ? 4 + cl : cl < 36 ? 8 * ((cl - 4) & 7) + ((cl - 4) >> 3) : 8 * (1 + (cl - 36) % 7) + 4 + (cl - 36) / 7) << (8 * (cl & 3));
  const bool swapB = (uintptr_t)B_im < (uintptr_t)B_re;

  EncodeFn fn = nullptr;
  cudaDriverEntryPointQueryResult qr;
  cudaGetDriverEntryPoint("cuTensorMapEncodeTiled", (void**)&fn, cudaEnableDefault, &qr);
  if (!fn) return;

  CUtensorMap mX, mB, mCre, mCim, mXs, mK, mV, mQ, mS, mO;
  bool ok = true;
  {
    const cuuint64_t dims[4] = {1024, 2, 64, 16}, str[3] = {2048, 32 * 2048, 2 * 2048};
    const cuuint32_t box[4] = {64, 2, 4, 16};
    ok &= encode(fn, &mX, 4, x, dims, str, box, CU_TENSOR_MAP_SWIZZLE_128B);
  }
  {
    const uintptr_t lo = swapB ? (uintptr_t)B_im : (uintptr_t)B_re, hi = swapB ? (uintptr_t)B_re : (uintptr_t)B_im;
    const cuuint64_t dims[4] = {1024, 8, 2, 128}, str[3] = {2048, (cuuint64_t)(hi - lo), 8 * 2048};
    const cuuint32_t box[4] = {64, 8, 2, 4};
    ok &= encode(fn, &mB, 4, (const void*)lo, dims, str, box, CU_TENSOR_MAP_SWIZZLE_128B);
  }
  {
    const cuuint64_t dims[5] = {1024, 2, 4, 2, 64}, str[4] = {2048, 4 * 2048, 2 * 2048, 16 * 2048};
    const cuuint32_t box[5] = {64, 2, 4, 2, 4};
    ok &= encode(fn, &mCre, 5, C_re, dims, str, box, CU_TENSOR_MAP_SWIZZLE_128B);
    ok &= encode(fn, &mCim, 5, C_im, dims, str, box, CU_TENSOR_MAP_SWIZZLE_128B);
  }
  {
    const cuuint64_t dims[4] = {1024, 8, 64, 4}, str[3] = {2048, 32 * 2048, 8 * 2048};
    const cuuint32_t box[4] = {64, 8, 4, 4};
    ok &= encode(fn, &mXs, 4, x, dims, str, box, CU_TENSOR_MAP_SWIZZLE_128B);
  }
  {
    const cuuint64_t dims[3] = {1024, 64, 32}, str[2] = {32 * 2048, 2048};
    const cuuint32_t box[3] = {16, 32, 4};
    const cuuint64_t dimq[4] = {1024, 8, 32, 8}, strq[3] = {32 * 2048, 2048, 256 * 2048};
    const cuuint32_t boxq[4] = {16, 8, 4, 4};
    ok &= encode(fn, &mQ, 4, q, dimq, strq, boxq, CU_TENSOR_MAP_SWIZZLE_NONE);
    ok &= encode(fn, &mK, 3, k, dims, str, box, CU_TENSOR_MAP_SWIZZLE_32B);
    ok &= encode(fn, &mV, 3, v, dims, str, box, CU_TENSOR_MAP_SWIZZLE_32B);
  }
  {
    const cuuint64_t dims[2] = {32, 65536}, str[1] = {64};
    const cuuint32_t box[2] = {32, 64};
    ok &= encode(fn, &mS, 2, ssm_k, dims, str, box, CU_TENSOR_MAP_SWIZZLE_64B);
  }
  {
    const cuuint64_t dims[3] = {2048, 64, 32}, str[2] = {32 * 8192, 8192};
    const cuuint32_t box[3] = {32, 8, 2};
    ok &= encode(fn, &mO, 3, d_out, dims, str, box, CU_TENSOR_MAP_SWIZZLE_NONE);
  }
  if (!ok) return;
  auto kern = swapB ? fused_kernel<1> : fused_kernel<0>;
  cudaFuncSetAttribute(kern, cudaFuncAttributeMaxDynamicSharedMemorySize, SMEM_BYTES);
  kern<<<NCTA, 512, SMEM_BYTES, cudaStreamPerThread>>>(P, mX, mB, mCre, mCim, mXs, mK, mV, mQ, mS, mO);
}
```

```cpp
#include <cuda_runtime.h>
#include <cuda_bf16.h>
#include <cuda.h>
#include <stdint.h>
#include <type_traits>

namespace {

constexpr int D_DIM = 1024;
constexpr int NCTA = 128;

constexpr int STAGES = 5, STAGE_BYTES = 32768;
constexpr int OFF_RING = 0;
constexpr int OFF_F1 = STAGES * STAGE_BYTES, OFF_F2 = OFF_F1 + 4096, OFF_K = OFF_F2 + 2048, OFF_VP = OFF_K + 8192, OFF_Q = OFF_VP + 4096, OFF_IN = OFF_Q + 8192;
constexpr int OFF_KV = OFF_K;
constexpr int U_CH = 528, U_N8 = 8 * U_CH, OFF_U = OFF_IN + U_N8;
constexpr int OFF_COEF = OFF_U + 8 * U_N8;
constexpr int OFF_DS = OFF_COEF + 2048, OFF_D = OFF_DS + 512;
constexpr int OFF_BAR = OFF_D + 64;
constexpr int SMEM_BYTES = OFF_BAR + 512;
static_assert(SMEM_BYTES <= 232448 && OFF_K % 1024 == 0 && (OFF_U + 3 * U_N8) % 512 == 0 && (4 * U_N8) % 512 == 0, "smem map");
constexpr int B_FULL = 0, B_XI = 5, B_HR = 6, B_HP = 7, B_KVF = 8, B_KF = 11, B_KE = 13, B_QF = 15, B_IN = 19, B_UF = 27, B_Y = 31, B_ACK = 36,
              B_EMPTY = 38, B_COEF = 43, B_KVE = 44, B_NONE = 47, B_EPOCH = 48;
constexpr int QD1 = 8;
constexpr int QD2 = 2;
constexpr int QD3 = 8;
constexpr int QSW = 16;
constexpr int HEAD = 3;
constexpr int ST_T0 = 200;
constexpr int ST_DELAY = 300;
constexpr int XPOS = 32;
constexpr int K_T0 = 800;
constexpr int KV_T0 = 1500;
constexpr int KV_DT = 560;
constexpr int KV_DV = 100;
constexpr int POLL_NS = 30;
constexpr int GREEDY = 1;
constexpr int TAILB = 5;
constexpr int GREG = 176;
constexpr int COEF_T0 = 2500;
constexpr int T_ST = 2;
constexpr int PFC_T0 = 13500;
constexpr int PFC_T1 = 1500;
constexpr int PFC_DT = 400;
constexpr int CFM = 0x40f1;
constexpr int SPIN_LIMIT = 1 << 14;

struct Params {
  unsigned slot[16];
  unsigned zero;
  const __nv_bfloat16 *shift_k, *ssm_D, *lam_re, *lam_im, *log_dt, *Dskip;
  float* out;
};

__device__ __align__(1024) uint4 g_h[16 * 32 * 1024];
__device__ __align__(128) uint2 g_carry[32 * 16 * 32];
__device__ unsigned g_flagH[2 * 16 * 32];
__device__ unsigned g_epoch[NCTA * 32];

__device__ __forceinline__ uint64_t make_desc(uint32_t addr, uint32_t lbo, uint32_t sbo, uint32_t swz) {
  return (uint64_t)((addr & 0x3FFFF) >> 4) | ((uint64_t)(lbo >> 4) << 16) | ((uint64_t)(sbo >> 4) << 32) | ((uint64_t)swz << 62);
}
__device__ __forceinline__ void wg_fence() { asm volatile("wgmma.fence.sync.aligned;" ::: "memory"); }
__device__ __forceinline__ void wg_commit() { asm volatile("wgmma.commit_group.sync.aligned;" ::: "memory"); }
template <int N> __device__ __forceinline__ void wg_wait() { asm volatile("wgmma.wait_group.sync.aligned %0;" ::"n"(N) : "memory"); }
__device__ __forceinline__ void mbar_init(uint32_t bar, int cnt) { asm volatile("mbarrier.init.shared::cta.b64 [%0], %1;" ::"r"(bar), "r"(cnt) : "memory"); }
__device__ __forceinline__ void mbar_expect(uint32_t bar, uint32_t bytes) { asm volatile("mbarrier.arrive.expect_tx.shared::cta.b64 _, [%0], %1;" ::"r"(bar), "r"(bytes) : "memory"); }
__device__ __forceinline__ bool mbar_try(uint32_t bar, uint32_t parity) {
  uint32_t ok;
  asm volatile("{\n.reg .pred p;\nmbarrier.try_wait.parity.shared::cta.b64 p, [%1], %2;\nselp.u32 %0, 1, 0, p;\n}\n" : "=r"(ok) : "r"(bar), "r"(parity) : "memory");
  return ok;
}
__device__ __forceinline__ void mbar_wait(uint32_t bar, uint32_t parity) {
  if (__builtin_expect(!mbar_try(bar, parity), 0)) {
#pragma unroll 1
    for (int n = 0; n < SPIN_LIMIT && !mbar_try(bar, parity); n++) {}
  }
}
__device__ __forceinline__ void mbar_arrive(uint32_t bar) { asm volatile("mbarrier.arrive.shared::cta.b64 _, [%0];" ::"r"(bar) : "memory"); }
__device__ __forceinline__ void mbar_arrive_cta(uint32_t bar, uint32_t cta) {
  asm volatile("{\n.reg .b32 ra;\nmapa.shared::cluster.u32 ra, %0, %1;\nmbarrier.arrive.shared::cluster.b64 _, [ra];\n}\n" ::"r"(bar), "r"(cta) : "memory");
}
__device__ __forceinline__ bool elect_one() {
  uint32_t p;
  asm volatile("{\n.reg .pred P;\nelect.sync _|P, 0xffffffff;\nselp.u32 %0, 1, 0, P;\n}\n" : "=r"(p));
  return p != 0;
}
__device__ __forceinline__ void bar_sync(int id, int n) { asm volatile("bar.sync %0, %1;" ::"r"(id), "r"(n) : "memory"); }
#define TMA_LD(dim) "cp.async.bulk.tensor." dim ".shared::cluster.global.mbarrier::complete_tx::bytes"
__device__ __forceinline__ void tma2d(uint32_t dst, const CUtensorMap* m, int c0, int c1, uint32_t bar) {
  asm volatile(TMA_LD("2d") " [%0], [%1, {%3, %4}], [%2];" ::"r"(dst), "l"(m), "r"(bar), "r"(c0), "r"(c1) : "memory");
}
__device__ __forceinline__ void tma3d(uint32_t dst, const CUtensorMap* m, int c0, int c1, int c2, uint32_t bar) {
  asm volatile(TMA_LD("3d") " [%0], [%1, {%3, %4, %5}], [%2];" ::"r"(dst), "l"(m), "r"(bar), "r"(c0), "r"(c1), "r"(c2) : "memory");
}
__device__ __forceinline__ void tma4d(uint32_t dst, const CUtensorMap* m, int c0, int c1, int c2, int c3, uint32_t bar) {
  asm volatile(TMA_LD("4d") " [%0], [%1, {%3, %4, %5, %6}], [%2];" ::"r"(dst), "l"(m), "r"(bar), "r"(c0), "r"(c1), "r"(c2), "r"(c3) : "memory");
}
__device__ __forceinline__ void tma4d_mc(uint32_t dst, const CUtensorMap* m, int c0, int c1, int c2, int c3, uint32_t bar) {
  asm volatile(TMA_LD("4d") ".multicast::cluster [%0], [%1, {%3, %4, %5, %6}], [%2], %7;" ::"r"(dst), "l"(m), "r"(bar), "r"(c0), "r"(c1), "r"(c2), "r"(c3), "h"((uint16_t)3) : "memory");
}
__device__ __forceinline__ void tma5d_mc(uint32_t dst, const CUtensorMap* m, int c0, int c1, int c2, int c3, int c4, uint32_t bar) {
  asm volatile(TMA_LD("5d") ".multicast::cluster [%0], [%1, {%3, %4, %5, %6, %7}], [%2], %8;" ::"r"(dst), "l"(m), "r"(bar), "r"(c0), "r"(c1), "r"(c2), "r"(c3), "r"(c4), "h"((uint16_t)3) : "memory");
}
__device__ __forceinline__ void bulk_load(uint32_t dst, const void* src, uint32_t bytes, uint32_t bar) {
  asm volatile("cp.async.bulk.shared::cluster.global.mbarrier::complete_tx::bytes [%0], [%1], %2, [%3];" ::"r"(dst), "l"(src), "r"(bytes), "r"(bar) : "memory");
}
__device__ __forceinline__ void bulk_send(uint32_t dst, uint32_t src, uint32_t bytes, uint32_t bar, uint32_t cta) {
  asm volatile("{\n.reg .b32 rd, rb;\nmapa.shared::cluster.u32 rd, %0, %3;\nmapa.shared::cluster.u32 rb, %2, %3;\n"
               "cp.async.bulk.shared::cluster.shared::cta.mbarrier::complete_tx::bytes [rd], [%1], %4, [rb];\n}\n"
               ::"r"(dst), "r"(src), "r"(bar), "r"(cta), "r"(bytes) : "memory");
}
__device__ __forceinline__ void fence_proxy_async_smem() { asm volatile("fence.proxy.async.shared::cta;" ::: "memory"); }
__device__ __forceinline__ void fence_proxy_async_global() { asm volatile("fence.proxy.async.global;" ::: "memory"); }
__device__ __forceinline__ uint32_t clk32() { uint32_t c; asm volatile("mov.u32 %0, %%clock;" : "=r"(c)::"memory"); return c; }
__device__ __forceinline__ void wait_until(uint32_t t0, uint32_t dt) { while (clk32() - t0 < dt) __nanosleep(32); }
__device__ __forceinline__ void spin_until(uint32_t t0, uint32_t dt) { while (clk32() - t0 < dt) {} }
__device__ __forceinline__ void prefetch_map(const CUtensorMap* m) { asm volatile("prefetch.tensormap [%0];" ::"l"(m) : "memory"); }
__device__ __forceinline__ void prefetch_line(const void* p) { asm volatile("prefetch.global.L2 [%0];" ::"l"(p) : "memory"); }
__device__ __forceinline__ unsigned ld_acquire(const unsigned* p) { unsigned v; asm volatile("ld.acquire.gpu.global.u32 %0, [%1];" : "=r"(v) : "l"(p) : "memory"); return v; }
__device__ __forceinline__ unsigned ld_relaxed(const unsigned* p) { unsigned v; asm volatile("ld.relaxed.gpu.global.u32 %0, [%1];" : "=r"(v) : "l"(p) : "memory"); return v; }
__device__ __forceinline__ uint32_t lds32(uint32_t a) { uint32_t v; asm volatile("ld.shared.u32 %0, [%1];" : "=r"(v) : "r"(a)); return v; }
__device__ __forceinline__ uint2 lds64(uint32_t a) { uint2 v; asm volatile("ld.shared.v2.u32 {%0,%1}, [%2];" : "=r"(v.x), "=r"(v.y) : "r"(a) : "memory"); return v; }
__device__ __forceinline__ uint4 lds128(uint32_t a) { uint4 v; asm volatile("ld.shared.v4.u32 {%0,%1,%2,%3}, [%4];" : "=r"(v.x), "=r"(v.y), "=r"(v.z), "=r"(v.w) : "r"(a) : "memory"); return v; }
__device__ __forceinline__ void sts32(uint32_t a, uint32_t v) { asm volatile("st.shared.u32 [%0], %1;" ::"r"(a), "r"(v) : "memory"); }
__device__ __forceinline__ void sts128(uint32_t a, uint4 v) { asm volatile("st.shared.v4.u32 [%0], {%1,%2,%3,%4};" ::"r"(a), "r"(v.x), "r"(v.y), "r"(v.z), "r"(v.w) : "memory"); }
__device__ __forceinline__ void ldsm4(uint32_t* r, uint32_t a) { asm volatile("ldmatrix.sync.aligned.m8n8.x4.shared.b16 {%0,%1,%2,%3}, [%4];" : "=r"(r[0]), "=r"(r[1]), "=r"(r[2]), "=r"(r[3]) : "r"(a) : "memory"); }
__device__ __forceinline__ void ldsm4t(uint32_t* r, uint32_t a) { asm volatile("ldmatrix.sync.aligned.m8n8.x4.trans.shared.b16 {%0,%1,%2,%3}, [%4];" : "=r"(r[0]), "=r"(r[1]), "=r"(r[2]), "=r"(r[3]) : "r"(a) : "memory"); }
__device__ __forceinline__ void stsm4t(uint32_t a, uint32_t r0, uint32_t r1, uint32_t r2, uint32_t r3) {
  asm volatile("stmatrix.sync.aligned.m8n8.x4.trans.shared.b16 [%0], {%1,%2,%3,%4};" ::"r"(a), "r"(r0), "r"(r1), "r"(r2), "r"(r3) : "memory");
}
__device__ __forceinline__ uint4 ldg128_nc(const void* p) { uint4 v; asm volatile("ld.global.nc.L1::no_allocate.v4.u32 {%0,%1,%2,%3}, [%4];" : "=r"(v.x), "=r"(v.y), "=r"(v.z), "=r"(v.w) : "l"(p)); return v; }
__device__ __forceinline__ void stg128(void* p, uint4 v) { asm volatile("st.global.L1::no_allocate.v4.u32 [%0], {%1,%2,%3,%4};" ::"l"(p), "r"(v.x), "r"(v.y), "r"(v.z), "r"(v.w) : "memory"); }
__device__ __forceinline__ uint32_t pack_bf16(float lo, float hi) { uint32_t r; asm("cvt.rn.bf16x2.f32 %0, %1, %2;" : "=r"(r) : "f"(hi), "f"(lo)); return r; }
__device__ __forceinline__ uint32_t bmul2(uint32_t a, uint32_t b) { uint32_t r; asm("mul.rn.bf16x2 %0, %1, %2;" : "=r"(r) : "r"(a), "r"(b)); return r; }
__device__ __forceinline__ uint32_t bfma2(uint32_t a, uint32_t b, uint32_t c) { uint32_t r; asm("fma.rn.bf16x2 %0, %1, %2, %3;" : "=r"(r) : "r"(a), "r"(b), "r"(c)); return r; }
__device__ __forceinline__ uint32_t blo2(uint32_t a) { uint32_t r; asm("{\n.reg .b16 l, h;\nmov.b32 {l, h}, %1;\nmov.b32 %0, {l, l};\n}" : "=r"(r) : "r"(a)); return r; }
__device__ __forceinline__ float bf2f(__nv_bfloat16 v) { return __bfloat162float(v); }

#define R8(d, o) "+f"(d[o]), "+f"(d[o + 1]), "+f"(d[o + 2]), "+f"(d[o + 3]), "+f"(d[o + 4]), "+f"(d[o + 5]), "+f"(d[o + 6]), "+f"(d[o + 7])
#define R16(d, o) R8(d, o), R8(d, o + 8)
#define R64(d, o) R16(d, o), R16(d, o + 16), R16(d, o + 32), R16(d, o + 48)
template <int TA> __device__ __forceinline__ void wgmma_n128(float* d, uint64_t da, uint64_t db, int scale_d) {
  asm volatile("{\n.reg .pred p;\nsetp.ne.b32 p, %66, 0;\n"
    "wgmma.mma_async.sync.aligned.m64n128k16.f32.bf16.bf16 {"
    "%0,%1,%2,%3,%4,%5,%6,%7,%8,%9,%10,%11,%12,%13,%14,%15,%16,%17,%18,%19,%20,%21,%22,%23,%24,%25,%26,%27,%28,%29,%30,%31,"
    "%32,%33,%34,%35,%36,%37,%38,%39,%40,%41,%42,%43,%44,%45,%46,%47,%48,%49,%50,%51,%52,%53,%54,%55,%56,%57,%58,%59,%60,%61,%62,%63"
    "}, %64, %65, p, 1, 1, %67, 0;\n}\n"
    : R64(d, 0)
    : "l"(da), "l"(db), "r"(scale_d), "n"(TA));
}
template <int N> __device__ __forceinline__ void fence_regs(float* d) {
#pragma unroll
  for (int i = 0; i < N; i++) asm volatile("" : "+f"(d[i])::"memory");
}
#define PMFENCE() asm volatile("pmevent 0;" ::: "memory")
__device__ __forceinline__ void cmul(float ar, float ai, float br, float bi, float& cr, float& ci) {
  cr = ar * br - ai * bi; ci = ar * bi + ai * br;
}
__device__ __forceinline__ void csq(float& r, float& i) { const float x = fmaf(r, r, -i * i), y = r * i; r = x; i = y + y; }

#define W8(d, o) "=f"(d[o]), "=f"(d[o + 1]), "=f"(d[o + 2]), "=f"(d[o + 3]), "=f"(d[o + 4]), "=f"(d[o + 5]), "=f"(d[o + 6]), "=f"(d[o + 7])
#define L16 "{%0,%1,%2,%3,%4,%5,%6,%7,%8,%9,%10,%11,%12,%13,%14,%15}"
#define L32 "{%0,%1,%2,%3,%4,%5,%6,%7,%8,%9,%10,%11,%12,%13,%14,%15,%16,%17,%18,%19,%20,%21,%22,%23,%24,%25,%26,%27,%28,%29,%30,%31}"
template <int ACC, int TB> __device__ __forceinline__ void rs_n32(float* d, const uint32_t* a, uint64_t db) {
  if constexpr (ACC) asm volatile("wgmma.mma_async.sync.aligned.m64n32k16.f32.bf16.bf16 " L16 ", {%16,%17,%18,%19}, %20, 1, 1, 1, %21;" : R16(d, 0) : "r"(a[0]), "r"(a[1]), "r"(a[2]), "r"(a[3]), "l"(db), "n"(TB));
  else asm volatile("wgmma.mma_async.sync.aligned.m64n32k16.f32.bf16.bf16 " L16 ", {%16,%17,%18,%19}, %20, 0, 1, 1, %21;" : W8(d, 0), W8(d, 8) : "r"(a[0]), "r"(a[1]), "r"(a[2]), "r"(a[3]), "l"(db), "n"(TB));
}
template <int ACC, int TB> __device__ __forceinline__ void ss_n64(float* d, uint64_t da, uint64_t db) {
  if constexpr (ACC) asm volatile("wgmma.mma_async.sync.aligned.m64n64k16.f32.bf16.bf16 " L32 ", %32, %33, 1, 1, 1, 0, %34;" : R16(d, 0), R16(d, 16) : "l"(da), "l"(db), "n"(TB));
  else asm volatile("wgmma.mma_async.sync.aligned.m64n64k16.f32.bf16.bf16 " L32 ", %32, %33, 0, 1, 1, 0, %34;" : W8(d, 0), W8(d, 8), W8(d, 16), W8(d, 24) : "l"(da), "l"(db), "n"(TB));
}
template <int ACC> __device__ __forceinline__ void ss_n32_tt(float* d, uint64_t da, uint64_t db) {
  if constexpr (ACC) asm volatile("wgmma.mma_async.sync.aligned.m64n32k16.f32.bf16.bf16 " L16 ", %16, %17, 1, 1, 1, 1, 1;" : R16(d, 0) : "l"(da), "l"(db));
  else asm volatile("wgmma.mma_async.sync.aligned.m64n32k16.f32.bf16.bf16 " L16 ", %16, %17, 0, 1, 1, 1, 1;" : W8(d, 0), W8(d, 8) : "l"(da), "l"(db));
}
__device__ __forceinline__ void stsm4(uint32_t a, uint32_t r0, uint32_t r1, uint32_t r2, uint32_t r3) {
  asm volatile("stmatrix.sync.aligned.m8n8.x4.shared.b16 [%0], {%1,%2,%3,%4};" ::"r"(a), "r"(r0), "r"(r1), "r"(r2), "r"(r3) : "memory");
}
template <int N> __device__ __forceinline__ void fence_u32(uint32_t* d) {
#pragma unroll
  for (int i = 0; i < N; i++) asm volatile("" : "+r"(d[i])::"memory");
}
__device__ __forceinline__ void pack32(uint32_t* f, const float* z) {
#pragma unroll
  for (int i = 0; i < 16; i++) f[i] = pack_bf16(z[2 * i], z[2 * i + 1]);
}
template <int INV> __device__ __forceinline__ void twiddle(uint32_t* f, const uint32_t* tp, const uint32_t* ts) {
#pragma unroll
  for (int i = 0; i < 8; i++) {
    uint32_t x = f[2 * i + INV], y = f[2 * i + 1 - INV];
    x = bfma2(tp[i & 3], y, x); y = bfma2(ts[i & 3], x, y); x = bfma2(tp[i & 3], y, x);
    f[2 * i + INV] = x; f[2 * i + 1 - INV] = y;
  }
}
__device__ __forceinline__ uint32_t bfnma2(uint32_t a, uint32_t b, uint32_t c) { uint32_t r; asm("{\n.reg .b32 t;\nmul.bf16x2 t, %1, %2;\nsub.bf16x2 %0, %3, t;\n}" : "=r"(r) : "r"(a), "r"(b), "r"(c)); return r; }
__device__ __forceinline__ uint32_t bfms2(uint32_t a, uint32_t b, uint32_t c) { uint32_t r; asm("{\n.reg .b32 t;\nmul.bf16x2 t, %1, %2;\nsub.bf16x2 %0, t, %3;\n}" : "=r"(r) : "r"(a), "r"(b), "r"(c)); return r; }
template <int ADD> __device__ __forceinline__ void bimac(uint32_t* o, const uint32_t* a, const uint32_t* b, const uint32_t* c) {
#pragma unroll
  for (int J = 0; J < 2; J++) {
    const uint32_t Pr = a[2 * J], Pi = a[2 * J + 1], Qr = a[2 * J + 4], Qi = a[2 * J + 5], pr = b[2 * J], pi = b[2 * J + 1], qr = b[2 * J + 4], qi = b[2 * J + 5];
    uint32_t x0, x1, x2, x3;
    if (ADD == 0) { x0 = bmul2(Pr, pr); x1 = bmul2(Pr, pi); x2 = bmul2(Pr, qr); x3 = bmul2(Pr, qi); }
    if (ADD == 1) { x0 = bfma2(Pr, pr, c[2 * J]); x1 = bfma2(Pr, pi, c[2 * J + 1]); x2 = bfma2(Pr, qr, c[2 * J + 4]); x3 = bfma2(Pr, qi, c[2 * J + 5]); }
    if (ADD == 2) { x0 = bfma2(Pr, pr, c[2 * J + 1]); x1 = bfms2(Pr, pi, c[2 * J]); x2 = bfma2(Pr, qr, c[2 * J + 5]); x3 = bfms2(Pr, qi, c[2 * J + 4]); }
    x0 = bfnma2(Pi, pi, x0); x1 = bfma2(Pi, pr, x1); x2 = bfnma2(Pi, qi, x2); x3 = bfma2(Pi, qr, x3);
    x0 = bfnma2(Qr, qr, x0); x1 = bfnma2(Qr, qi, x1); x2 = bfma2(Qr, pr, x2); x3 = bfma2(Qr, pi, x3);
    x0 = bfma2(Qi, qi, x0); x1 = bfnma2(Qi, qr, x1); x2 = bfnma2(Qi, pi, x2); x3 = bfma2(Qi, pr, x3);
    o[2 * J] = x0; o[2 * J + 1] = x1; o[2 * J + 4] = x2; o[2 * J + 5] = x3;
  }
}
__device__ __forceinline__ void sincos8k(int n, float& s, float& c) {
  const float x = (float)((n << 19) >> 19) * (6.283185307179586f / 8192.f);
  s = __sinf(x); c = __cosf(x);
}
__device__ __forceinline__ void fft_tables(uint32_t f1a, uint32_t f2a, int w, int lane, uint32_t* tp, uint32_t* ts, float& d0r, float& d0i) {
  const int c = lane & 3, f1 = 8 * w + (lane >> 2);
#pragma unroll 1
  for (int J = 3; J >= 0; J--) {
    const int a = 8 * J + 2 * c;
    float s0, c0, s1, c1;
    sincos8k(64 * (4 * f1 + 1) * a + 31 * (4 * f1 - 63), d0i, d0r); sincos8k(64 * (4 * f1 + 1) * (a + 1) + 31 * (4 * f1 - 63), s1, c1);
    d0r *= 0.125f; d0i *= 0.125f;
    sts32(f1a + w * 1024 + J * 128 + lane * 4, pack_bf16(d0r, 0.125f * c1)); sts32(f1a + w * 1024 + 512 + J * 128 + lane * 4, pack_bf16(d0i, 0.125f * s1));
    sincos8k(128 * (2 * (a & 15) + 1) * f1 - 128 * (a & 16), s0, c0); sincos8k(128 * (2 * (a & 15) + 3) * f1 - 128 * (a & 16), s1, c1);
    sts32(f2a + w * 512 + J * 128 + lane * 4, pack_bf16(c0, c1));
    sincos8k((4 * f1 - 63) * (2 * a - 31), s0, c0); sincos8k((4 * f1 - 63) * (2 * a - 29), s1, c1);
#pragma unroll
    for (int i = 3; i > 0; i--) { ts[i] = ts[i - 1]; tp[i] = tp[i - 1]; }
    ts[0] = pack_bf16(s0, s1); tp[0] = pack_bf16(-__fdividef(s0, 1.f + c0), -__fdividef(s1, 1.f + c1));
  }
  if (c != 0) d0r = d0i = 0.f;
}

__device__ __forceinline__ void ss_n16(float* d, uint64_t da, uint64_t db) {
  asm volatile("wgmma.mma_async.sync.aligned.m64n16k16.f32.bf16.bf16 {%0,%1,%2,%3,%4,%5,%6,%7}, %8, %9, 0, 1, 1, 0, 0;" : W8(d, 0) : "l"(da), "l"(db));
}
template <int N> __device__ __forceinline__ void rename_regs(float* d) {
#pragma unroll
  for (int i = 0; i < N; i++) { float t; asm volatile("mov.b32 %0, %1;" : "=f"(t) : "f"(d[i]) : "memory"); d[i] = t; }
}

template <int SWAPB>
__global__ void __cluster_dims__(2, 1, 1) __launch_bounds__(512, 1)
fused_kernel(const __grid_constant__ Params P, const __grid_constant__ CUtensorMap mX, const __grid_constant__ CUtensorMap mB,
             const __grid_constant__ CUtensorMap mCre, const __grid_constant__ CUtensorMap mCim, const __grid_constant__ CUtensorMap mXs,
             const __grid_constant__ CUtensorMap mK, const __grid_constant__ CUtensorMap mV, const __grid_constant__ CUtensorMap mQ, const __grid_constant__ CUtensorMap mS,
             const __grid_constant__ CUtensorMap mO) {
  extern __shared__ __align__(1024) uint8_t smem_raw[];
  const uint32_t sb = (uint32_t)__cvta_generic_to_shared(smem_raw);
  const uint32_t bars = sb + OFF_BAR;
  const int slot = (P.slot[blockIdx.x >> 3] >> (4 * (blockIdx.x & 6))) & 63, rank = blockIdx.x & 1;
  const int j = slot & 7, tc = 2 * (slot >> 3) + rank, b = 2 * slot + rank;
  const int tid = threadIdx.x;
  const int warp = __shfl_sync(0xffffffffu, tid >> 5, 0);
  const int wg = warp >> 2;
  const uint32_t c_start = clk32();
  auto kblock = [&](int n) { return ((n & 14) == 0 || (n & 14) == 2 * j ? n ^ (2 * j) : n) & 31; };
  auto send_y = [&](int r) {
    const uint32_t src = sb + OFF_U + 4 * (rank ^ 1) * U_N8 + r * U_CH, dst = r >= 2 ? sb + OFF_U + 4 * rank * U_N8 + (r - 2) * U_CH : sb + OFF_IN + 96 + r * 2064;
#pragma unroll 1
    for (int n = 0; n < 4; n++) bulk_send(dst + n * (r >= 2 ? U_N8 : 512), src + n * U_N8, 512, bars + (B_IN + r) * 8, rank ^ 1);
  };
  auto load_q = [&](int i, int off, int bar) {
    const uint32_t fb = bars + bar * 8 + 4 * (i & 2);
    mbar_expect(fb, 4096); tma4d(sb + off + 2048 * (i & 2), &mQ, 16 * slot, 0, 4 * i, 4 * rank, fb);
  };
  auto head = [&](int n) {
    const uint32_t fb = bars + (B_FULL + n) * 8, dst = sb + OFF_RING + n * STAGE_BYTES;
    mbar_expect(fb, STAGE_BYTES);
    tma4d(dst + 16384, &mX, 64 * n, 0, 4 * tc, 0, fb);
    tma4d(dst, &mB, 64 * n, 0, 0, 8 * j, fb);
    tma4d(dst + 8192, &mB, 64 * n, 0, 0, 8 * j + 4, fb);
  };
  if (warp == 0 && elect_one()) {
#pragma unroll
    for (int s = 0; s < STAGES; s++) mbar_init(bars + (B_FULL + s) * 8, 1);
    head(0);
    asm volatile("fence.mbarrier_init.release.cluster;" ::: "memory");
  }
  if (wg == 3 && elect_one()) {
    if (warp < 15) {
#pragma unroll
      for (int s = 0; s < 11; s++) mbar_init(bars + 8 * B_XI + (warp & 3) * 88 + 8 * s, 1);
    } else {
#pragma unroll
      for (int s = B_EMPTY; s <= B_NONE; s++) mbar_init(bars + 8 * s, s < B_COEF ? 2 : s == B_COEF ? 128 : 4);
    }
    asm volatile("fence.mbarrier_init.release.cluster;" ::: "memory");
  }
  __syncwarp();
  asm volatile("barrier.cluster.arrive.relaxed.aligned;" ::: "memory");
  if (warp == 0 && elect_one()) {
#pragma unroll 1
    for (int n = 1; n < HEAD; n++) { spin_until(c_start, ST_T0 + n * ST_DELAY); head(n); }
  }
  __syncwarp();
  int fl;
  uint32_t fa, fs;
  uint2 q[4][4];
  auto fin_setup = [&]() {
    asm volatile("mov.u32 %0, %%laneid;" : "=r"(fl));
    const int lc = 2 * (fl & 2) + (fl & 1) + ((fl >> 2) & 2);
    const bool own = ((fl >> 2) & 1) == rank, spare = !own && lc < 2;
    fa = (spare ? sb + OFF_IN + 96 + lc * 2064 : sb + OFF_U + (own ? 4 * rank * U_N8 : 4 * (rank ^ 1) * U_N8 - 2 * U_CH) + lc * U_CH) + (warp & 3) * 128 + (fl >> 4) * 16 + (wg & 1) * 64;
    fs = spare ? 512 : U_N8;
  };
  auto get_q = [&](int n, int off, int bar, int ph) {
#pragma unroll
    for (int u = 0; u < 2; u++) {
      mbar_wait(bars + (bar + u) * 8, ph);
#pragma unroll
      for (int r = 0; r < 4; r++) q[n + u][r] = lds64(sb + off + 4096 * u + 1024 * (warp & 3) + 256 * r + 8 * fl);
    }
  };
#define CLUSTER_WAIT() asm volatile("barrier.cluster.wait.aligned;" ::: "memory")

  if (wg == 3) {
    asm volatile("setmaxnreg.dec.sync.aligned.u32 24;");
    CLUSTER_WAIT();
    if (warp < 14) {
      if (elect_one()) {
        uint32_t so = 8 * (HEAD % STAGES), ph = HEAD < STAGES;
        auto step = [&](auto issue) {
          mbar_wait(bars + B_EMPTY * 8 + so, ph);
          issue(sb + OFF_RING + (so << 12), bars + B_FULL * 8 + so);
          so += 8;
          if (so == 8 * STAGES) { so = 0; ph ^= 1; }
        };
        if (warp == 12) {
          auto g1 = [&](int n0, int n1, int grp) {
#pragma unroll 1
            for (int n = n0; n < n1; n++) step([&](uint32_t dst, uint32_t fb) { mbar_expect(fb, STAGE_BYTES); tma4d_mc(dst + rank * 8192, &mB, n * 64, 0, 0, grp + 4 * rank, fb); });
          };
#pragma unroll 1
          for (int n = HEAD; n < STAGES; n++) { spin_until(c_start, ST_T0 + n * ST_DELAY); g1(n, n + 1, 8 * j); }
          g1(STAGES, 16, 8 * j);
          g1(0, XPOS - 16, 8 * j + 64);
          step([&](uint32_t dst, uint32_t fb) { mbar_expect(fb, STAGE_BYTES); tma4d(dst, &mXs, 128 * j, 0, 4 * tc, 0, fb); });
#pragma unroll 1
          for (int n = 0; n < 32; n += 2) {
            const int col = kblock(n) * 32;
#pragma unroll
            for (int part = 0; part < 2; part++)
              step([&](uint32_t dst, uint32_t fb) { mbar_expect(fb, STAGE_BYTES); tma5d_mc(dst + rank * 8192, part ? &mCim : &mCre, col, 0, 0, 0, 8 * j + 4 * rank, fb); });
          }
        } else {
          auto g1 = [&](int n0, int n1, int nb) {
#pragma unroll 1
            for (int n = n0; n < n1; n++) step([&](uint32_t dst, uint32_t fb) { tma4d(dst + 16384, &mX, n * 64, 0, 4 * tc, 0, fb); });
          };
          auto g2 = [&](int n0, int n1) {
#pragma unroll 1
            for (int n = n0; n < n1; n++) step([&](uint32_t dst, uint32_t fb) { bulk_load(dst + 16384, g_h + (32 * tc + kblock(n)) * 1024, 16384, fb); });
          };
#pragma unroll 1
          for (int n = HEAD; n < STAGES; n++) { spin_until(c_start, ST_T0 + n * ST_DELAY); g1(n, n + 1, 0); }
          g1(STAGES, 16, 0);
          g1(0, XPOS - 16, 16);
          step([&](uint32_t dst, uint32_t fb) { tma4d(dst + 16384, &mXs, 128 * j + 64, 0, 4 * tc, 0, fb); });
#pragma unroll 1
          for (int v = 0; v < 2; v++) {
            mbar_wait(bars + B_HP * 8, v);
            fence_proxy_async_global();
            g2(16 * v, 16 * v + 2);
            mbar_wait(bars + B_HR * 8, v);
            fence_proxy_async_global();
            g2(16 * v + 2, 16 * v + 16);
          }
        }
      }
    } else if (warp == 15) {
      mbar_wait(bars + B_COEF * 8, 0);
      const unsigned epoch = lds32(bars + B_EPOCH * 8);
#pragma unroll 1
      for (int v = 0; v < 2; v++) {
        unsigned* fp = &g_flagH[(16 * v + tc) * 32];
        if (elect_one()) {
          wait_until(v ? clk32() : c_start, (v ? PFC_T1 : PFC_T0) + (slot >> 3) * PFC_DT);
#pragma unroll
          for (int part = 0; part < 2; part++)
            asm volatile("cp.async.bulk.prefetch.tensor.5d.L2.global [%0, {%1, %2, %2, %2, %3}];" ::"l"(part ? &mCim : &mCre), "r"(512 * v + 8 * (slot & 56)), "r"(0), "r"(8 * j + 4 * rank) : "memory");
        }
        __syncwarp();
        bar_sync(4 + v, 160);
        if (elect_one()) {
          asm volatile("red.release.gpu.global.add.u32 [%0], 1;" ::"l"(fp) : "memory");
          mbar_arrive(bars + B_HP * 8);
          int it = 0;
          while (ld_acquire(fp) != 8 * epoch && ++it < (SPIN_LIMIT << 4)) __nanosleep(POLL_NS);
          mbar_arrive(bars + B_HR * 8);
        }
        __syncwarp();
      }
    } else if (elect_one()) {
      const int ch0 = 16 * slot;
      auto load_k = [&](int s, uint32_t dst) { const uint32_t fb = bars + (B_KF + (s & 1)) * 8; mbar_expect(fb, 4096); tma2d(dst, &mS, 0, 64 * (8 * b + s), fb); };
      prefetch_map(&mS); prefetch_map(&mK); prefetch_map(&mV);
      wait_until(c_start, K_T0);
      load_k(0, sb + OFF_U + (4 * rank + 3) * U_N8); load_k(1, sb + OFF_U + (4 * rank + 3) * U_N8 - 4096);
      {
        uint32_t so = 16, ph = 1;
#pragma unroll 1
        for (int e = 0; e < 9; e++) {
          const uint32_t fb = bars + B_KVF * 8 + so, dst = sb + OFF_KV + (so << 10);
          wait_until(c_start, KV_T0 + (e ? 2 * e - 1 : 0) * KV_DT);
          mbar_wait(bars + B_KVE * 8 + so, ph);
          const uint32_t c1 = clk32();
          mbar_expect(fb, e ? 8192 : 4096);
          tma3d(dst, &mK, ch0, 32 * rank - (e == 0), (4 * e - 4) & 31, fb);
          if (e > 0) { wait_until(c1, KV_DV); tma3d(dst + 4096, &mV, ch0, 32 * rank, 4 * e - 4, fb); }
          so += 8;
          if (so == 24) so = 0;
          if (so == 16) ph ^= 1;
        }
      }
      prefetch_map(&mCre); prefetch_map(&mCim); prefetch_map(&mXs); prefetch_map(&mQ); prefetch_map(&mO);
      mbar_wait(bars + B_KVE * 8, 0);
      load_k(2, sb + OFF_K); load_k(3, sb + OFF_K + 4096);
      mbar_wait(bars + (B_UF + 3) * 8, 0);
#pragma unroll 1
      for (int ch = 0; ch < 7; ch++) {
        if (ch > 0) {
          mbar_wait(bars + (B_Y + (ch & 3)) * 8, ch >> 2);
          if (ch > 2) mbar_wait(bars + (B_IN + ch - 3) * 8, 0);
          send_y(ch - 1);
        }
        if (ch < 6) {
          mbar_wait(bars + (B_KE + (ch & 1)) * 8, (ch >> 1) & 1);
          if (ch < 4) load_k(ch + 4, sb + OFF_K + (ch & 1) * 4096);
          if (ch == 3) asm volatile("cp.async.bulk.prefetch.tensor.4d.L2.global [%0, {%1, %2, %3, %4}];" ::"l"(&mQ), "r"(16 * (slot & ~3)), "r"(0), "r"(16 + 4 * (slot & 3)), "r"(4 * rank) : "memory");
          if (ch == 2) load_q(1, OFF_Q, B_QF);
          if (ch >= 4) load_q(2 * (ch & 1), OFF_K, B_KF);
          if (ch == 4) { mbar_wait(bars + B_XI * 8, 0); load_q(3, OFF_Q, B_QF); }
        }
      }
    }
    return;
  } else if (wg == 2) {
    asm volatile("setmaxnreg.inc.sync.aligned.u32 %0;" ::"n"(488 - 2 * GREG));
    const int t = tid & 127, w = warp & 3, lane = t & 31, g = lane >> 2, c = lane & 3;
    const uint4 s2[2] = {ldg128_nc(P.shift_k + (8 * b + 2 * c) * 4), ldg128_nc(P.shift_k + (8 * (b ^ 1) + 2 * c) * 4)};
    const uint32_t dskip = __bfloat16_as_ushort(P.ssm_D[8 * b + (t & 7)]);
    uint32_t tp[4] = {}, ts[4] = {};
    float d0r, d0i;
    fft_tables(sb + OFF_F1, sb + OFF_F2, w, lane, tp, ts, d0r, d0i);
    CLUSTER_WAIT();
    if (t < 12) mbar_expect(bars + (B_IN + t) * 8, t < 6 ? 2048 : t < 8 ? 4 * (U_CH + 512) : U_N8);
    if (t < 8) sts32(sb + OFF_D + 4 * t, dskip << 16);
    const uint64_t dF1a = make_desc(sb + OFF_F1, 128, 512, 0), dF1b = make_desc(sb + OFF_F1, 512, 128, 0);
    const uint64_t dF2f = make_desc(sb + OFF_F2, 512, 128, 0), dF2i = make_desc(sb + OFF_F2, 128, 512, 0);
    auto T1k = [&](float* z, uint64_t dk) { wg_fence(); ss_n64<0, 1>(z, dF1a, dk); ss_n64<1, 1>(z, dF1a + 16, dk + 64); wg_commit(); };
    auto T1u = [&](float* z, uint64_t du) { wg_fence(); ss_n64<0, 0>(z, dF1a, du); ss_n64<1, 0>(z, dF1a + 16, du + 16); wg_commit(); };
    auto T2 = [&](float* s, const uint32_t* f) {
      wg_fence();
      rs_n32<0, 1>(s, f, dF2f); rs_n32<0, 1>(s + 16, f + 8, dF2f); rs_n32<1, 1>(s, f + 4, dF2f + 64); rs_n32<1, 1>(s + 16, f + 12, dF2f + 64);
      wg_commit();
    };
    auto product = [&](uint32_t* pr, const uint32_t* kh, const uint32_t* uh) {
      bimac<0>(pr, kh, uh, pr); bimac<2>(pr + 8, kh + 8, uh, pr); bimac<1>(pr + 8, kh, uh + 8, pr + 8);
      fence_u32<16>(pr);
    };
    float zk[32] = {};
    uint32_t pr[16];
    {
      uint32_t kh0[16];
      {
        float z0[32], sk[32];
        uint32_t fk[16];
        const uint64_t dk = make_desc(sb + OFF_U + (4 * rank + 3) * U_N8, 2048, 512, 2);
        fence_proxy_async_smem();
        bar_sync(7, 128);
        mbar_wait(bars + B_KF * 8, 0);
        T1k(z0, dk);
        mbar_wait(bars + (B_KF + 1) * 8, 0);
        T1k(zk, dk - 256);
        wg_wait<0>(); fence_regs<32>(z0); fence_regs<32>(zk);
        const float dd = __uint_as_float(lds32(sb + OFF_D));
        z0[0] = fmaf(d0r, dd, z0[0]); z0[2] = fmaf(d0i, dd, z0[2]);
        pack32(fk, z0); twiddle<0>(fk, tp, ts); fence_u32<16>(fk);
        T2(sk, fk);
        wg_wait<0>(); fence_regs<32>(sk); fence_u32<16>(fk);
        pack32(kh0, sk); fence_u32<16>(kh0);
      }
      {
        uint32_t sk[2][4], kx[2][8];
#pragma unroll
        for (int o = 0; o < 2; o++) {
          sk[o][0] = __byte_perm(s2[o].x, s2[o].z, 0x5410); sk[o][1] = __byte_perm(s2[o].x, s2[o].z, 0x7632);
          sk[o][2] = __byte_perm(s2[o].y, s2[o].w, 0x5410); sk[o][3] = __byte_perm(s2[o].y, s2[o].w, 0x7632);
        }
        const uint32_t la = sb + OFF_KV + (lane >> 3) * 1024 + (8 * w + (lane & 7)) * 32 + ((rank ^ ((lane >> 2) & 1)) << 4);
        const uint32_t uo = (lane & 7) * U_CH + w * 128 + (lane >> 3) * 16;
        mbar_wait(bars + (B_KVF + 2) * 8, 0);
        ldsm4(kx[0], la + 16384); ldsm4(kx[1], (la ^ 16) + 16384);
        if (lane == 0) mbar_arrive(bars + (B_KVE + 2) * 8 + (kx[0][1] & kx[1][1] & P.zero));
        uint32_t so = 0, ph = 0;
#pragma unroll 1
        for (int n = 0; n < 4; n++) {
          const uint32_t own = sb + OFF_U + (4 * rank + n) * U_N8, box = n < 3 ? sb + OFF_U + (4 * (rank ^ 1) + n + 1) * U_N8 : sb + OFF_IN;
#pragma unroll
          for (int e = 0; e < 2; e++) {
            uint32_t vx[2][4];
            mbar_wait(bars + B_KVF * 8 + so, ph);
#pragma unroll
            for (int o = 0; o < 2; o++) { ldsm4(kx[o] + 4, (la ^ (16 * o)) + (so << 10)); ldsm4(vx[o], (la ^ (16 * o)) + (so << 10) + 4096); }
            if (lane == 0) mbar_arrive(bars + B_KVE * 8 + so + (kx[0][4] & kx[1][4] & vx[0][0] & vx[1][0] & P.zero));
#pragma unroll
            for (int o = 0; o < 2; o++) {
#pragma unroll
              for (int i = 0; i < 4; i++) vx[o][i] = bmul2(bfma2(kx[o][i + 4], sk[o][0], bfma2(kx[o][i + 3], sk[o][1], bfma2(kx[o][i + 2], sk[o][2], bmul2(kx[o][i + 1], sk[o][3])))), vx[o][i]);
              stsm4t((o ? box : own) + uo + e * 64, vx[o][0], vx[o][1], vx[o][2], vx[o][3]);
              kx[o][1] = kx[o][5]; kx[o][2] = kx[o][6]; kx[o][3] = kx[o][7];
            }
            so += 8;
            if (so == 24) so = 0;
            if (so == 16) ph ^= 1;
          }
          fence_proxy_async_smem();
          bar_sync(7, 128);
          if (w == 0 && elect_one()) {
            if (n > 0) mbar_wait(bars + B_UF * 8 + 8 * (n - 1), 0);
            bulk_send(own, box, U_N8, bars + B_UF * 8 + 8 * n, rank ^ 1);
          }
          __syncwarp();
        }
      }
      float zu[32], su[32];
      uint32_t fu[16], uh[16];
#pragma unroll
      for (int n = 0; n < 4; n++) mbar_wait(bars + (B_UF + n) * 8, 0);
      T1u(zu, make_desc(sb + OFF_U, 128, U_N8, 0));
      wg_wait<0>(); fence_regs<32>(zu);
      pack32(fu, zu); twiddle<0>(fu, tp, ts); fence_u32<16>(fu);
      T2(su, fu);
      wg_wait<0>(); fence_regs<32>(su); fence_u32<16>(fu);
      pack32(uh, su);
      product(pr, kh0, uh);
    }
    {
#define CF(i) do { if ((CFM >> (i)) & 1) PMFENCE(); } while (0)
      const uint32_t vs = w < 2 ? 512 : U_N8;
      uint32_t va = (w < 2 ? sb + OFF_VP : sb + OFF_U) + ((lane >> 4) & 1) * vs + (w & 1) * 256 + (lane & 15) * 16;
      uint32_t ya = sb + OFF_U + (2 * w + ((lane >> 3) & 1)) * U_N8 + (lane >> 4) * 128 + (lane & 7) * 16;
      uint64_t du = make_desc(sb + OFF_U, 128, U_N8, 0), dk = make_desc(sb + OFF_K, 2048, 512, 2);
      const uint64_t dv = make_desc(sb + OFF_VP, 128, 512, 0);
      uint32_t yp[8] = {};
      uint32_t yq = sb + OFF_Q + lane * 16;
      auto store_y = [&]() { stsm4(yq, yp[0], yp[1], yp[2], yp[3]); stsm4(yq + 256, yp[4], yp[5], yp[6], yp[7]); };
      auto step = [&](int ch, auto fwd) {
        constexpr bool FWD = decltype(fwd)::value;
        float zu[32], sk[32], su[32], v[32], y[16];
        uint32_t kh[16], uh[16], fk[16], fu[16], fv[16];
        wg_fence();
        rs_n32<0, 0>(v, pr, dF2i); rs_n32<0, 0>(v + 16, pr + 8, dF2i); rs_n32<1, 0>(v, pr + 4, dF2i + 16); rs_n32<1, 0>(v + 16, pr + 12, dF2i + 16);
        wg_commit();
        CF(0);
        store_y();
        if (FWD) {
          const float dd = __uint_as_float(lds32(sb + OFF_D + 4 * (ch + 1)));
          zk[0] = fmaf(d0r, dd, zk[0]); zk[2] = fmaf(d0i, dd, zk[2]);
          pack32(fk, zk); twiddle<0>(fk, tp, ts); fence_u32<16>(fk);
          T2(sk, fk);
          CF(2);
          mbar_wait(bars + (B_KF + (ch & 1)) * 8, ((ch >> 1) & 1) ^ 1);
          wg_wait<1>();
        } else {
#pragma unroll
          for (int r = 3; r < 6; r++) mbar_wait(bars + (B_IN + r) * 8, 0);
          wg_wait<0>();
        }
        fence_regs<32>(v); fence_u32<16>(pr);
        pack32(fv, v); fence_u32<16>(fv);
        CF(4);
        if (FWD) T1u(zu, du + U_CH / 16);
        CF(5);
        if (FWD) { wg_wait<1>(); fence_regs<32>(sk); fence_u32<16>(fk); pack32(kh, sk); }
        twiddle<1>(fv, tp, ts);
#pragma unroll
        for (int i = 0; i < 4; i++) stsm4(va + 2 * i * vs, fv[4 * i], fv[4 * i + 1], fv[4 * i + 2], fv[4 * i + 3]);
        if (FWD) {
          fence_u32<16>(kh);
          CF(7);
          T1k(zk, dk);
          CF(8);
          wg_wait<1>(); fence_regs<32>(zu);
          pack32(fu, zu); twiddle<0>(fu, tp, ts); fence_u32<16>(fu);
          T2(su, fu);
          CF(10);
        }
        fence_proxy_async_smem();
        bar_sync(7, 128);
        wg_fence();
        ss_n32_tt<0>(y, dv, dF1b); ss_n32_tt<1>(y, dv + 16, dF1b + 64); ss_n32_tt<1>(y, du, dF1b + 128); ss_n32_tt<1>(y, du + 16, dF1b + 192);
        wg_commit();
        if (FWD && t == 0) mbar_arrive(bars + (B_Y + (ch & 3)) * 8);
        CF(12);
        if (FWD) {
          wg_wait<1>(); fence_regs<32>(su); fence_u32<16>(fu); fence_regs<32>(zk);
          if (t == 0) mbar_arrive(bars + (B_KE + (ch & 1)) * 8);
          pack32(uh, su);
          bimac<0>(pr, kh, uh, pr); bimac<2>(pr + 8, kh + 8, uh, pr); fence_u32<16>(pr);
          CF(14);
          wg_wait<0>(); fence_regs<16>(y);
          bimac<1>(pr + 8, kh, uh + 8, pr + 8); fence_u32<8>(pr + 8);
          du += U_CH / 16; dk += (ch & 1) ? -256 : 256;
          if (w >= 2) va += U_CH;
        }
        if (!FWD) {
          PMFENCE();
          fin_setup(); get_q(0, OFF_K, B_KF, 0);
#pragma unroll
          for (int r = 0; r < 8; r++) q[2 + (r >> 2)][r & 3] = make_uint2(0, 0);
          wg_wait<0>(); fence_regs<16>(y);
        }
#pragma unroll
        for (int i = 0; i < 8; i++) yp[i] = pack_bf16(y[2 * i], y[2 * i + 1]);
        fence_u32<8>(yp);
        yq = ya;
        ya += U_CH;
      };
#pragma unroll 1
      for (int ch = 0; ch < 7; ch++) step(ch, std::true_type());
      step(7, std::false_type());
      store_y();
    }
    fence_proxy_async_smem();
    bar_sync(7, 128);
    if (elect_one()) bulk_send(sb + OFF_U + (4 * rank + w) * U_N8 + 4 * U_CH, sb + OFF_U + (4 * (rank ^ 1) + w) * U_N8 + 6 * U_CH, U_CH + 512, bars + (B_IN + 6) * 8, rank ^ 1);
    __syncwarp();
    asm volatile("bar.arrive 9, 256;" ::: "memory");
  } else {
    asm volatile("setmaxnreg.inc.sync.aligned.u32 %0;" ::"n"(GREG));
    const int t = tid & 127, w = warp & 3, lane = t & 31, g = lane >> 2, c = lane & 3;
    if (wg == 1) {
      wait_until(c_start, COEF_T0);
      const int p = 64 * j + (t & 63) + 8 * (t & 64);
      const float Lr = bf2f(P.lam_re[p]), Li = bf2f(P.lam_im[p]);
      const uint32_t ds = __bfloat16_as_ushort(P.Dskip[128 * j + t]);
      const unsigned epoch = ld_relaxed(&g_epoch[b * 32]) + 1;
      const float dt = bf2f(__float2bfloat16_rn(expf(bf2f(P.log_dt[p]))));
      const float e = expf(dt * Lr);
      float sn, cs;
      {
        const double z = (double)(dt * Li) * 0.15915494309189535;
        sincospif(2.f * (float)(z - rint(z)), &sn, &cs);
      }
      const float lr = e * cs, li = e * sn;
      const float nr = lr - 1.0f, ni = li;
      const bool big = fabsf(Lr) >= fabsf(Li);
      const float la = big ? Lr : Li, lb = big ? Li : Lr, r = __fdiv_rn(lb, la), inv = __frcp_rn(fmaf(lb, r, la));
      const float br = (big ? fmaf(ni, r, nr) : fmaf(nr, r, ni)) * inv, bi = (big ? fmaf(-nr, r, ni) : fmaf(ni, r, -nr)) * inv;
      sts128(sb + OFF_COEF + t * 16, make_uint4(__float_as_uint(lr), __float_as_uint(li), pack_bf16(2.f * br, 2.f * br), pack_bf16(-2.f * bi, -2.f * bi)));
      sts32(sb + OFF_DS + 4 * t, ds << 16);
      if (t == 0) sts32(bars + B_EPOCH * 8, epoch);
    }
    CLUSTER_WAIT();
    if (wg == 1) mbar_arrive(bars + B_COEF * 8);
    float d[128];
    uint32_t so = 0, ph = 0, po = 0;
    uint32_t ra;
    auto set_ra = [&]() { asm volatile("mapa.shared::cluster.u32 %0, %1, %2;" : "=r"(ra) : "r"(bars + B_EMPTY * 8), "r"((t & 1) ? rank ^ 1 : rank)); };
    set_ra();
    auto release = [&](uint32_t off) { if (t < 2) asm volatile("mbarrier.arrive.shared::cluster.b64 _, [%0];" ::"r"(ra + off) : "memory"); };
    constexpr uint32_t NOBAR = 8 * (B_NONE - B_EMPTY);
    auto block = [&](auto ta, uint64_t da0, uint64_t db0, bool zero, int nn) {
      constexpr int PH = decltype(ta)::value, TA = PH > 0, KS = TA ? 128 : 2, QD = PH == 0 ? QD1 : PH == 1 ? QD2 : QD3;
      mbar_wait(bars + B_FULL * 8 + so, ph);
      const uint64_t da = da0 + (so << 8), db = db0 + (so << 8);
      wg_fence();
      wgmma_n128<TA>(d, da, db, !zero);
      wgmma_n128<TA>(d + 64, da + 512, db, !zero);
      wg_commit();
      wg_wait<1>();
      release(po);
#pragma unroll
      for (int k = 1; k < 4; k++) {
        if (QD == 2 || (QD == 4 && k == 2)) wg_fence();
        wgmma_n128<TA>(d, da + KS * k, db + 2 * k, 1);
        wgmma_n128<TA>(d + 64, da + 512 + KS * k, db + 2 * k, 1);
        if (QD == 2 || (QD == 4 && k == 1)) wg_commit();
        if ((QD == 2 && k < 3) || (QD == 4 && k == 1)) wg_wait<1>();
      }
      if (QD != 2) wg_commit();
      po = so;
      so += 8;
      if (so == 8 * STAGES) { so = 0; ph ^= 1; }
    };
    {
      so = wg ? 8 * (16 % STAGES) : 0; ph = wg ? (16 / STAGES) & 1 : 0; po = NOBAR;
      const uint64_t da0 = make_desc(sb + OFF_RING, 16, 1024, 1), db0 = make_desc(sb + OFF_RING + 16384, 16, 1024, 1);
      if (wg == 1) bar_sync(1, 256);
#pragma unroll 1
      for (int kb = 0; kb < 16; kb++) {
        block(std::integral_constant<int, 0>(), da0, db0, kb == 0, 16 * wg + kb);
      }
      asm volatile("bar.arrive %0, 256;" ::"r"(1 + wg) : "memory");
    }
    mbar_wait(bars + B_COEF * 8, 0);
    const uint32_t ca = sb + OFF_COEF + (64 * wg + 8 * w + g) * 16;
    const uint32_t tag = __shfl_sync(0xffffffffu, lds32(bars + B_EPOCH * 8) & 3, 0);
    constexpr int RE = SWAPB ? 2 : 0, IM = 2 - RE;
    const int ct = lane >> 3;
    const uint2* cp = g_carry + __shfl_sync(0xffffffffu, ((16 * wg + 2 * j) * 16 + tc - 1 - ct) * 32 + 8 * w + (lane & 7), lane);
    unsigned long long cv[4];
    auto load_carry = [&](int i) {
#pragma unroll
      for (int m = 0; m < 4; m++)
        asm volatile("{\n.reg .pred p;\nsetp.lt.s32 p, %2, %3;\n@p ld.relaxed.gpu.global.b64 %0, [%1];\n}\n" : "=l"(cv[m]) : "l"(cp + 512 * i - 128 * m), "r"(ct + 4 * m), "r"(tc) : "memory");
    };
    float lr[2], li[2], pr[2], pi[2], wr[2], wi[2], vr[2], vi[2], qr[2], qi[2], er[2], ei[2], gr[2], gi[2];
    auto powers = [&](int i) {
      const uint2 cf = lds64(ca + 512 * i);
      pr[i] = lr[i] = __uint_as_float(cf.x); pi[i] = li[i] = __uint_as_float(cf.y);
#pragma unroll
      for (int s = 0; s < 4; s++) csq(pr[i], pi[i]);
      gr[i] = pr[i]; gi[i] = pi[i];
      csq(pr[i], pi[i]);
      qr[i] = pr[i]; qi[i] = pi[i];
      csq(qr[i], qi[i]);
      er[i] = qr[i]; ei[i] = qi[i];
      wr[i] = (c & 1) ? pr[i] : 1.f; wi[i] = (c & 1) ? pi[i] : 0.f;
      if (c & 2) { float x, y; cmul(wr[i], wi[i], qr[i], qi[i], x, y); wr[i] = x; wi[i] = y; }
      vr[i] = wr[i]; vi[i] = wi[i];
      csq(vr[i], vi[i]); csq(vr[i], vi[i]);
      csq(qr[i], qi[i]); csq(qr[i], qi[i]); csq(qr[i], qi[i]);
      const int src = 4 * (lane & 7) + ct;
      vr[i] = __shfl_sync(0xffffffffu, vr[i], src); vi[i] = __shfl_sync(0xffffffffu, vi[i], src);
      qr[i] = __shfl_sync(0xffffffffu, qr[i], src); qi[i] = __shfl_sync(0xffffffffu, qi[i], src);
      asm volatile("" : "+f"(wr[i]), "+f"(wi[i]), "+f"(pr[i]), "+f"(pi[i]), "+f"(er[i]), "+f"(ei[i]));
    };
    powers(0);
    PMFENCE();
    wg_wait<0>();
    fence_regs<128>(d);
    release(po);
#pragma unroll
    for (int i = 0; i < 2; i++) {
      const float* e = d + 64 * i;
      auto chain = [&](int s0, int s1, float& sr, float& si) {
        sr = e[2 * s0 + RE]; si = e[2 * s0 + IM];
#pragma unroll
        for (int s = s0 + 1; s < s1; s++) {
          const int ia = 4 * (s >> 1) + (s & 1);
          const float nr = fmaf(-li[i], si, fmaf(lr[i], sr, e[ia + RE])), ni = fmaf(li[i], sr, fmaf(lr[i], si, e[ia + IM]));
          sr = nr; si = ni;
        }
      };
      float sr, si;
      if (i == 1) powers(1);
      if ((GREEDY >> i) & 1) {
        float ar, ai;
        chain(0, 16, ar, ai); chain(16, 32, sr, si);
        sr = fmaf(gr[i], ar, fmaf(-gi[i], ai, sr)); si = fmaf(gr[i], ai, fmaf(gi[i], ar, si));
      } else chain(0, 32, sr, si);
      if (i == 1) { asm volatile("pmevent 0;" : "+f"(sr), "+f"(si)::"memory"); load_carry(0); }
      float ur = __shfl_up_sync(0xffffffffu, sr, 1, 4), ui = __shfl_up_sync(0xffffffffu, si, 1, 4);
      if (c >= 1) { sr = fmaf(pr[i], ur, fmaf(-pi[i], ui, sr)); si = fmaf(pr[i], ui, fmaf(pi[i], ur, si)); }
      ur = __shfl_up_sync(0xffffffffu, sr, 2, 4); ui = __shfl_up_sync(0xffffffffu, si, 2, 4);
      if (c >= 2) { sr = fmaf(er[i], ur, fmaf(-ei[i], ui, sr)); si = fmaf(er[i], ui, fmaf(ei[i], ur, si)); }
      ur = __shfl_sync(0xffffffffu, sr, 4 * lane + 3); ui = __shfl_sync(0xffffffffu, si, 4 * lane + 3);
      asm volatile("{\n.reg .pred p;\n.reg .b64 v;\nsetp.lt.u32 p, %3, 8;\nmov.b64 v, {%1,%2};\n@p st.relaxed.gpu.global.b64 [%0], v;\n}\n"
                   ::"l"(cp + 512 * i + 32), "r"((__float_as_uint(ur) & ~3u) | tag), "r"(__float_as_uint(ui)), "r"(lane) : "memory");
      PMFENCE();
      er[i] = __shfl_up_sync(0xffffffffu, sr, 1, 4); ei[i] = __shfl_up_sync(0xffffffffu, si, 1, 4);
      if (c == 0) er[i] = ei[i] = 0.f;
    }
    uint4* hp = g_h + (32 * tc + 16 * wg + 2 * j) * 1024 + 64 * w + 4 * g + (c ^ (g >> 1));
#pragma unroll
    for (int i = 0; i < 2; i++) {
      float* e = d + 64 * i;
      const uint2 cf = lds64(ca + 512 * i + 8);
      const uint32_t gp = cf.x, gms = cf.y;
      PMFENCE();
      auto ready = [&]() {
        uint32_t bad = 0;
#pragma unroll
        for (int m = 0; m < 4; m++) if (ct + 4 * m < tc) bad |= (uint32_t)cv[m] ^ tag;
        return __all_sync(0xffffffffu, (bad & 3) == 0);
      };
      if (!ready()) {
        int n = 0;
#pragma unroll 1
        do load_carry(i); while (!ready() && ++n <= (SPIN_LIMIT << 4));
      }
      float hr = 0.f, hi = 0.f;
#pragma unroll
      for (int m = 3; m >= 0; m--) {
        const float x = __uint_as_float((uint32_t)cv[m]), y = __uint_as_float((uint32_t)(cv[m] >> 32));
        const float nr = m == 3 ? x : fmaf(qr[i], hr, fmaf(-qi[i], hi, x)), ni = m == 3 ? y : fmaf(qr[i], hi, fmaf(qi[i], hr, y));
        if (ct + 4 * m < tc) { hr = nr; hi = ni; }
      }
      { float x, y; cmul(hr, hi, vr[i], vi[i], x, y); hr = x; hi = y; }
      hr += __shfl_xor_sync(0xffffffffu, hr, 8); hi += __shfl_xor_sync(0xffffffffu, hi, 8);
      hr = __shfl_sync(0xffffffffu, hr, g) + __shfl_sync(0xffffffffu, hr, g + 16); hi = __shfl_sync(0xffffffffu, hi, g) + __shfl_sync(0xffffffffu, hi, g + 16);
      float sr = fmaf(wr[i], hr, fmaf(-wi[i], hi, er[i])), si = fmaf(wr[i], hi, fmaf(wi[i], hr, ei[i]));
#pragma unroll
      for (int i8 = 0; i8 < 4; i8++) {
        asm volatile("pmevent 0;" : "+f"(sr), "+f"(si)::"memory");
        if (i == 0 && i8 == 1) load_carry(1);
#pragma unroll
        for (int s = 8 * i8; s < 8 * i8 + 8; s++) {
          const int ia = 4 * (s >> 1) + (s & 1);
          const float nr = fmaf(-li[i], si, fmaf(lr[i], sr, e[ia + RE])), ni = fmaf(li[i], sr, fmaf(lr[i], si, e[ia + IM]));
          sr = nr; si = ni;
          e[ia + RE] = nr; e[ia + IM] = ni;
        }
        uint32_t hp0[4], hp1[4];
#pragma unroll
        for (int m = 0; m < 4; m++) {
          const float* f = e + 16 * i8 + 4 * m;
          const uint32_t x = pack_bf16(f[RE], f[RE + 1]), y = pack_bf16(f[IM], f[IM + 1]);
          hp0[m] = bfma2(gp, x, bmul2(gms, y)); hp1[m] = bfnma2(gp, y, bmul2(gms, x));
        }
        uint4* o = hp + 512 * (i8 >> 1) + 256 * i + 32 * (i8 & 1);
        stg128(o, make_uint4(hp0[0], hp0[1], hp0[2], hp0[3]));
        stg128(o + 1024, make_uint4(hp1[0], hp1[1], hp1[2], hp1[3]));
      }
    }
    const int trow = 128 * tc + 64 * (w & 1) + 8 * (w >> 1) + g;
    const int dcol = 128 * j + 4 * c;
    asm volatile("bar.arrive %0, 160;" ::"r"(4 + wg) : "memory");
    if (wg == 0) {
      set_ra();
      {
        const uint32_t dt = sb + OFF_Q + 4096;
        mbar_wait(bars + (B_UF + 3) * 8, 0);
        const int n = t & 15, k = 2 * (n & 6) + 2 * (n >> 3) + (n & 1);
        const uint32_t dv = lds32(sb + OFF_DS + (t & ~15) * 4 + 4 * k) >> (16 - 16 * (k & 1));
#pragma unroll
        for (int u = 0; u < 2; u++) {
          const int m = (k >> 1) - 4 * u;
          sts128(dt + (t >> 4) * 512 + u * 256 + n * 16, make_uint4(m == 0 ? dv : 0, m == 1 ? dv : 0, m == 2 ? dv : 0, m == 3 ? dv : 0));
        }
        fence_proxy_async_smem();
        bar_sync(2, 256);
        mbar_wait(bars + (B_FULL + XPOS % STAGES) * 8, (XPOS / STAGES) & 1);
        const uint64_t dx = make_desc(sb + OFF_RING + (XPOS % STAGES) * STAGE_BYTES, 16, 1024, 1), dd = make_desc(dt, 256, 128, 0);
        wg_fence();
#pragma unroll
        for (int u = 0; u < 16; u++) ss_n16(d + 8 * u, dx + ((u >> 2) & 1) * 1024 + (u >> 3) * 512 + (u & 3) * 2, dd + (u & 7) * 32);
        wg_commit();
        wg_wait<0>();
        rename_regs<128>(d);
        release(8 * (XPOS % STAGES));
        if (t == 0) mbar_arrive(bars + B_XI * 8);
      }
      so = 8 * (33 % STAGES); ph = (33 / STAGES) & 1; po = NOBAR;
      const uint64_t da0 = make_desc(sb + OFF_RING + 16384, 512, 1024, 2), db0 = make_desc(sb + OFF_RING, 16, 1024, 1);
#pragma unroll 1
      for (int kb = 0; kb < QSW; kb++) block(std::integral_constant<int, 1>(), da0, db0, false, 32 + kb);
#pragma unroll 1
      for (int kb = QSW; kb < 32 - TAILB; kb++) block(std::integral_constant<int, 2>(), da0, db0, false, 32 + kb);
      float* op = P.out + (size_t)trow * 2048 + 1024 + dcol;
      auto mma = [&](int i, int kb, int k0, int k1) {
        const int s = (33 + kb) % STAGES;
        wg_fence();
#pragma unroll
        for (int k = k0; k < k1; k++) wgmma_n128<1>(d + 64 * i, da0 + s * 2048 + 512 * i + 128 * k, db0 + (i ? 0 : P.zero) + s * 2048 + 2 * k, 1);
        wg_commit();
      };
      auto store = [&](int i, int J0, int J1) {
#pragma unroll
        for (int J = J0; J < J1; J++) {
#pragma unroll
          for (int h = 0; h < 2; h++) {
            const float* e = d + 64 * i + 8 * J + 2 * h;
            stg128(op + (size_t)(16 * i + 32 * h) * 2048 + 16 * J, make_uint4(__float_as_uint(e[0]), __float_as_uint(e[1]), __float_as_uint(e[4]), __float_as_uint(e[5])));
          }
        }
        PMFENCE();
      };
      constexpr int K0 = 32 - TAILB;
#pragma unroll
      for (int kb = K0; kb < 32; kb++) {
        mbar_wait(bars + (B_FULL + (33 + kb) % STAGES) * 8, ((33 + kb) / STAGES) & 1);
        if (TAILB == 5 && kb == K0) { mma(0, kb, 0, 2); wg_wait<1>(); release(po); mma(0, kb, 2, 4); }
        else mma(0, kb, 0, 4);
      }
      mma(1, K0, 0, 4);
      wg_wait<1>();
      fence_regs<64>(d);
#pragma unroll
      for (int kb = K0 + 1; kb < 32; kb++) {
        mma(1, kb, 0, 4);
        store(0, T_ST * (kb - K0 - 1), kb == 31 ? 8 : T_ST * (kb - K0));
      }
      wg_wait<0>();
      fence_regs<64>(d + 64);
      store(1, 0, 8);
      if (t == 0) g_epoch[b * 32] = lds32(bars + B_EPOCH * 8);
      return;
    }
    asm volatile("setmaxnreg.dec.sync.aligned.u32 %0;" ::"n"(488 - 2 * GREG));
    fin_setup();
#pragma unroll
    for (int n = 0; n < 4; n += 2) {
      get_q(n, OFF_Q, B_QF, n >> 1);
      uint32_t dep = P.zero;
#pragma unroll
      for (int r = 0; r < 8; r++) dep &= q[n + (r >> 2)][r & 3].x;
      bar_sync(6 + dep, 128);
      if (w < 2 && elect_one()) load_q(5 + 2 * w - (n >> 1), OFF_Q, B_QF + n);
      __syncwarp();
    }
#pragma unroll 1
    for (int r = 0; r < 6; r++) mbar_wait(bars + (B_IN + r) * 8, 0);
    bar_sync(9, 256);
  }
  {
    const int w = warp & 3, h = wg & 1, lane = fl;
    const uint32_t ob0 = sb + (h ? OFF_F1 : OFF_K) + 1024 * w, ob1 = sb + (h ? OFF_VP : OFF_K + 4096) + 1024 * w;
    uint32_t y[2][8];
    auto get_y = [&](int n) { ldsm4t(y[n & 1], fa + n * fs); ldsm4t(y[n & 1] + 4, fa + n * fs + 32); };
    mbar_wait(bars + B_HR * 8, 1);
    mbar_wait(bars + (B_IN + 6) * 8, 0);
    get_y(0);
#pragma unroll
    for (int n = 0; n < 4; n++) {
      uint32_t* o = y[n & 1];
#pragma unroll
      for (int r = 0; r < 4; r++) { o[2 * r] = bmul2(o[2 * r], q[n][r].x); o[2 * r + 1] = bmul2(o[2 * r + 1], q[n][r].y); }
      if (n > 0 && lane == 0) asm volatile("cp.async.bulk.wait_group.read 0;" ::: "memory");
      __syncwarp();
#pragma unroll
      for (int r = 0; r < 4; r++)
        sts128((r & 2 ? ob1 : ob0) + (r & 1) * 512 + lane * 16, make_uint4(o[2 * r] << 16, o[2 * r] & 0xffff0000u, o[2 * r + 1] << 16, o[2 * r + 1] & 0xffff0000u));
      fence_proxy_async_smem();
      __syncwarp();
      if (lane == 0) {
#pragma unroll
        for (int u = 0; u < 2; u++)
          asm volatile("cp.async.bulk.tensor.3d.global.shared::cta.bulk_group [%0, {%2, %3, %4}], [%1];"
                       ::"l"(&mO), "r"(u ? ob1 : ob0), "r"(32 * slot), "r"(32 * rank + 8 * w), "r"(8 * n + 4 * h + 2 * u) : "memory");
        asm volatile("cp.async.bulk.commit_group;" ::: "memory");
      }
      __syncwarp();
      if (n < 3) get_y(n + 1);
      if (n == 1 && !h) get_q(2, OFF_Q, B_QF + 2, 0);
    }
    if (warp == 8 && lane == 0) mbar_arrive_cta(bars + B_ACK * 8, rank ^ 1);
    if (lane == 0) asm volatile("cp.async.bulk.wait_group 0;" ::: "memory");
    mbar_wait(bars + B_ACK * 8, 0);
  }
}

typedef CUresult (*EncodeFn)(CUtensorMap*, CUtensorMapDataType, cuuint32_t, void*, const cuuint64_t*, const cuuint64_t*, const cuuint32_t*,
                             const cuuint32_t*, CUtensorMapInterleave, CUtensorMapSwizzle, CUtensorMapL2promotion, CUtensorMapFloatOOBfill);

bool encode(EncodeFn fn, CUtensorMap* m, int rank, const void* base, const cuuint64_t* dims, const cuuint64_t* strides, const cuuint32_t* box, CUtensorMapSwizzle swz,
            CUtensorMapL2promotion promo = CU_TENSOR_MAP_L2_PROMOTION_L2_128B) {
  const cuuint32_t es[5] = {1, 1, 1, 1, 1};
  return fn(m, CU_TENSOR_MAP_DATA_TYPE_BFLOAT16, rank, const_cast<void*>(base), dims, strides, box, es, CU_TENSOR_MAP_INTERLEAVE_NONE, swz,
            promo, CU_TENSOR_MAP_FLOAT_OOB_FILL_NONE) == CUDA_SUCCESS;
}

}

extern "C" void kernel_launch(void* const* d_in, const int* in_sizes, int n_in, void* d_out, int out_size) {
  (void)in_sizes; (void)n_in; (void)out_size;
  typedef const __nv_bfloat16* In;
  const In q = (In)d_in[0], k = (In)d_in[1], v = (In)d_in[2], ssm_k = (In)d_in[4], x = (In)d_in[6], B_re = (In)d_in[9], B_im = (In)d_in[10], C_re = (In)d_in[11], C_im = (In)d_in[12];
  Params P = {};
  P.shift_k = (In)d_in[3]; P.ssm_D = (In)d_in[5]; P.lam_re = (In)d_in[7]; P.lam_im = (In)d_in[8]; P.log_dt = (In)d_in[13]; P.Dskip = (In)d_in[14];
  P.out = (float*)d_out;
  for (int cl = 0; cl < 64; cl++) P.slot[cl >> 2] |= (cl < 4 ? 4 + cl : cl < 36 ? 8 * ((cl - 4) & 7) + ((cl - 4) >> 3) : 8 * (1 + (cl - 36) % 7) + 4 + (cl - 36) / 7) << (8 * (cl & 3));
  const bool swapB = (uintptr_t)B_im < (uintptr_t)B_re;

  EncodeFn fn = nullptr;
  cudaDriverEntryPointQueryResult qr;
  cudaGetDriverEntryPoint("cuTensorMapEncodeTiled", (void**)&fn, cudaEnableDefault, &qr);
  if (!fn) return;

  CUtensorMap mX, mB, mCre, mCim, mXs, mK, mV, mQ, mS, mO;
  bool ok = true;
  {
    const cuuint64_t dims[4] = {1024, 2, 64, 16}, str[3] = {2048, 32 * 2048, 2 * 2048};
    const cuuint32_t box[4] = {64, 2, 4, 16};
    ok &= encode(fn, &mX, 4, x, dims, str, box, CU_TENSOR_MAP_SWIZZLE_128B);
  }
  {
    const uintptr_t lo = swapB ? (uintptr_t)B_im : (uintptr_t)B_re, hi = swapB ? (uintptr_t)B_re : (uintptr_t)B_im;
    const cuuint64_t dims[4] = {1024, 8, 2, 128}, str[3] = {2048, (cuuint64_t)(hi - lo), 8 * 2048};
    const cuuint32_t box[4] = {64, 8, 2, 4};
    ok &= encode(fn, &mB, 4, (const void*)lo, dims, str, box, CU_TENSOR_MAP_SWIZZLE_128B);
  }
  {
    const cuuint64_t dims[5] = {1024, 2, 4, 2, 64}, str[4] = {2048, 4 * 2048, 2 * 2048, 16 * 2048};
    const cuuint32_t box[5] = {64, 2, 4, 2, 4};
    ok &= encode(fn, &mCre, 5, C_re, dims, str, box, CU_TENSOR_MAP_SWIZZLE_128B);
    ok &= encode(fn, &mCim, 5, C_im, dims, str, box, CU_TENSOR_MAP_SWIZZLE_128B);
  }
  {
    const cuuint64_t dims[4] = {1024, 8, 64, 4}, str[3] = {2048, 32 * 2048, 8 * 2048};
    const cuuint32_t box[4] = {64, 8, 4, 4};
    ok &= encode(fn, &mXs, 4, x, dims, str, box, CU_TENSOR_MAP_SWIZZLE_128B);
  }
  {
    const cuuint64_t dims[3] = {1024, 64, 32}, str[2] = {32 * 2048, 2048};
    const cuuint32_t box[3] = {16, 32, 4};
    const cuuint64_t dimq[4] = {1024, 8, 32, 8}, strq[3] = {32 * 2048, 2048, 256 * 2048};
    const cuuint32_t boxq[4] = {16, 8, 4, 4};
    ok &= encode(fn, &mQ, 4, q, dimq, strq, boxq, CU_TENSOR_MAP_SWIZZLE_NONE);
    ok &= encode(fn, &mK, 3, k, dims, str, box, CU_TENSOR_MAP_SWIZZLE_32B);
    ok &= encode(fn, &mV, 3, v, dims, str, box, CU_TENSOR_MAP_SWIZZLE_32B);
  }
  {
    const cuuint64_t dims[2] = {32, 65536}, str[1] = {64};
    const cuuint32_t box[2] = {32, 64};
    ok &= encode(fn, &mS, 2, ssm_k, dims, str, box, CU_TENSOR_MAP_SWIZZLE_64B);
  }
  {
    const cuuint64_t dims[3] = {2048, 64, 32}, str[2] = {32 * 8192, 8192};
    const cuuint32_t box[3] = {32, 8, 2};
    ok &= encode(fn, &mO, 3, d_out, dims, str, box, CU_TENSOR_MAP_SWIZZLE_NONE);
  }
  if (!ok) return;
  auto kern = swapB ? fused_kernel<1> : fused_kernel<0>;
  cudaFuncSetAttribute(kern, cudaFuncAttributeMaxDynamicSharedMemorySize, SMEM_BYTES);
  kern<<<NCTA, 512, SMEM_BYTES, cudaStreamPerThread>>>(P, mX, mB, mCre, mCim, mXs, mK, mV, mQ, mS, mO);
}
```

```cpp
#include <cuda_runtime.h>
#include <cuda_bf16.h>
#include <cuda.h>
#include <stdint.h>
#include <type_traits>

namespace {

constexpr int D_DIM = 1024;
constexpr int NCTA = 128;

constexpr int STAGES = 5, STAGE_BYTES = 32768;
constexpr int OFF_RING = 0;
constexpr int OFF_F1 = STAGES * STAGE_BYTES, OFF_F2 = OFF_F1 + 4096, OFF_K = OFF_F2 + 2048, OFF_VP = OFF_K + 8192, OFF_Q = OFF_VP + 4096, OFF_IN = OFF_Q + 8192;
constexpr int OFF_KV = OFF_K;
constexpr int U_CH = 528, U_N8 = 8 * U_CH, OFF_U = OFF_IN + U_N8;
constexpr int OFF_COEF = OFF_U + 8 * U_N8;
constexpr int OFF_DS = OFF_COEF + 2048, OFF_D = OFF_DS + 512;
constexpr int OFF_BAR = OFF_D + 64;
constexpr int SMEM_BYTES = OFF_BAR + 512;
static_assert(SMEM_BYTES <= 232448 && OFF_K % 1024 == 0 && (OFF_U + 3 * U_N8) % 512 == 0 && (4 * U_N8) % 512 == 0, "smem map");
constexpr int B_FULL = 0, B_XI = 5, B_HR = 6, B_HP = 7, B_KVF = 8, B_KF = 11, B_KE = 13, B_QF = 15, B_IN = 19, B_UF = 27, B_Y = 31, B_ACK = 36,
              B_EMPTY = 38, B_COEF = 43, B_KVE = 44, B_NONE = 47, B_EPOCH = 48;
constexpr int QD1 = 8;
constexpr int QD2 = 2;
constexpr int QD3 = 8;
constexpr int QSW = 16;
constexpr int HEAD = 3;
constexpr int ST_T0 = 200;
constexpr int ST_DELAY = 300;
constexpr int XPOS = 32;
constexpr int K_T0 = 800;
constexpr int KV_T0 = 1500;
constexpr int KV_DT = 620;
constexpr int KV_DV = 450;
constexpr int POLL_NS = 30;
constexpr int GREEDY = 1;
constexpr int TAILB = 5;
constexpr int GREG = 168;
constexpr int COEF_T0 = 2500;
constexpr int T_ST = 2;
constexpr int PFC_T0 = 13500;
constexpr int PFC_T1 = 1500;
constexpr int PFC_DT = 400;
constexpr int KV_E = 6;
constexpr int KV_D2 = 300;
constexpr int CFM = 0x40f1;
constexpr int SPIN_LIMIT = 1 << 14;

struct Params {
  unsigned slot[16];
  unsigned zero;
  const __nv_bfloat16 *shift_k, *ssm_D, *lam_re, *lam_im, *log_dt, *Dskip;
  float* out;
};

__device__ __align__(1024) uint4 g_h[16 * 32 * 1024];
__device__ __align__(128) uint2 g_carry[32 * 16 * 32];
__device__ unsigned g_flagH[2 * 16 * 32];
__device__ unsigned g_epoch[NCTA * 32];

__device__ __forceinline__ uint64_t make_desc(uint32_t addr, uint32_t lbo, uint32_t sbo, uint32_t swz) {
  return (uint64_t)((addr & 0x3FFFF) >> 4) | ((uint64_t)(lbo >> 4) << 16) | ((uint64_t)(sbo >> 4) << 32) | ((uint64_t)swz << 62);
}
__device__ __forceinline__ void wg_fence() { asm volatile("wgmma.fence.sync.aligned;" ::: "memory"); }
__device__ __forceinline__ void wg_commit() { asm volatile("wgmma.commit_group.sync.aligned;" ::: "memory"); }
template <int N> __device__ __forceinline__ void wg_wait() { asm volatile("wgmma.wait_group.sync.aligned %0;" ::"n"(N) : "memory"); }
__device__ __forceinline__ void mbar_init(uint32_t bar, int cnt) { asm volatile("mbarrier.init.shared::cta.b64 [%0], %1;" ::"r"(bar), "r"(cnt) : "memory"); }
__device__ __forceinline__ void mbar_expect(uint32_t bar, uint32_t bytes) { asm volatile("mbarrier.arrive.expect_tx.shared::cta.b64 _, [%0], %1;" ::"r"(bar), "r"(bytes) : "memory"); }
__device__ __forceinline__ bool mbar_try(uint32_t bar, uint32_t parity) {
  uint32_t ok;
  asm volatile("{\n.reg .pred p;\nmbarrier.try_wait.parity.shared::cta.b64 p, [%1], %2;\nselp.u32 %0, 1, 0, p;\n}\n" : "=r"(ok) : "r"(bar), "r"(parity) : "memory");
  return ok;
}
__device__ __forceinline__ void mbar_wait(uint32_t bar, uint32_t parity) {
  if (__builtin_expect(!mbar_try(bar, parity), 0)) {
#pragma unroll 1
    for (int n = 0; n < SPIN_LIMIT && !mbar_try(bar, parity); n++) {}
  }
}
__device__ __forceinline__ void mbar_arrive(uint32_t bar) { asm volatile("mbarrier.arrive.shared::cta.b64 _, [%0];" ::"r"(bar) : "memory"); }
__device__ __forceinline__ void mbar_arrive_cta(uint32_t bar, uint32_t cta) {
  asm volatile("{\n.reg .b32 ra;\nmapa.shared::cluster.u32 ra, %0, %1;\nmbarrier.arrive.shared::cluster.b64 _, [ra];\n}\n" ::"r"(bar), "r"(cta) : "memory");
}
__device__ __forceinline__ bool elect_one() {
  uint32_t p;
  asm volatile("{\n.reg .pred P;\nelect.sync _|P, 0xffffffff;\nselp.u32 %0, 1, 0, P;\n}\n" : "=r"(p));
  return p != 0;
}
__device__ __forceinline__ void bar_sync(int id, int n) { asm volatile("bar.sync %0, %1;" ::"r"(id), "r"(n) : "memory"); }
#define TMA_LD(dim) "cp.async.bulk.tensor." dim ".shared::cluster.global.mbarrier::complete_tx::bytes"
__device__ __forceinline__ void tma2d(uint32_t dst, const CUtensorMap* m, int c0, int c1, uint32_t bar) {
  asm volatile(TMA_LD("2d") " [%0], [%1, {%3, %4}], [%2];" ::"r"(dst), "l"(m), "r"(bar), "r"(c0), "r"(c1) : "memory");
}
__device__ __forceinline__ void tma3d(uint32_t dst, const CUtensorMap* m, int c0, int c1, int c2, uint32_t bar) {
  asm volatile(TMA_LD("3d") " [%0], [%1, {%3, %4, %5}], [%2];" ::"r"(dst), "l"(m), "r"(bar), "r"(c0), "r"(c1), "r"(c2) : "memory");
}
__device__ __forceinline__ void tma4d(uint32_t dst, const CUtensorMap* m, int c0, int c1, int c2, int c3, uint32_t bar) {
  asm volatile(TMA_LD("4d") " [%0], [%1, {%3, %4, %5, %6}], [%2];" ::"r"(dst), "l"(m), "r"(bar), "r"(c0), "r"(c1), "r"(c2), "r"(c3) : "memory");
}
__device__ __forceinline__ void tma4d_mc(uint32_t dst, const CUtensorMap* m, int c0, int c1, int c2, int c3, uint32_t bar) {
  asm volatile(TMA_LD("4d") ".multicast::cluster [%0], [%1, {%3, %4, %5, %6}], [%2], %7;" ::"r"(dst), "l"(m), "r"(bar), "r"(c0), "r"(c1), "r"(c2), "r"(c3), "h"((uint16_t)3) : "memory");
}
__device__ __forceinline__ void tma5d_mc(uint32_t dst, const CUtensorMap* m, int c0, int c1, int c2, int c3, int c4, uint32_t bar) {
  asm volatile(TMA_LD("5d") ".multicast::cluster [%0], [%1, {%3, %4, %5, %6, %7}], [%2], %8;" ::"r"(dst), "l"(m), "r"(bar), "r"(c0), "r"(c1), "r"(c2), "r"(c3), "r"(c4), "h"((uint16_t)3) : "memory");
}
__device__ __forceinline__ void bulk_load(uint32_t dst, const void* src, uint32_t bytes, uint32_t bar) {
  asm volatile("cp.async.bulk.shared::cluster.global.mbarrier::complete_tx::bytes [%0], [%1], %2, [%3];" ::"r"(dst), "l"(src), "r"(bytes), "r"(bar) : "memory");
}
__device__ __forceinline__ void bulk_send(uint32_t dst, uint32_t src, uint32_t bytes, uint32_t bar, uint32_t cta) {
  asm volatile("{\n.reg .b32 rd, rb;\nmapa.shared::cluster.u32 rd, %0, %3;\nmapa.shared::cluster.u32 rb, %2, %3;\n"
               "cp.async.bulk.shared::cluster.shared::cta.mbarrier::complete_tx::bytes [rd], [%1], %4, [rb];\n}\n"
               ::"r"(dst), "r"(src), "r"(bar), "r"(cta), "r"(bytes) : "memory");
}
__device__ __forceinline__ void fence_proxy_async_smem() { asm volatile("fence.proxy.async.shared::cta;" ::: "memory"); }
__device__ __forceinline__ void fence_proxy_async_global() { asm volatile("fence.proxy.async.global;" ::: "memory"); }
__device__ __forceinline__ uint32_t clk32() { uint32_t c; asm volatile("mov.u32 %0, %%clock;" : "=r"(c)::"memory"); return c; }
__device__ __forceinline__ void wait_until(uint32_t t0, uint32_t dt) { while (clk32() - t0 < dt) __nanosleep(32); }
__device__ __forceinline__ void spin_until(uint32_t t0, uint32_t dt) { while (clk32() - t0 < dt) {} }
__device__ __forceinline__ void prefetch_map(const CUtensorMap* m) { asm volatile("prefetch.tensormap [%0];" ::"l"(m) : "memory"); }
__device__ __forceinline__ void prefetch_line(const void* p) { asm volatile("prefetch.global.L2 [%0];" ::"l"(p) : "memory"); }
__device__ __forceinline__ unsigned ld_acquire(const unsigned* p) { unsigned v; asm volatile("ld.acquire.gpu.global.u32 %0, [%1];" : "=r"(v) : "l"(p) : "memory"); return v; }
__device__ __forceinline__ unsigned ld_relaxed(const unsigned* p) { unsigned v; asm volatile("ld.relaxed.gpu.global.u32 %0, [%1];" : "=r"(v) : "l"(p) : "memory"); return v; }
__device__ __forceinline__ uint32_t lds32(uint32_t a) { uint32_t v; asm volatile("ld.shared.u32 %0, [%1];" : "=r"(v) : "r"(a)); return v; }
__device__ __forceinline__ uint2 lds64(uint32_t a) { uint2 v; asm volatile("ld.shared.v2.u32 {%0,%1}, [%2];" : "=r"(v.x), "=r"(v.y) : "r"(a) : "memory"); return v; }
__device__ __forceinline__ uint4 lds128(uint32_t a) { uint4 v; asm volatile("ld.shared.v4.u32 {%0,%1,%2,%3}, [%4];" : "=r"(v.x), "=r"(v.y), "=r"(v.z), "=r"(v.w) : "r"(a) : "memory"); return v; }
__device__ __forceinline__ void sts32(uint32_t a, uint32_t v) { asm volatile("st.shared.u32 [%0], %1;" ::"r"(a), "r"(v) : "memory"); }
__device__ __forceinline__ void sts128(uint32_t a, uint4 v) { asm volatile("st.shared.v4.u32 [%0], {%1,%2,%3,%4};" ::"r"(a), "r"(v.x), "r"(v.y), "r"(v.z), "r"(v.w) : "memory"); }
__device__ __forceinline__ void ldsm4(uint32_t* r, uint32_t a) { asm volatile("ldmatrix.sync.aligned.m8n8.x4.shared.b16 {%0,%1,%2,%3}, [%4];" : "=r"(r[0]), "=r"(r[1]), "=r"(r[2]), "=r"(r[3]) : "r"(a) : "memory"); }
__device__ __forceinline__ void ldsm4t(uint32_t* r, uint32_t a) { asm volatile("ldmatrix.sync.aligned.m8n8.x4.trans.shared.b16 {%0,%1,%2,%3}, [%4];" : "=r"(r[0]), "=r"(r[1]), "=r"(r[2]), "=r"(r[3]) : "r"(a) : "memory"); }
__device__ __forceinline__ void stsm4t(uint32_t a, uint32_t r0, uint32_t r1, uint32_t r2, uint32_t r3) {
  asm volatile("stmatrix.sync.aligned.m8n8.x4.trans.shared.b16 [%0], {%1,%2,%3,%4};" ::"r"(a), "r"(r0), "r"(r1), "r"(r2), "r"(r3) : "memory");
}
__device__ __forceinline__ uint4 ldg128_nc(const void* p) { uint4 v; asm volatile("ld.global.nc.L1::no_allocate.v4.u32 {%0,%1,%2,%3}, [%4];" : "=r"(v.x), "=r"(v.y), "=r"(v.z), "=r"(v.w) : "l"(p)); return v; }
__device__ __forceinline__ void stg128(void* p, uint4 v) { asm volatile("st.global.L1::no_allocate.v4.u32 [%0], {%1,%2,%3,%4};" ::"l"(p), "r"(v.x), "r"(v.y), "r"(v.z), "r"(v.w) : "memory"); }
__device__ __forceinline__ uint32_t pack_bf16(float lo, float hi) { uint32_t r; asm("cvt.rn.bf16x2.f32 %0, %1, %2;" : "=r"(r) : "f"(hi), "f"(lo)); return r; }
__device__ __forceinline__ uint32_t bmul2(uint32_t a, uint32_t b) { uint32_t r; asm("mul.rn.bf16x2 %0, %1, %2;" : "=r"(r) : "r"(a), "r"(b)); return r; }
__device__ __forceinline__ uint32_t bfma2(uint32_t a, uint32_t b, uint32_t c) { uint32_t r; asm("fma.rn.bf16x2 %0, %1, %2, %3;" : "=r"(r) : "r"(a), "r"(b), "r"(c)); return r; }
__device__ __forceinline__ uint32_t blo2(uint32_t a) { uint32_t r; asm("{\n.reg .b16 l, h;\nmov.b32 {l, h}, %1;\nmov.b32 %0, {l, l};\n}" : "=r"(r) : "r"(a)); return r; }
__device__ __forceinline__ float bf2f(__nv_bfloat16 v) { return __bfloat162float(v); }

#define R8(d, o) "+f"(d[o]), "+f"(d[o + 1]), "+f"(d[o + 2]), "+f"(d[o + 3]), "+f"(d[o + 4]), "+f"(d[o + 5]), "+f"(d[o + 6]), "+f"(d[o + 7])
#define R16(d, o) R8(d, o), R8(d, o + 8)
#define R64(d, o) R16(d, o), R16(d, o + 16), R16(d, o + 32), R16(d, o + 48)
template <int TA> __device__ __forceinline__ void wgmma_n128(float* d, uint64_t da, uint64_t db, int scale_d) {
  asm volatile("{\n.reg .pred p;\nsetp.ne.b32 p, %66, 0;\n"
    "wgmma.mma_async.sync.aligned.m64n128k16.f32.bf16.bf16 {"
    "%0,%1,%2,%3,%4,%5,%6,%7,%8,%9,%10,%11,%12,%13,%14,%15,%16,%17,%18,%19,%20,%21,%22,%23,%24,%25,%26,%27,%28,%29,%30,%31,"
    "%32,%33,%34,%35,%36,%37,%38,%39,%40,%41,%42,%43,%44,%45,%46,%47,%48,%49,%50,%51,%52,%53,%54,%55,%56,%57,%58,%59,%60,%61,%62,%63"
    "}, %64, %65, p, 1, 1, %67, 0;\n}\n"
    : R64(d, 0)
    : "l"(da), "l"(db), "r"(scale_d), "n"(TA));
}
template <int N> __device__ __forceinline__ void fence_regs(float* d) {
#pragma unroll
  for (int i = 0; i < N; i++) asm volatile("" : "+f"(d[i])::"memory");
}
#define PMFENCE() asm volatile("pmevent 0;" ::: "memory")
__device__ __forceinline__ void cmul(float ar, float ai, float br, float bi, float& cr, float& ci) {
  cr = ar * br - ai * bi; ci = ar * bi + ai * br;
}
__device__ __forceinline__ void csq(float& r, float& i) { const float x = fmaf(r, r, -i * i), y = r * i; r = x; i = y + y; }

#define W8(d, o) "=f"(d[o]), "=f"(d[o + 1]), "=f"(d[o + 2]), "=f"(d[o + 3]), "=f"(d[o + 4]), "=f"(d[o + 5]), "=f"(d[o + 6]), "=f"(d[o + 7])
#define L16 "{%0,%1,%2,%3,%4,%5,%6,%7,%8,%9,%10,%11,%12,%13,%14,%15}"
#define L32 "{%0,%1,%2,%3,%4,%5,%6,%7,%8,%9,%10,%11,%12,%13,%14,%15,%16,%17,%18,%19,%20,%21,%22,%23,%24,%25,%26,%27,%28,%29,%30,%31}"
template <int ACC, int TB> __device__ __forceinline__ void rs_n32(float* d, const uint32_t* a, uint64_t db) {
  if constexpr (ACC) asm volatile("wgmma.mma_async.sync.aligned.m64n32k16.f32.bf16.bf16 " L16 ", {%16,%17,%18,%19}, %20, 1, 1, 1, %21;" : R16(d, 0) : "r"(a[0]), "r"(a[1]), "r"(a[2]), "r"(a[3]), "l"(db), "n"(TB));
  else asm volatile("wgmma.mma_async.sync.aligned.m64n32k16.f32.bf16.bf16 " L16 ", {%16,%17,%18,%19}, %20, 0, 1, 1, %21;" : W8(d, 0), W8(d, 8) : "r"(a[0]), "r"(a[1]), "r"(a[2]), "r"(a[3]), "l"(db), "n"(TB));
}
template <int ACC, int TB> __device__ __forceinline__ void rs_n64(float* d, const uint32_t* a, uint64_t db) {
  if constexpr (ACC) asm volatile("wgmma.mma_async.sync.aligned.m64n64k16.f32.bf16.bf16 " L32 ", {%32,%33,%34,%35}, %36, 1, 1, 1, %37;" : R16(d, 0), R16(d, 16) : "r"(a[0]), "r"(a[1]), "r"(a[2]), "r"(a[3]), "l"(db), "n"(TB));
  else asm volatile("wgmma.mma_async.sync.aligned.m64n64k16.f32.bf16.bf16 " L32 ", {%32,%33,%34,%35}, %36, 0, 1, 1, %37;" : W8(d, 0), W8(d, 8), W8(d, 16), W8(d, 24) : "r"(a[0]), "r"(a[1]), "r"(a[2]), "r"(a[3]), "l"(db), "n"(TB));
}
template <int ACC> __device__ __forceinline__ void ss_n32_tt(float* d, uint64_t da, uint64_t db) {
  if constexpr (ACC) asm volatile("wgmma.mma_async.sync.aligned.m64n32k16.f32.bf16.bf16 " L16 ", %16, %17, 1, 1, 1, 1, 1;" : R16(d, 0) : "l"(da), "l"(db));
  else asm volatile("wgmma.mma_async.sync.aligned.m64n32k16.f32.bf16.bf16 " L16 ", %16, %17, 0, 1, 1, 1, 1;" : W8(d, 0), W8(d, 8) : "l"(da), "l"(db));
}
__device__ __forceinline__ void stsm4(uint32_t a, uint32_t r0, uint32_t r1, uint32_t r2, uint32_t r3) {
  asm volatile("stmatrix.sync.aligned.m8n8.x4.shared.b16 [%0], {%1,%2,%3,%4};" ::"r"(a), "r"(r0), "r"(r1), "r"(r2), "r"(r3) : "memory");
}
template <int N> __device__ __forceinline__ void fence_u32(uint32_t* d) {
#pragma unroll
  for (int i = 0; i < N; i++) asm volatile("" : "+r"(d[i])::"memory");
}
__device__ __forceinline__ void pack32(uint32_t* f, const float* z) {
#pragma unroll
  for (int i = 0; i < 16; i++) f[i] = pack_bf16(z[2 * i], z[2 * i + 1]);
}
template <int INV> __device__ __forceinline__ void twiddle(uint32_t* f, const uint32_t* tp, const uint32_t* ts) {
#pragma unroll
  for (int i = 0; i < 8; i++) {
    uint32_t x = f[2 * i + INV], y = f[2 * i + 1 - INV];
    x = bfma2(tp[i & 3], y, x); y = bfma2(ts[i & 3], x, y); x = bfma2(tp[i & 3], y, x);
    f[2 * i + INV] = x; f[2 * i + 1 - INV] = y;
  }
}
__device__ __forceinline__ uint32_t bfnma2(uint32_t a, uint32_t b, uint32_t c) { uint32_t r; asm("{\n.reg .b32 t;\nmul.bf16x2 t, %1, %2;\nsub.bf16x2 %0, %3, t;\n}" : "=r"(r) : "r"(a), "r"(b), "r"(c)); return r; }
__device__ __forceinline__ uint32_t bfms2(uint32_t a, uint32_t b, uint32_t c) { uint32_t r; asm("{\n.reg .b32 t;\nmul.bf16x2 t, %1, %2;\nsub.bf16x2 %0, t, %3;\n}" : "=r"(r) : "r"(a), "r"(b), "r"(c)); return r; }
template <int ADD> __device__ __forceinline__ void bimac(uint32_t* o, const uint32_t* a, const uint32_t* b, const uint32_t* c) {
#pragma unroll
  for (int J = 0; J < 2; J++) {
    const uint32_t Pr = a[2 * J], Pi = a[2 * J + 1], Qr = a[2 * J + 4], Qi = a[2 * J + 5], pr = b[2 * J], pi = b[2 * J + 1], qr = b[2 * J + 4], qi = b[2 * J + 5];
    uint32_t x0, x1, x2, x3;
    if (ADD == 0) { x0 = bmul2(Pr, pr); x1 = bmul2(Pr, pi); x2 = bmul2(Pr, qr); x3 = bmul2(Pr, qi); }
    if (ADD == 1) { x0 = bfma2(Pr, pr, c[2 * J]); x1 = bfma2(Pr, pi, c[2 * J + 1]); x2 = bfma2(Pr, qr, c[2 * J + 4]); x3 = bfma2(Pr, qi, c[2 * J + 5]); }
    if (ADD == 2) { x0 = bfma2(Pr, pr, c[2 * J + 1]); x1 = bfms2(Pr, pi, c[2 * J]); x2 = bfma2(Pr, qr, c[2 * J + 5]); x3 = bfms2(Pr, qi, c[2 * J + 4]); }
    x0 = bfnma2(Pi, pi, x0); x1 = bfma2(Pi, pr, x1); x2 = bfnma2(Pi, qi, x2); x3 = bfma2(Pi, qr, x3);
    x0 = bfnma2(Qr, qr, x0); x1 = bfnma2(Qr, qi, x1); x2 = bfma2(Qr, pr, x2); x3 = bfma2(Qr, pi, x3);
    x0 = bfma2(Qi, qi, x0); x1 = bfnma2(Qi, qr, x1); x2 = bfnma2(Qi, pi, x2); x3 = bfma2(Qi, pr, x3);
    o[2 * J] = x0; o[2 * J + 1] = x1; o[2 * J + 4] = x2; o[2 * J + 5] = x3;
  }
}
__device__ __forceinline__ void sincos8k(int n, float& s, float& c) {
  const float x = (float)((n << 19) >> 19) * (6.283185307179586f / 8192.f);
  s = __sinf(x); c = __cosf(x);
}
__device__ __forceinline__ void fft_tables(uint32_t f1a, uint32_t f2a, int w, int lane, uint32_t* tp, uint32_t* ts, float& d0r, float& d0i) {
  const int c = lane & 3, f1 = 8 * w + (lane >> 2);
#pragma unroll 1
  for (int J = 3; J >= 0; J--) {
    const int a = 8 * J + 2 * c;
    float s0, c0, s1, c1;
    sincos8k(64 * (4 * f1 + 1) * a + 31 * (4 * f1 - 63), d0i, d0r); sincos8k(64 * (4 * f1 + 1) * (a + 1) + 31 * (4 * f1 - 63), s1, c1);
    d0r *= 0.125f; d0i *= 0.125f;
    sts32(f1a + w * 1024 + J * 128 + lane * 4, pack_bf16(d0r, 0.125f * c1)); sts32(f1a + w * 1024 + 512 + J * 128 + lane * 4, pack_bf16(d0i, 0.125f * s1));
    sincos8k(128 * (2 * (a & 15) + 1) * f1 - 128 * (a & 16), s0, c0); sincos8k(128 * (2 * (a & 15) + 3) * f1 - 128 * (a & 16), s1, c1);
    sts32(f2a + w * 512 + J * 128 + lane * 4, pack_bf16(c0, c1));
    sincos8k((4 * f1 - 63) * (2 * a - 31), s0, c0); sincos8k((4 * f1 - 63) * (2 * a - 29), s1, c1);
#pragma unroll
    for (int i = 3; i > 0; i--) { ts[i] = ts[i - 1]; tp[i] = tp[i - 1]; }
    ts[0] = pack_bf16(s0, s1); tp[0] = pack_bf16(-__fdividef(s0, 1.f + c0), -__fdividef(s1, 1.f + c1));
  }
  if (c != 0) d0r = d0i = 0.f;
}

__device__ __forceinline__ void ss_n16(float* d, uint64_t da, uint64_t db) {
  asm volatile("wgmma.mma_async.sync.aligned.m64n16k16.f32.bf16.bf16 {%0,%1,%2,%3,%4,%5,%6,%7}, %8, %9, 0, 1, 1, 0, 0;" : W8(d, 0) : "l"(da), "l"(db));
}
template <int N> __device__ __forceinline__ void rename_regs(float* d) {
#pragma unroll
  for (int i = 0; i < N; i++) { float t; asm volatile("mov.b32 %0, %1;" : "=f"(t) : "f"(d[i]) : "memory"); d[i] = t; }
}

template <int SWAPB>
__global__ void __cluster_dims__(2, 1, 1) __launch_bounds__(512, 1)
fused_kernel(const __grid_constant__ Params P, const __grid_constant__ CUtensorMap mX, const __grid_constant__ CUtensorMap mB,
             const __grid_constant__ CUtensorMap mCre, const __grid_constant__ CUtensorMap mCim, const __grid_constant__ CUtensorMap mXs,
             const __grid_constant__ CUtensorMap mK, const __grid_constant__ CUtensorMap mV, const __grid_constant__ CUtensorMap mQ, const __grid_constant__ CUtensorMap mS,
             const __grid_constant__ CUtensorMap mO) {
  extern __shared__ __align__(1024) uint8_t smem_raw[];
  if (threadIdx.x == 0) { prefetch_map(&mX); prefetch_map(&mB); }
  const uint32_t sb = (uint32_t)__cvta_generic_to_shared(smem_raw);
  const uint32_t bars = sb + OFF_BAR;
  const int slot = (P.slot[blockIdx.x >> 3] >> (4 * (blockIdx.x & 6))) & 63, rank = blockIdx.x & 1;
  const int j = slot & 7, tc = 2 * (slot >> 3) + rank, b = 2 * slot + rank;
  const int tid = threadIdx.x;
  const int warp = __shfl_sync(0xffffffffu, tid >> 5, 0);
  const int wg = warp >> 2;
  const uint32_t c_start = clk32();
  auto kblock = [&](int n) { return ((n & 14) == 0 || (n & 14) == 2 * j ? n ^ (2 * j) : n) & 31; };
  auto send_y = [&](int r) {
    const uint32_t src = sb + OFF_U + 4 * (rank ^ 1) * U_N8 + r * U_CH, dst = r >= 2 ? sb + OFF_U + 4 * rank * U_N8 + (r - 2) * U_CH : sb + OFF_IN + 96 + r * 2064;
#pragma unroll 1
    for (int n = 0; n < 4; n++) bulk_send(dst + n * (r >= 2 ? U_N8 : 512), src + n * U_N8, 512, bars + (B_IN + r) * 8, rank ^ 1);
  };
  auto load_q = [&](int i, int off, int bar) {
    const uint32_t fb = bars + bar * 8 + 4 * (i & 2);
    mbar_expect(fb, 4096); tma4d(sb + off + 2048 * (i & 2), &mQ, 16 * slot, 0, 4 * i, 4 * rank, fb);
  };
  auto head = [&](int n) {
    const uint32_t fb = bars + (B_FULL + n) * 8, dst = sb + OFF_RING + n * STAGE_BYTES;
    mbar_expect(fb, STAGE_BYTES);
    tma4d(dst + 16384, &mX, 64 * n, 0, 4 * tc, 0, fb);
    tma4d(dst, &mB, 64 * n, 0, 0, 8 * j, fb);
    tma4d(dst + 8192, &mB, 64 * n, 0, 0, 8 * j + 4, fb);
  };
  if (warp == 0 && elect_one()) {
#pragma unroll
    for (int s = 0; s < STAGES; s++) mbar_init(bars + (B_FULL + s) * 8, 1);
    head(0);
    asm volatile("fence.mbarrier_init.release.cluster;" ::: "memory");
  }
  if (wg == 3 && elect_one()) {
    if (warp < 15) {
#pragma unroll
      for (int s = 0; s < 11; s++) mbar_init(bars + 8 * B_XI + (warp & 3) * 88 + 8 * s, 1);
    } else {
#pragma unroll
      for (int s = B_EMPTY; s <= B_NONE; s++) mbar_init(bars + 8 * s, s < B_COEF ? 2 : s == B_COEF ? 128 : 4);
    }
    asm volatile("fence.mbarrier_init.release.cluster;" ::: "memory");
  }
  __syncwarp();
  asm volatile("barrier.cluster.arrive.relaxed.aligned;" ::: "memory");
  if (warp == 0 && elect_one()) {
#pragma unroll 1
    for (int n = 1; n < HEAD; n++) { spin_until(c_start, ST_T0 + n * ST_DELAY); head(n); }
  }
  __syncwarp();
  int fl;
  uint32_t fa, fs;
  uint2 q[4][4];
  auto fin_setup = [&]() {
    asm volatile("mov.u32 %0, %%laneid;" : "=r"(fl));
    const int lc = 2 * (fl & 2) + (fl & 1) + ((fl >> 2) & 2);
    const bool own = ((fl >> 2) & 1) == rank, spare = !own && lc < 2;
    fa = (spare ? sb + OFF_IN + 96 + lc * 2064 : sb + OFF_U + (own ? 4 * rank * U_N8 : 4 * (rank ^ 1) * U_N8 - 2 * U_CH) + lc * U_CH) + (warp & 3) * 128 + (fl >> 4) * 16 + (wg & 1) * 64;
    fs = spare ? 512 : U_N8;
  };
  auto get_q = [&](int n, int off, int bar, int ph) {
#pragma unroll
    for (int u = 0; u < 2; u++) {
      mbar_wait(bars + (bar + u) * 8, ph);
#pragma unroll
      for (int r = 0; r < 4; r++) q[n + u][r] = lds64(sb + off + 4096 * u + 1024 * (warp & 3) + 256 * r + 8 * fl);
    }
  };
#define CLUSTER_WAIT() asm volatile("barrier.cluster.wait.aligned;" ::: "memory")

  if (wg == 3) {
    asm volatile("setmaxnreg.dec.sync.aligned.u32 24;");
    CLUSTER_WAIT();
    if (warp < 14) {
      if (elect_one()) {
        uint32_t so = 8 * (HEAD % STAGES), ph = HEAD < STAGES;
        auto step = [&](auto issue) {
          mbar_wait(bars + B_EMPTY * 8 + so, ph);
          issue(sb + OFF_RING + (so << 12), bars + B_FULL * 8 + so);
          so += 8;
          if (so == 8 * STAGES) { so = 0; ph ^= 1; }
        };
        if (warp == 12) {
          auto g1 = [&](int n0, int n1, int grp) {
#pragma unroll 1
            for (int n = n0; n < n1; n++) step([&](uint32_t dst, uint32_t fb) { mbar_expect(fb, STAGE_BYTES); tma4d_mc(dst + rank * 8192, &mB, n * 64, 0, 0, grp + 4 * rank, fb); });
          };
#pragma unroll 1
          for (int n = HEAD; n < STAGES; n++) { spin_until(c_start, ST_T0 + n * ST_DELAY); g1(n, n + 1, 8 * j); }
          g1(STAGES, 16, 8 * j);
          g1(0, XPOS - 16, 8 * j + 64);
          step([&](uint32_t dst, uint32_t fb) { mbar_expect(fb, STAGE_BYTES); tma4d(dst, &mXs, 128 * j, 0, 4 * tc, 0, fb); });
#pragma unroll 1
          for (int n = 0; n < 32; n += 2) {
            const int col = kblock(n) * 32;
#pragma unroll
            for (int part = 0; part < 2; part++)
              step([&](uint32_t dst, uint32_t fb) { mbar_expect(fb, STAGE_BYTES); tma5d_mc(dst + rank * 8192, part ? &mCim : &mCre, col, 0, 0, 0, 8 * j + 4 * rank, fb); });
          }
        } else {
          auto g1 = [&](int n0, int n1, int nb) {
#pragma unroll 1
            for (int n = n0; n < n1; n++) step([&](uint32_t dst, uint32_t fb) { tma4d(dst + 16384, &mX, n * 64, 0, 4 * tc, 0, fb); });
          };
          auto g2 = [&](int n0, int n1) {
#pragma unroll 1
            for (int n = n0; n < n1; n++) step([&](uint32_t dst, uint32_t fb) { bulk_load(dst + 16384, g_h + (32 * tc + kblock(n)) * 1024, 16384, fb); });
          };
#pragma unroll 1
          for (int n = HEAD; n < STAGES; n++) { spin_until(c_start, ST_T0 + n * ST_DELAY); g1(n, n + 1, 0); }
          g1(STAGES, 16, 0);
          g1(0, XPOS - 16, 16);
          step([&](uint32_t dst, uint32_t fb) { tma4d(dst + 16384, &mXs, 128 * j + 64, 0, 4 * tc, 0, fb); });
#pragma unroll 1
          for (int v = 0; v < 2; v++) {
            mbar_wait(bars + B_HP * 8, v);
            fence_proxy_async_global();
            g2(16 * v, 16 * v + 2);
            mbar_wait(bars + B_HR * 8, v);
            fence_proxy_async_global();
            g2(16 * v + 2, 16 * v + 16);
          }
        }
      }
    } else if (warp == 15) {
      mbar_wait(bars + B_COEF * 8, 0);
      const unsigned epoch = lds32(bars + B_EPOCH * 8);
#pragma unroll 1
      for (int v = 0; v < 2; v++) {
        unsigned* fp = &g_flagH[(16 * v + tc) * 32];
        if (elect_one()) {
          wait_until(v ? clk32() : c_start, (v ? PFC_T1 : PFC_T0) + (slot >> 3) * PFC_DT);
#pragma unroll
          for (int part = 0; part < 2; part++)
            asm volatile("cp.async.bulk.prefetch.tensor.5d.L2.global [%0, {%1, %2, %2, %2, %3}];" ::"l"(part ? &mCim : &mCre), "r"(512 * v + 8 * (slot & 56)), "r"(0), "r"(8 * j + 4 * rank) : "memory");
        }
        __syncwarp();
        bar_sync(4 + v, 160);
        if (elect_one()) {
          asm volatile("red.release.gpu.global.add.u32 [%0], 1;" ::"l"(fp) : "memory");
          mbar_arrive(bars + B_HP * 8);
          int it = 0;
          while (ld_acquire(fp) != 8 * epoch && ++it < (SPIN_LIMIT << 4)) __nanosleep(POLL_NS);
          mbar_arrive(bars + B_HR * 8);
        }
        __syncwarp();
      }
    } else if (elect_one()) {
      const int ch0 = 16 * slot;
      auto load_k = [&](int s, uint32_t dst) { const uint32_t fb = bars + (B_KF + (s & 1)) * 8; mbar_expect(fb, 4096); tma2d(dst, &mS, 0, 64 * (8 * b + s), fb); };
      prefetch_map(&mS); prefetch_map(&mK); prefetch_map(&mV);
      wait_until(c_start, K_T0);
      load_k(0, sb + OFF_U + (4 * rank + 3) * U_N8); load_k(1, sb + OFF_U + (4 * rank + 3) * U_N8 - 4096);
      {
        uint32_t so = 16, ph = 1;
#pragma unroll 1
        for (int e = 0; e < 9; e++) {
          const uint32_t fb = bars + B_KVF * 8 + so, dst = sb + OFF_KV + (so << 10);
          wait_until(c_start, KV_T0 + (e ? 2 * e - 1 : 0) * KV_DT - (e > KV_E ? e - KV_E : 0) * 2 * (KV_DT - KV_D2));
          mbar_wait(bars + B_KVE * 8 + so, ph);
          const uint32_t c1 = clk32();
          mbar_expect(fb, e ? 8192 : 4096);
          tma3d(dst, &mK, ch0, 32 * rank - (e == 0), (4 * e - 4) & 31, fb);
          if (e > 0) { wait_until(c1, KV_DV); tma3d(dst + 4096, &mV, ch0, 32 * rank, 4 * e - 4, fb); }
          so += 8;
          if (so == 24) so = 0;
          if (so == 16) ph ^= 1;
        }
      }
      prefetch_map(&mCre); prefetch_map(&mCim); prefetch_map(&mXs); prefetch_map(&mQ); prefetch_map(&mO);
      mbar_wait(bars + B_KVE * 8, 0);
      load_k(2, sb + OFF_K); load_k(3, sb + OFF_K + 4096);
      mbar_wait(bars + (B_UF + 3) * 8, 0);
#pragma unroll 1
      for (int ch = 0; ch < 7; ch++) {
        if (ch > 0) {
          mbar_wait(bars + (B_Y + (ch & 3)) * 8, ch >> 2);
          if (ch > 2) mbar_wait(bars + (B_IN + ch - 3) * 8, 0);
          send_y(ch - 1);
        }
        if (ch < 6) {
          mbar_wait(bars + (B_KE + (ch & 1)) * 8, (ch >> 1) & 1);
          if (ch < 4) load_k(ch + 4, sb + OFF_K + (ch & 1) * 4096);
          if (ch == 3) asm volatile("cp.async.bulk.prefetch.tensor.4d.L2.global [%0, {%1, %2, %3, %4}];" ::"l"(&mQ), "r"(16 * (slot & ~3)), "r"(0), "r"(16 + 4 * (slot & 3)), "r"(4 * rank) : "memory");
          if (ch == 2) load_q(1, OFF_Q, B_QF);
          if (ch >= 4) load_q(2 * (ch & 1), OFF_K, B_KF);
          if (ch == 4) { mbar_wait(bars + B_XI * 8, 0); load_q(3, OFF_Q, B_QF); }
        }
      }
    }
    return;
  } else if (wg == 2) {
    asm volatile("setmaxnreg.inc.sync.aligned.u32 %0;" ::"n"(488 - 2 * GREG));
    const int t = tid & 127, w = warp & 3, lane = t & 31, g = lane >> 2, c = lane & 3;
    const uint4 s2[2] = {ldg128_nc(P.shift_k + (8 * b + 2 * c) * 4), ldg128_nc(P.shift_k + (8 * (b ^ 1) + 2 * c) * 4)};
    const uint32_t dskip = __bfloat16_as_ushort(P.ssm_D[8 * b + (t & 7)]);
    uint32_t tp[4] = {}, ts[4] = {};
    float d0r, d0i;
    fft_tables(sb + OFF_F1, sb + OFF_F2, w, lane, tp, ts, d0r, d0i);
    CLUSTER_WAIT();
    if (t < 12) mbar_expect(bars + (B_IN + t) * 8, t < 6 ? 2048 : t < 8 ? 4 * (U_CH + 512) : U_N8);
    if (t < 8) sts32(sb + OFF_D + 4 * t, dskip << 16);
    const uint64_t dF1b = make_desc(sb + OFF_F1, 512, 128, 0);
    const uint64_t dF2f = make_desc(sb + OFF_F2, 512, 128, 0), dF2i = make_desc(sb + OFF_F2, 128, 512, 0);
    uint32_t f1[8];
#pragma unroll
    for (int i = 0; i < 8; i++) f1[i] = lds32(sb + OFF_F1 + w * 1024 + (i & 1) * 512 + (i >> 1) * 128 + lane * 4);
    auto T1k = [&](float* z, uint64_t dk) { wg_fence(); rs_n64<0, 1>(z, f1, dk); rs_n64<1, 1>(z, f1 + 4, dk + 64); wg_commit(); };
    auto T1u = [&](float* z, uint64_t du) { wg_fence(); rs_n64<0, 0>(z, f1, du); rs_n64<1, 0>(z, f1 + 4, du + 16); wg_commit(); };
    auto T2 = [&](float* s, const uint32_t* f) {
      wg_fence();
      rs_n32<0, 1>(s, f, dF2f); rs_n32<0, 1>(s + 16, f + 8, dF2f); rs_n32<1, 1>(s, f + 4, dF2f + 64); rs_n32<1, 1>(s + 16, f + 12, dF2f + 64);
      wg_commit();
    };
    auto product = [&](uint32_t* pr, const uint32_t* kh, const uint32_t* uh) {
      bimac<0>(pr, kh, uh, pr); bimac<2>(pr + 8, kh + 8, uh, pr); bimac<1>(pr + 8, kh, uh + 8, pr + 8);
      fence_u32<16>(pr);
    };
    float zk[32] = {};
    uint32_t pr[16];
    {
      uint32_t kh0[16];
      {
        float z0[32], sk[32];
        uint32_t fk[16];
        const uint64_t dk = make_desc(sb + OFF_U + (4 * rank + 3) * U_N8, 2048, 512, 2);
        fence_proxy_async_smem();
        bar_sync(7, 128);
        mbar_wait(bars + B_KF * 8, 0);
        T1k(z0, dk);
        mbar_wait(bars + (B_KF + 1) * 8, 0);
        T1k(zk, dk - 256);
        wg_wait<0>(); fence_regs<32>(z0); fence_regs<32>(zk);
        const float dd = __uint_as_float(lds32(sb + OFF_D));
        z0[0] = fmaf(d0r, dd, z0[0]); z0[2] = fmaf(d0i, dd, z0[2]);
        pack32(fk, z0); twiddle<0>(fk, tp, ts); fence_u32<16>(fk);
        T2(sk, fk);
        wg_wait<0>(); fence_regs<32>(sk); fence_u32<16>(fk);
        pack32(kh0, sk); fence_u32<16>(kh0);
      }
      {
        uint32_t sk[2][4], kx[2][8];
#pragma unroll
        for (int o = 0; o < 2; o++) {
          sk[o][0] = __byte_perm(s2[o].x, s2[o].z, 0x5410); sk[o][1] = __byte_perm(s2[o].x, s2[o].z, 0x7632);
          sk[o][2] = __byte_perm(s2[o].y, s2[o].w, 0x5410); sk[o][3] = __byte_perm(s2[o].y, s2[o].w, 0x7632);
        }
        const uint32_t la = sb + OFF_KV + (lane >> 3) * 1024 + (8 * w + (lane & 7)) * 32 + ((rank ^ ((lane >> 2) & 1)) << 4);
        const uint32_t uo = (lane & 7) * U_CH + w * 128 + (lane >> 3) * 16;
        mbar_wait(bars + (B_KVF + 2) * 8, 0);
        ldsm4(kx[0], la + 16384); ldsm4(kx[1], (la ^ 16) + 16384);
        if (lane == 0) mbar_arrive(bars + (B_KVE + 2) * 8 + (kx[0][1] & kx[1][1] & P.zero));
        uint32_t so = 0, ph = 0;
#pragma unroll 1
        for (int n = 0; n < 4; n++) {
          const uint32_t own = sb + OFF_U + (4 * rank + n) * U_N8, box = n < 3 ? sb + OFF_U + (4 * (rank ^ 1) + n + 1) * U_N8 : sb + OFF_IN;
#pragma unroll
          for (int e = 0; e < 2; e++) {
            uint32_t vx[2][4];
            mbar_wait(bars + B_KVF * 8 + so, ph);
#pragma unroll
            for (int o = 0; o < 2; o++) { ldsm4(kx[o] + 4, (la ^ (16 * o)) + (so << 10)); ldsm4(vx[o], (la ^ (16 * o)) + (so << 10) + 4096); }
            if (lane == 0) mbar_arrive(bars + B_KVE * 8 + so + (kx[0][4] & kx[1][4] & vx[0][0] & vx[1][0] & P.zero));
#pragma unroll
            for (int o = 0; o < 2; o++) {
#pragma unroll
              for (int i = 0; i < 4; i++) vx[o][i] = bmul2(bfma2(kx[o][i + 4], sk[o][0], bfma2(kx[o][i + 3], sk[o][1], bfma2(kx[o][i + 2], sk[o][2], bmul2(kx[o][i + 1], sk[o][3])))), vx[o][i]);
              stsm4t((o ? box : own) + uo + e * 64, vx[o][0], vx[o][1], vx[o][2], vx[o][3]);
              kx[o][1] = kx[o][5]; kx[o][2] = kx[o][6]; kx[o][3] = kx[o][7];
            }
            so += 8;
            if (so == 24) so = 0;
            if (so == 16) ph ^= 1;
          }
          fence_proxy_async_smem();
          bar_sync(7, 128);
          if (w == 0 && elect_one()) {
            if (n > 0) mbar_wait(bars + B_UF * 8 + 8 * (n - 1), 0);
            bulk_send(own, box, U_N8, bars + B_UF * 8 + 8 * n, rank ^ 1);
          }
          __syncwarp();
        }
      }
      float zu[32], su[32];
      uint32_t fu[16], uh[16];
#pragma unroll
      for (int n = 0; n < 4; n++) mbar_wait(bars + (B_UF + n) * 8, 0);
      T1u(zu, make_desc(sb + OFF_U, 128, U_N8, 0));
      wg_wait<0>(); fence_regs<32>(zu);
      pack32(fu, zu); twiddle<0>(fu, tp, ts); fence_u32<16>(fu);
      T2(su, fu);
      wg_wait<0>(); fence_regs<32>(su); fence_u32<16>(fu);
      pack32(uh, su);
      product(pr, kh0, uh);
    }
    {
#define CF(i) do { if ((CFM >> (i)) & 1) PMFENCE(); } while (0)
      const uint32_t vs = w < 2 ? 512 : U_N8;
      uint32_t va = (w < 2 ? sb + OFF_VP : sb + OFF_U) + ((lane >> 4) & 1) * vs + (w & 1) * 256 + (lane & 15) * 16;
      uint32_t ya = sb + OFF_U + (2 * w + ((lane >> 3) & 1)) * U_N8 + (lane >> 4) * 128 + (lane & 7) * 16;
      uint64_t du = make_desc(sb + OFF_U, 128, U_N8, 0), dk = make_desc(sb + OFF_K, 2048, 512, 2);
      const uint64_t dv = make_desc(sb + OFF_VP, 128, 512, 0);
      uint32_t yp[8] = {};
      uint32_t yq = sb + OFF_Q + lane * 16;
      auto store_y = [&]() { stsm4(yq, yp[0], yp[1], yp[2], yp[3]); stsm4(yq + 256, yp[4], yp[5], yp[6], yp[7]); };
      auto step = [&](int ch, auto fwd) {
        constexpr bool FWD = decltype(fwd)::value;
        float zu[32], sk[32], su[32], v[32], y[16];
        uint32_t kh[16], uh[16], fk[16], fu[16], fv[16];
        wg_fence();
        rs_n32<0, 0>(v, pr, dF2i); rs_n32<0, 0>(v + 16, pr + 8, dF2i); rs_n32<1, 0>(v, pr + 4, dF2i + 16); rs_n32<1, 0>(v + 16, pr + 12, dF2i + 16);
        wg_commit();
        CF(0);
        store_y();
        if (FWD) {
          const float dd = __uint_as_float(lds32(sb + OFF_D + 4 * (ch + 1)));
          zk[0] = fmaf(d0r, dd, zk[0]); zk[2] = fmaf(d0i, dd, zk[2]);
          pack32(fk, zk); twiddle<0>(fk, tp, ts); fence_u32<16>(fk);
          T2(sk, fk);
          CF(2);
          mbar_wait(bars + (B_KF + (ch & 1)) * 8, ((ch >> 1) & 1) ^ 1);
          wg_wait<1>();
        } else {
#pragma unroll
          for (int r = 3; r < 6; r++) mbar_wait(bars + (B_IN + r) * 8, 0);
          wg_wait<0>();
        }
        fence_regs<32>(v); fence_u32<16>(pr);
        pack32(fv, v); fence_u32<16>(fv);
        CF(4);
        if (FWD) T1u(zu, du + U_CH / 16);
        CF(5);
        if (FWD) { wg_wait<1>(); fence_regs<32>(sk); fence_u32<16>(fk); pack32(kh, sk); }
        twiddle<1>(fv, tp, ts);
#pragma unroll
        for (int i = 0; i < 4; i++) stsm4(va + 2 * i * vs, fv[4 * i], fv[4 * i + 1], fv[4 * i + 2], fv[4 * i + 3]);
        if (FWD) {
          fence_u32<16>(kh);
          CF(7);
          T1k(zk, dk);
          CF(8);
          wg_wait<1>(); fence_regs<32>(zu);
          pack32(fu, zu); twiddle<0>(fu, tp, ts); fence_u32<16>(fu);
          T2(su, fu);
          CF(10);
        }
        fence_proxy_async_smem();
        bar_sync(7, 128);
        wg_fence();
        ss_n32_tt<0>(y, dv, dF1b); ss_n32_tt<1>(y, dv + 16, dF1b + 64); ss_n32_tt<1>(y, du, dF1b + 128); ss_n32_tt<1>(y, du + 16, dF1b + 192);
        wg_commit();
        if (FWD && t == 0) mbar_arrive(bars + (B_Y + (ch & 3)) * 8);
        CF(12);
        if (FWD) {
          wg_wait<1>(); fence_regs<32>(su); fence_u32<16>(fu); fence_regs<32>(zk);
          if (t == 0) mbar_arrive(bars + (B_KE + (ch & 1)) * 8);
          pack32(uh, su);
          bimac<0>(pr, kh, uh, pr); bimac<2>(pr + 8, kh + 8, uh, pr); fence_u32<16>(pr);
          CF(14);
          wg_wait<0>(); fence_regs<16>(y);
          bimac<1>(pr + 8, kh, uh + 8, pr + 8); fence_u32<8>(pr + 8);
          du += U_CH / 16; dk += (ch & 1) ? -256 : 256;
          if (w >= 2) va += U_CH;
        }
        if (!FWD) {
          PMFENCE();
          fin_setup(); get_q(0, OFF_K, B_KF, 0);
#pragma unroll
          for (int r = 0; r < 8; r++) q[2 + (r >> 2)][r & 3] = make_uint2(0, 0);
          wg_wait<0>(); fence_regs<16>(y);
        }
#pragma unroll
        for (int i = 0; i < 8; i++) yp[i] = pack_bf16(y[2 * i], y[2 * i + 1]);
        fence_u32<8>(yp);
        yq = ya;
        ya += U_CH;
      };
#pragma unroll 1
      for (int ch = 0; ch < 7; ch++) step(ch, std::true_type());
      step(7, std::false_type());
      store_y();
    }
    fence_proxy_async_smem();
    bar_sync(7, 128);
    if (elect_one()) bulk_send(sb + OFF_U + (4 * rank + w) * U_N8 + 4 * U_CH, sb + OFF_U + (4 * (rank ^ 1) + w) * U_N8 + 6 * U_CH, U_CH + 512, bars + (B_IN + 6) * 8, rank ^ 1);
    __syncwarp();
    asm volatile("bar.arrive 9, 256;" ::: "memory");
  } else {
    asm volatile("setmaxnreg.inc.sync.aligned.u32 %0;" ::"n"(GREG));
    const int t = tid & 127, w = warp & 3, lane = t & 31, g = lane >> 2, c = lane & 3;
    if (wg == 1) {
      wait_until(c_start, COEF_T0);
      const int p = 64 * j + (t & 63) + 8 * (t & 64);
      const float Lr = bf2f(P.lam_re[p]), Li = bf2f(P.lam_im[p]);
      const uint32_t ds = __bfloat16_as_ushort(P.Dskip[128 * j + t]);
      const unsigned epoch = ld_relaxed(&g_epoch[b * 32]) + 1;
      const float dt = bf2f(__float2bfloat16_rn(expf(bf2f(P.log_dt[p]))));
      const float e = expf(dt * Lr);
      float sn, cs;
      {
        const double z = (double)(dt * Li) * 0.15915494309189535;
        sincospif(2.f * (float)(z - rint(z)), &sn, &cs);
      }
      const float lr = e * cs, li = e * sn;
      const float nr = lr - 1.0f, ni = li;
      const bool big = fabsf(Lr) >= fabsf(Li);
      const float la = big ? Lr : Li, lb = big ? Li : Lr, r = __fdiv_rn(lb, la), inv = __frcp_rn(fmaf(lb, r, la));
      const float br = (big ? fmaf(ni, r, nr) : fmaf(nr, r, ni)) * inv, bi = (big ? fmaf(-nr, r, ni) : fmaf(ni, r, -nr)) * inv;
      sts128(sb + OFF_COEF + t * 16, make_uint4(__float_as_uint(lr), __float_as_uint(li), pack_bf16(2.f * br, 2.f * br), pack_bf16(-2.f * bi, -2.f * bi)));
      sts32(sb + OFF_DS + 4 * t, ds << 16);
      if (t == 0) sts32(bars + B_EPOCH * 8, epoch);
    }
    CLUSTER_WAIT();
    if (wg == 1) mbar_arrive(bars + B_COEF * 8);
    float d[128];
    uint32_t so = 0, ph = 0, po = 0;
    uint32_t ra;
    auto set_ra = [&]() { asm volatile("mapa.shared::cluster.u32 %0, %1, %2;" : "=r"(ra) : "r"(bars + B_EMPTY * 8), "r"((t & 1) ? rank ^ 1 : rank)); };
    set_ra();
    auto release = [&](uint32_t off) { if (t < 2) asm volatile("mbarrier.arrive.shared::cluster.b64 _, [%0];" ::"r"(ra + off) : "memory"); };
    constexpr uint32_t NOBAR = 8 * (B_NONE - B_EMPTY);
    auto block = [&](auto ta, uint64_t da0, uint64_t db0, bool zero, int nn) {
      constexpr int PH = decltype(ta)::value, TA = PH > 0, KS = TA ? 128 : 2, QD = PH == 0 ? QD1 : PH == 1 ? QD2 : QD3;
      mbar_wait(bars + B_FULL * 8 + so, ph);
      const uint64_t da = da0 + (so << 8), db = db0 + (so << 8);
      wg_fence();
      wgmma_n128<TA>(d, da, db, !zero);
      wgmma_n128<TA>(d + 64, da + 512, db, !zero);
      wg_commit();
      wg_wait<1>();
      release(po);
#pragma unroll
      for (int k = 1; k < 4; k++) {
        if (QD == 2 || (QD == 4 && k == 2)) wg_fence();
        wgmma_n128<TA>(d, da + KS * k, db + 2 * k, 1);
        wgmma_n128<TA>(d + 64, da + 512 + KS * k, db + 2 * k, 1);
        if (QD == 2 || (QD == 4 && k == 1)) wg_commit();
        if ((QD == 2 && k < 3) || (QD == 4 && k == 1)) wg_wait<1>();
      }
      if (QD != 2) wg_commit();
      po = so;
      so += 8;
      if (so == 8 * STAGES) { so = 0; ph ^= 1; }
    };
    {
      so = wg ? 8 * (16 % STAGES) : 0; ph = wg ? (16 / STAGES) & 1 : 0; po = NOBAR;
      const uint64_t da0 = make_desc(sb + OFF_RING, 16, 1024, 1), db0 = make_desc(sb + OFF_RING + 16384, 16, 1024, 1);
      if (wg == 1) bar_sync(1, 256);
#pragma unroll 1
      for (int kb = 0; kb < 16; kb++) {
        block(std::integral_constant<int, 0>(), da0, db0, kb == 0, 16 * wg + kb);
      }
      asm volatile("bar.arrive %0, 256;" ::"r"(1 + wg) : "memory");
    }
    mbar_wait(bars + B_COEF * 8, 0);
    const uint32_t ca = sb + OFF_COEF + (64 * wg + 8 * w + g) * 16;
    const uint32_t tag = __shfl_sync(0xffffffffu, lds32(bars + B_EPOCH * 8) & 3, 0);
    constexpr int RE = SWAPB ? 2 : 0, IM = 2 - RE;
    const int ct = lane >> 3;
    const uint2* cp = g_carry + __shfl_sync(0xffffffffu, ((16 * wg + 2 * j) * 16 + tc - 1 - ct) * 32 + 8 * w + (lane & 7), lane);
    unsigned long long cv[4];
    auto load_carry = [&](int i) {
#pragma unroll
      for (int m = 0; m < 4; m++)
        asm volatile("{\n.reg .pred p;\nsetp.lt.s32 p, %2, %3;\n@p ld.relaxed.gpu.global.b64 %0, [%1];\n}\n" : "=l"(cv[m]) : "l"(cp + 512 * i - 128 * m), "r"(ct + 4 * m), "r"(tc) : "memory");
    };
    float lr[2], li[2], pr[2], pi[2], wr[2], wi[2], vr[2], vi[2], qr[2], qi[2], gr[2], gi[2];
#pragma unroll
    for (int i = 0; i < 2; i++) {
      const uint2 cf = lds64(ca + 512 * i);
      pr[i] = lr[i] = __uint_as_float(cf.x); pi[i] = li[i] = __uint_as_float(cf.y);
#pragma unroll
      for (int s = 0; s < 4; s++) csq(pr[i], pi[i]);
      gr[i] = pr[i]; gi[i] = pi[i];
      csq(pr[i], pi[i]);
      qr[i] = pr[i]; qi[i] = pi[i];
      csq(qr[i], qi[i]);
      asm volatile("" : "+f"(pr[i]), "+f"(pi[i]), "+f"(qr[i]), "+f"(qi[i]));
    }
    PMFENCE();
    wg_wait<0>();
    fence_regs<128>(d);
    release(po);
#pragma unroll
    for (int i = 0; i < 2; i++) {
      float* e = d + 64 * i;
      auto chain = [&](int s0, int s1, float& sr, float& si) {
        sr = e[2 * s0 + RE]; si = e[2 * s0 + IM];
#pragma unroll
        for (int s = s0 + 1; s < s1; s++) {
          const int ia = 4 * (s >> 1) + (s & 1);
          const float nr = fmaf(-li[i], si, fmaf(lr[i], sr, e[ia + RE])), ni = fmaf(li[i], sr, fmaf(lr[i], si, e[ia + IM]));
          sr = nr; si = ni;
        }
      };
      float sr, si;
      if ((GREEDY >> i) & 1) {
        float ar, ai;
        chain(0, 16, ar, ai); chain(16, 32, sr, si);
        sr = fmaf(gr[i], ar, fmaf(-gi[i], ai, sr)); si = fmaf(gr[i], ai, fmaf(gi[i], ar, si));
      } else chain(0, 32, sr, si);
      if (i == 1) { asm volatile("pmevent 0;" : "+f"(sr), "+f"(si)::"memory"); load_carry(0); }
      float ur = __shfl_up_sync(0xffffffffu, sr, 1, 4), ui = __shfl_up_sync(0xffffffffu, si, 1, 4);
      if (c >= 1) { sr = fmaf(pr[i], ur, fmaf(-pi[i], ui, sr)); si = fmaf(pr[i], ui, fmaf(pi[i], ur, si)); }
      ur = __shfl_up_sync(0xffffffffu, sr, 2, 4); ui = __shfl_up_sync(0xffffffffu, si, 2, 4);
      if (c >= 2) { sr = fmaf(qr[i], ur, fmaf(-qi[i], ui, sr)); si = fmaf(qr[i], ui, fmaf(qi[i], ur, si)); }
      ur = __shfl_sync(0xffffffffu, sr, 4 * lane + 3); ui = __shfl_sync(0xffffffffu, si, 4 * lane + 3);
      asm volatile("{\n.reg .pred p;\n.reg .b64 v;\nsetp.lt.u32 p, %3, 8;\nmov.b64 v, {%1,%2};\n@p st.relaxed.gpu.global.b64 [%0], v;\n}\n"
                   ::"l"(cp + 512 * i + 32), "r"((__float_as_uint(ur) & ~3u) | tag), "r"(__float_as_uint(ui)), "r"(lane) : "memory");
      PMFENCE();
      ur = __shfl_up_sync(0xffffffffu, sr, 1, 4); ui = __shfl_up_sync(0xffffffffu, si, 1, 4);
      if (c >= 1) { e[RE] = fmaf(lr[i], ur, fmaf(-li[i], ui, e[RE])); e[IM] = fmaf(lr[i], ui, fmaf(li[i], ur, e[IM])); }
      asm volatile("" : "+f"(e[RE]), "+f"(e[IM]));
    }
#pragma unroll
    for (int i = 0; i < 2; i++) {
      wr[i] = (c & 1) ? pr[i] : 1.f; wi[i] = (c & 1) ? pi[i] : 0.f;
      if (c & 2) { float x, y; cmul(wr[i], wi[i], qr[i], qi[i], x, y); wr[i] = x; wi[i] = y; }
      vr[i] = wr[i]; vi[i] = wi[i];
      csq(vr[i], vi[i]); csq(vr[i], vi[i]);
      csq(qr[i], qi[i]); csq(qr[i], qi[i]); csq(qr[i], qi[i]);
      const int src = 4 * (lane & 7) + ct;
      vr[i] = __shfl_sync(0xffffffffu, vr[i], src); vi[i] = __shfl_sync(0xffffffffu, vi[i], src);
      qr[i] = __shfl_sync(0xffffffffu, qr[i], src); qi[i] = __shfl_sync(0xffffffffu, qi[i], src);
    }
    uint4* hp = g_h + (32 * tc + 16 * wg + 2 * j) * 1024 + 64 * w + 4 * g + (c ^ (g >> 1));
#pragma unroll
    for (int i = 0; i < 2; i++) {
      float* e = d + 64 * i;
      PMFENCE();
      auto ready = [&]() {
        uint32_t bad = 0;
#pragma unroll
        for (int m = 0; m < 4; m++) if (ct + 4 * m < tc) bad |= (uint32_t)cv[m] ^ tag;
        return __all_sync(0xffffffffu, (bad & 3) == 0);
      };
      if (!ready()) {
        int n = 0;
#pragma unroll 1
        do load_carry(i); while (!ready() && ++n <= (SPIN_LIMIT << 4));
      }
      float hr = 0.f, hi = 0.f;
#pragma unroll
      for (int m = 3; m >= 0; m--) {
        const float x = __uint_as_float((uint32_t)cv[m]), y = __uint_as_float((uint32_t)(cv[m] >> 32));
        const float nr = m == 3 ? x : fmaf(qr[i], hr, fmaf(-qi[i], hi, x)), ni = m == 3 ? y : fmaf(qr[i], hi, fmaf(qi[i], hr, y));
        if (ct + 4 * m < tc) { hr = nr; hi = ni; }
      }
      { float x, y; cmul(hr, hi, vr[i], vi[i], x, y); hr = x; hi = y; }
      const uint4 cf = lds128(ca + 512 * i);
      lr[i] = __uint_as_float(cf.x); li[i] = __uint_as_float(cf.y);
      const uint32_t gp = cf.z, gms = cf.w;
      hr += __shfl_xor_sync(0xffffffffu, hr, 8); hi += __shfl_xor_sync(0xffffffffu, hi, 8);
      hr = __shfl_sync(0xffffffffu, hr, g) + __shfl_sync(0xffffffffu, hr, g + 16); hi = __shfl_sync(0xffffffffu, hi, g) + __shfl_sync(0xffffffffu, hi, g + 16);
      float sr, si;
      cmul(wr[i], wi[i], hr, hi, sr, si);
#pragma unroll
      for (int i8 = 0; i8 < 4; i8++) {
        asm volatile("pmevent 0;" : "+f"(sr), "+f"(si)::"memory");
        if (i == 0 && i8 == 1) load_carry(1);
#pragma unroll
        for (int s = 8 * i8; s < 8 * i8 + 8; s++) {
          const int ia = 4 * (s >> 1) + (s & 1);
          const float nr = fmaf(-li[i], si, fmaf(lr[i], sr, e[ia + RE])), ni = fmaf(li[i], sr, fmaf(lr[i], si, e[ia + IM]));
          sr = nr; si = ni;
          e[ia + RE] = nr; e[ia + IM] = ni;
        }
        uint32_t hp0[4], hp1[4];
#pragma unroll
        for (int m = 0; m < 4; m++) {
          const float* f = e + 16 * i8 + 4 * m;
          const uint32_t x = pack_bf16(f[RE], f[RE + 1]), y = pack_bf16(f[IM], f[IM + 1]);
          hp0[m] = bfma2(gp, x, bmul2(gms, y)); hp1[m] = bfnma2(gp, y, bmul2(gms, x));
        }
        uint4* o = hp + 512 * (i8 >> 1) + 256 * i + 32 * (i8 & 1);
        stg128(o, make_uint4(hp0[0], hp0[1], hp0[2], hp0[3]));
        stg128(o + 1024, make_uint4(hp1[0], hp1[1], hp1[2], hp1[3]));
      }
    }
    const int trow = 128 * tc + 64 * (w & 1) + 8 * (w >> 1) + g;
    const int dcol = 128 * j + 4 * c;
    asm volatile("bar.arrive %0, 160;" ::"r"(4 + wg) : "memory");
    if (wg == 0) {
      set_ra();
      {
        const uint32_t dt = sb + OFF_Q + 4096;
        mbar_wait(bars + (B_UF + 3) * 8, 0);
        const int n = t & 15, k = 2 * (n & 6) + 2 * (n >> 3) + (n & 1);
        const uint32_t dv = lds32(sb + OFF_DS + (t & ~15) * 4 + 4 * k) >> (16 - 16 * (k & 1));
#pragma unroll
        for (int u = 0; u < 2; u++) {
          const int m = (k >> 1) - 4 * u;
          sts128(dt + (t >> 4) * 512 + u * 256 + n * 16, make_uint4(m == 0 ? dv : 0, m == 1 ? dv : 0, m == 2 ? dv : 0, m == 3 ? dv : 0));
        }
        fence_proxy_async_smem();
        bar_sync(2, 256);
        mbar_wait(bars + (B_FULL + XPOS % STAGES) * 8, (XPOS / STAGES) & 1);
        const uint64_t dx = make_desc(sb + OFF_RING + (XPOS % STAGES) * STAGE_BYTES, 16, 1024, 1), dd = make_desc(dt, 256, 128, 0);
        wg_fence();
#pragma unroll
        for (int u = 0; u < 16; u++) ss_n16(d + 8 * u, dx + ((u >> 2) & 1) * 1024 + (u >> 3) * 512 + (u & 3) * 2, dd + (u & 7) * 32);
        wg_commit();
        wg_wait<0>();
        rename_regs<128>(d);
        release(8 * (XPOS % STAGES));
        if (t == 0) mbar_arrive(bars + B_XI * 8);
      }
      so = 8 * (33 % STAGES); ph = (33 / STAGES) & 1; po = NOBAR;
      const uint64_t da0 = make_desc(sb + OFF_RING + 16384, 512, 1024, 2), db0 = make_desc(sb + OFF_RING, 16, 1024, 1);
#pragma unroll 1
      for (int kb = 0; kb < QSW; kb++) block(std::integral_constant<int, 1>(), da0, db0, false, 32 + kb);
#pragma unroll 1
      for (int kb = QSW; kb < 32 - TAILB; kb++) block(std::integral_constant<int, 2>(), da0, db0, false, 32 + kb);
      float* op = P.out + (size_t)trow * 2048 + 1024 + dcol;
      auto mma = [&](int i, int kb, int k0, int k1) {
        const int s = (33 + kb) % STAGES;
        wg_fence();
#pragma unroll
        for (int k = k0; k < k1; k++) wgmma_n128<1>(d + 64 * i, da0 + s * 2048 + 512 * i + 128 * k, db0 + (i ? 0 : P.zero) + s * 2048 + 2 * k, 1);
        wg_commit();
      };
      auto store = [&](int i, int J0, int J1) {
#pragma unroll
        for (int J = J0; J < J1; J++) {
#pragma unroll
          for (int h = 0; h < 2; h++) {
            const float* e = d + 64 * i + 8 * J + 2 * h;
            stg128(op + (size_t)(16 * i + 32 * h) * 2048 + 16 * J, make_uint4(__float_as_uint(e[0]), __float_as_uint(e[1]), __float_as_uint(e[4]), __float_as_uint(e[5])));
          }
        }
        PMFENCE();
      };
      constexpr int K0 = 32 - TAILB;
#pragma unroll
      for (int kb = K0; kb < 32; kb++) {
        mbar_wait(bars + (B_FULL + (33 + kb) % STAGES) * 8, ((33 + kb) / STAGES) & 1);
        if (TAILB == 5 && kb == K0) { mma(0, kb, 0, 2); wg_wait<1>(); release(po); mma(0, kb, 2, 4); }
        else mma(0, kb, 0, 4);
      }
      mma(1, K0, 0, 4);
      wg_wait<1>();
      fence_regs<64>(d);
#pragma unroll
      for (int kb = K0 + 1; kb < 32; kb++) {
        mma(1, kb, 0, 4);
        store(0, T_ST * (kb - K0 - 1), kb == 31 ? 8 : T_ST * (kb - K0));
      }
      wg_wait<0>();
      fence_regs<64>(d + 64);
      store(1, 0, 8);
      if (t == 0) g_epoch[b * 32] = lds32(bars + B_EPOCH * 8);
      return;
    }
    asm volatile("setmaxnreg.dec.sync.aligned.u32 %0;" ::"n"(488 - 2 * GREG));
    fin_setup();
#pragma unroll
    for (int n = 0; n < 4; n += 2) {
      get_q(n, OFF_Q, B_QF, n >> 1);
      uint32_t dep = P.zero;
#pragma unroll
      for (int r = 0; r < 8; r++) dep &= q[n + (r >> 2)][r & 3].x;
      bar_sync(6 + dep, 128);
      if (w < 2 && elect_one()) load_q(5 + 2 * w - (n >> 1), OFF_Q, B_QF + n);
      __syncwarp();
    }
#pragma unroll 1
    for (int r = 0; r < 6; r++) mbar_wait(bars + (B_IN + r) * 8, 0);
    bar_sync(9, 256);
  }
  {
    const int w = warp & 3, h = wg & 1, lane = fl;
    const uint32_t ob0 = sb + (h ? OFF_F1 : OFF_K) + 1024 * w, ob1 = sb + (h ? OFF_VP : OFF_K + 4096) + 1024 * w;
    uint32_t y[2][8];
    auto get_y = [&](int n) { ldsm4t(y[n & 1], fa + n * fs); ldsm4t(y[n & 1] + 4, fa + n * fs + 32); };
    mbar_wait(bars + B_HR * 8, 1);
    mbar_wait(bars + (B_IN + 6) * 8, 0);
    get_y(0);
#pragma unroll
    for (int n = 0; n < 4; n++) {
      uint32_t* o = y[n & 1];
#pragma unroll
      for (int r = 0; r < 4; r++) { o[2 * r] = bmul2(o[2 * r], q[n][r].x); o[2 * r + 1] = bmul2(o[2 * r + 1], q[n][r].y); }
      if (n > 0 && lane == 0) asm volatile("cp.async.bulk.wait_group.read 0;" ::: "memory");
      __syncwarp();
#pragma unroll
      for (int r = 0; r < 4; r++)
        sts128((r & 2 ? ob1 : ob0) + (r & 1) * 512 + lane * 16, make_uint4(o[2 * r] << 16, o[2 * r] & 0xffff0000u, o[2 * r + 1] << 16, o[2 * r + 1] & 0xffff0000u));
      fence_proxy_async_smem();
      __syncwarp();
      if (lane == 0) {
#pragma unroll
        for (int u = 0; u < 2; u++)
          asm volatile("cp.async.bulk.tensor.3d.global.shared::cta.bulk_group [%0, {%2, %3, %4}], [%1];"
                       ::"l"(&mO), "r"(u ? ob1 : ob0), "r"(32 * slot), "r"(32 * rank + 8 * w), "r"(8 * n + 4 * h + 2 * u) : "memory");
        asm volatile("cp.async.bulk.commit_group;" ::: "memory");
      }
      __syncwarp();
      if (n < 3) get_y(n + 1);
      if (n == 1 && !h) get_q(2, OFF_Q, B_QF + 2, 0);
    }
    if (warp == 8 && lane == 0) mbar_arrive_cta(bars + B_ACK * 8, rank ^ 1);
    if (lane == 0) asm volatile("cp.async.bulk.wait_group 0;" ::: "memory");
    mbar_wait(bars + B_ACK * 8, 0);
  }
}

typedef CUresult (*EncodeFn)(CUtensorMap*, CUtensorMapDataType, cuuint32_t, void*, const cuuint64_t*, const cuuint64_t*, const cuuint32_t*,
                             const cuuint32_t*, CUtensorMapInterleave, CUtensorMapSwizzle, CUtensorMapL2promotion, CUtensorMapFloatOOBfill);

bool encode(EncodeFn fn, CUtensorMap* m, int rank, const void* base, const cuuint64_t* dims, const cuuint64_t* strides, const cuuint32_t* box, CUtensorMapSwizzle swz,
            CUtensorMapL2promotion promo = CU_TENSOR_MAP_L2_PROMOTION_L2_128B) {
  const cuuint32_t es[5] = {1, 1, 1, 1, 1};
  return fn(m, CU_TENSOR_MAP_DATA_TYPE_BFLOAT16, rank, const_cast<void*>(base), dims, strides, box, es, CU_TENSOR_MAP_INTERLEAVE_NONE, swz,
            promo, CU_TENSOR_MAP_FLOAT_OOB_FILL_NONE) == CUDA_SUCCESS;
}

}

extern "C" void kernel_launch(void* const* d_in, const int* in_sizes, int n_in, void* d_out, int out_size) {
  (void)in_sizes; (void)n_in; (void)out_size;
  typedef const __nv_bfloat16* In;
  const In q = (In)d_in[0], k = (In)d_in[1], v = (In)d_in[2], ssm_k = (In)d_in[4], x = (In)d_in[6], B_re = (In)d_in[9], B_im = (In)d_in[10], C_re = (In)d_in[11], C_im = (In)d_in[12];
  Params P = {};
  P.shift_k = (In)d_in[3]; P.ssm_D = (In)d_in[5]; P.lam_re = (In)d_in[7]; P.lam_im = (In)d_in[8]; P.log_dt = (In)d_in[13]; P.Dskip = (In)d_in[14];
  P.out = (float*)d_out;
  for (int cl = 0; cl < 64; cl++) P.slot[cl >> 2] |= (cl < 4 ? 4 + cl : cl < 36 ? 8 * ((cl - 4) & 7) + ((cl - 4) >> 3) : 8 * (1 + (cl - 36) % 7) + 4 + (cl - 36) / 7) << (8 * (cl & 3));
  const bool swapB = (uintptr_t)B_im < (uintptr_t)B_re;

  EncodeFn fn = nullptr;
  cudaDriverEntryPointQueryResult qr;
  cudaGetDriverEntryPoint("cuTensorMapEncodeTiled", (void**)&fn, cudaEnableDefault, &qr);
  if (!fn) return;

  CUtensorMap mX, mB, mCre, mCim, mXs, mK, mV, mQ, mS, mO;
  bool ok = true;
  {
    const cuuint64_t dims[4] = {1024, 2, 64, 16}, str[3] = {2048, 32 * 2048, 2 * 2048};
    const cuuint32_t box[4] = {64, 2, 4, 16};
    ok &= encode(fn, &mX, 4, x, dims, str, box, CU_TENSOR_MAP_SWIZZLE_128B);
  }
  {
    const uintptr_t lo = swapB ? (uintptr_t)B_im : (uintptr_t)B_re, hi = swapB ? (uintptr_t)B_re : (uintptr_t)B_im;
    const cuuint64_t dims[4] = {1024, 8, 2, 128}, str[3] = {2048, (cuuint64_t)(hi - lo), 8 * 2048};
    const cuuint32_t box[4] = {64, 8, 2, 4};
    ok &= encode(fn, &mB, 4, (const void*)lo, dims, str, box, CU_TENSOR_MAP_SWIZZLE_128B);
  }
  {
    const cuuint64_t dims[5] = {1024, 2, 4, 2, 64}, str[4] = {2048, 4 * 2048, 2 * 2048, 16 * 2048};
    const cuuint32_t box[5] = {64, 2, 4, 2, 4};
    ok &= encode(fn, &mCre, 5, C_re, dims, str, box, CU_TENSOR_MAP_SWIZZLE_128B);
    ok &= encode(fn, &mCim, 5, C_im, dims, str, box, CU_TENSOR_MAP_SWIZZLE_128B);
  }
  {
    const cuuint64_t dims[4] = {1024, 8, 64, 4}, str[3] = {2048, 32 * 2048, 8 * 2048};
    const cuuint32_t box[4] = {64, 8, 4, 4};
    ok &= encode(fn, &mXs, 4, x, dims, str, box, CU_TENSOR_MAP_SWIZZLE_128B);
  }
  {
    const cuuint64_t dims[3] = {1024, 64, 32}, str[2] = {32 * 2048, 2048};
    const cuuint32_t box[3] = {16, 32, 4};
    const cuuint64_t dimq[4] = {1024, 8, 32, 8}, strq[3] = {32 * 2048, 2048, 256 * 2048};
    const cuuint32_t boxq[4] = {16, 8, 4, 4};
    ok &= encode(fn, &mQ, 4, q, dimq, strq, boxq, CU_TENSOR_MAP_SWIZZLE_NONE);
    ok &= encode(fn, &mK, 3, k, dims, str, box, CU_TENSOR_MAP_SWIZZLE_32B);
    ok &= encode(fn, &mV, 3, v, dims, str, box, CU_TENSOR_MAP_SWIZZLE_32B);
  }
  {
    const cuuint64_t dims[2] = {32, 65536}, str[1] = {64};
    const cuuint32_t box[2] = {32, 64};
    ok &= encode(fn, &mS, 2, ssm_k, dims, str, box, CU_TENSOR_MAP_SWIZZLE_64B);
  }
  {
    const cuuint64_t dims[3] = {2048, 64, 32}, str[2] = {32 * 8192, 8192};
    const cuuint32_t box[3] = {32, 8, 2};
    ok &= encode(fn, &mO, 3, d_out, dims, str, box, CU_TENSOR_MAP_SWIZZLE_NONE);
  }
  if (!ok) return;
  auto kern = swapB ? fused_kernel<1> : fused_kernel<0>;
  cudaFuncSetAttribute(kern, cudaFuncAttributeMaxDynamicSharedMemorySize, SMEM_BYTES);
  kern<<<NCTA, 512, SMEM_BYTES, cudaStreamPerThread>>>(P, mX, mB, mCre, mCim, mXs, mK, mV, mQ, mS, mO);
}
```

```cpp
#include <cuda_runtime.h>
#include <cuda_bf16.h>
#include <cuda.h>
#include <stdint.h>
#include <type_traits>

namespace {

constexpr int D_DIM = 1024;
constexpr int NCTA = 128;

constexpr int STAGES = 5, STAGE_BYTES = 32768;
constexpr int OFF_RING = 0;
constexpr int OFF_F1 = STAGES * STAGE_BYTES, OFF_F2 = OFF_F1 + 4096, OFF_K = OFF_F2 + 2048, OFF_VP = OFF_K + 8192, OFF_Q = OFF_VP + 4096, OFF_IN = OFF_Q + 8192;
constexpr int OFF_KV = OFF_K;
constexpr int U_CH = 528, U_N8 = 8 * U_CH, OFF_U = OFF_IN + U_N8;
constexpr int OFF_COEF = OFF_U + 8 * U_N8;
constexpr int OFF_DS = OFF_COEF + 2048, OFF_D = OFF_DS + 512;
constexpr int OFF_BAR = OFF_D + 64;
constexpr int SMEM_BYTES = OFF_BAR + 512;
static_assert(SMEM_BYTES <= 232448 && OFF_K % 1024 == 0 && (OFF_U + 3 * U_N8) % 512 == 0 && (4 * U_N8) % 512 == 0, "smem map");
constexpr int B_FULL = 0, B_XI = 5, B_HR = 6, B_HP = 7, B_KVF = 8, B_QF = 11, B_IN = 15, B_UF = 23, B_ACK = 27, B_KF = 28, B_ST = 38,
              B_EMPTY = 45, B_COEF = 50, B_KVE = 51, B_NONE = 54, B_EPOCH = 55;

constexpr int QD1 = 8;
constexpr int QD2 = 2;
constexpr int QD3 = 8;
constexpr int QSW = 16;
constexpr int HEAD = 3;
constexpr int ST_T0 = 200;
constexpr int ST_DELAY = 300;
constexpr int XPOS = 32;
constexpr int K_T0 = 800;
constexpr int KV_T0 = 1500;
constexpr int KV_DT = 620;
constexpr int KV_DV = 450;
constexpr int POLL_NS = 30;
constexpr int GREEDY = 1;
constexpr int TAILB = 5;
constexpr int GREG = 168;
constexpr int COEF_T0 = 2500;
constexpr int T_ST = 2;
constexpr int PFC_T0 = 13500;
constexpr int PFC_T1 = 1500;
constexpr int PFC_DT = 400;
constexpr int KV_E = 6;
constexpr int KV_D2 = 300;
constexpr int CFM = 0x40f1;
constexpr int SPIN_LIMIT = 1 << 14;

struct Params {
  unsigned slot[16];
  unsigned zero;
  const __nv_bfloat16 *shift_k, *ssm_D, *lam_re, *lam_im, *log_dt, *Dskip;
  float* out;
};

__device__ __align__(1024) uint4 g_h[16 * 32 * 1024];
__device__ __align__(128) uint2 g_carry[32 * 16 * 32];
__device__ unsigned g_flagH[2 * 16 * 32];
__device__ unsigned g_epoch[NCTA * 32];

__device__ __forceinline__ uint64_t make_desc(uint32_t addr, uint32_t lbo, uint32_t sbo, uint32_t swz) {
  return (uint64_t)((addr & 0x3FFFF) >> 4) | ((uint64_t)(lbo >> 4) << 16) | ((uint64_t)(sbo >> 4) << 32) | ((uint64_t)swz << 62);
}
__device__ __forceinline__ void wg_fence() { asm volatile("wgmma.fence.sync.aligned;" ::: "memory"); }
__device__ __forceinline__ void wg_commit() { asm volatile("wgmma.commit_group.sync.aligned;" ::: "memory"); }
template <int N> __device__ __forceinline__ void wg_wait() { asm volatile("wgmma.wait_group.sync.aligned %0;" ::"n"(N) : "memory"); }
__device__ __forceinline__ void mbar_init(uint32_t bar, int cnt) { asm volatile("mbarrier.init.shared::cta.b64 [%0], %1;" ::"r"(bar), "r"(cnt) : "memory"); }
__device__ __forceinline__ void mbar_expect(uint32_t bar, uint32_t bytes) { asm volatile("mbarrier.arrive.expect_tx.shared::cta.b64 _, [%0], %1;" ::"r"(bar), "r"(bytes) : "memory"); }
__device__ __forceinline__ bool mbar_try(uint32_t bar, uint32_t parity) {
  uint32_t ok;
  asm volatile("{\n.reg .pred p;\nmbarrier.try_wait.parity.shared::cta.b64 p, [%1], %2;\nselp.u32 %0, 1, 0, p;\n}\n" : "=r"(ok) : "r"(bar), "r"(parity) : "memory");
  return ok;
}
__device__ __forceinline__ void mbar_wait(uint32_t bar, uint32_t parity) {
  if (__builtin_expect(!mbar_try(bar, parity), 0)) {
#pragma unroll 1
    for (int n = 0; n < SPIN_LIMIT && !mbar_try(bar, parity); n++) {}
  }
}
__device__ __forceinline__ void mbar_arrive(uint32_t bar) { asm volatile("mbarrier.arrive.shared::cta.b64 _, [%0];" ::"r"(bar) : "memory"); }
__device__ __forceinline__ void mbar_arrive_cta(uint32_t bar, uint32_t cta) {
  asm volatile("{\n.reg .b32 ra;\nmapa.shared::cluster.u32 ra, %0, %1;\nmbarrier.arrive.shared::cluster.b64 _, [ra];\n}\n" ::"r"(bar), "r"(cta) : "memory");
}
__device__ __forceinline__ bool elect_one() {
  uint32_t p;
  asm volatile("{\n.reg .pred P;\nelect.sync _|P, 0xffffffff;\nselp.u32 %0, 1, 0, P;\n}\n" : "=r"(p));
  return p != 0;
}
__device__ __forceinline__ void bar_sync(int id, int n) { asm volatile("bar.sync %0, %1;" ::"r"(id), "r"(n) : "memory"); }
#define TMA_LD(dim) "cp.async.bulk.tensor." dim ".shared::cluster.global.mbarrier::complete_tx::bytes"
__device__ __forceinline__ void tma2d(uint32_t dst, const CUtensorMap* m, int c0, int c1, uint32_t bar) {
  asm volatile(TMA_LD("2d") " [%0], [%1, {%3, %4}], [%2];" ::"r"(dst), "l"(m), "r"(bar), "r"(c0), "r"(c1) : "memory");
}
__device__ __forceinline__ void tma3d(uint32_t dst, const CUtensorMap* m, int c0, int c1, int c2, uint32_t bar) {
  asm volatile(TMA_LD("3d") " [%0], [%1, {%3, %4, %5}], [%2];" ::"r"(dst), "l"(m), "r"(bar), "r"(c0), "r"(c1), "r"(c2) : "memory");
}
__device__ __forceinline__ void tma4d(uint32_t dst, const CUtensorMap* m, int c0, int c1, int c2, int c3, uint32_t bar) {
  asm volatile(TMA_LD("4d") " [%0], [%1, {%3, %4, %5, %6}], [%2];" ::"r"(dst), "l"(m), "r"(bar), "r"(c0), "r"(c1), "r"(c2), "r"(c3) : "memory");
}
__device__ __forceinline__ void tma4d_mc(uint32_t dst, const CUtensorMap* m, int c0, int c1, int c2, int c3, uint32_t bar) {
  asm volatile(TMA_LD("4d") ".multicast::cluster [%0], [%1, {%3, %4, %5, %6}], [%2], %7;" ::"r"(dst), "l"(m), "r"(bar), "r"(c0), "r"(c1), "r"(c2), "r"(c3), "h"((uint16_t)3) : "memory");
}
__device__ __forceinline__ void tma5d_mc(uint32_t dst, const CUtensorMap* m, int c0, int c1, int c2, int c3, int c4, uint32_t bar) {
  asm volatile(TMA_LD("5d") ".multicast::cluster [%0], [%1, {%3, %4, %5, %6, %7}], [%2], %8;" ::"r"(dst), "l"(m), "r"(bar), "r"(c0), "r"(c1), "r"(c2), "r"(c3), "r"(c4), "h"((uint16_t)3) : "memory");
}
__device__ __forceinline__ void bulk_load(uint32_t dst, const void* src, uint32_t bytes, uint32_t bar) {
  asm volatile("cp.async.bulk.shared::cluster.global.mbarrier::complete_tx::bytes [%0], [%1], %2, [%3];" ::"r"(dst), "l"(src), "r"(bytes), "r"(bar) : "memory");
}
__device__ __forceinline__ void bulk_send(uint32_t dst, uint32_t src, uint32_t bytes, uint32_t bar, uint32_t cta) {
  asm volatile("{\n.reg .b32 rd, rb;\nmapa.shared::cluster.u32 rd, %0, %3;\nmapa.shared::cluster.u32 rb, %2, %3;\n"
               "cp.async.bulk.shared::cluster.shared::cta.mbarrier::complete_tx::bytes [rd], [%1], %4, [rb];\n}\n"
               ::"r"(dst), "r"(src), "r"(bar), "r"(cta), "r"(bytes) : "memory");
}
__device__ __forceinline__ void fence_proxy_async_smem() { asm volatile("fence.proxy.async.shared::cta;" ::: "memory"); }
__device__ __forceinline__ void fence_proxy_async_global() { asm volatile("fence.proxy.async.global;" ::: "memory"); }
__device__ __forceinline__ uint32_t clk32() { uint32_t c; asm volatile("mov.u32 %0, %%clock;" : "=r"(c)::"memory"); return c; }
__device__ __forceinline__ void wait_until(uint32_t t0, uint32_t dt) { while (clk32() - t0 < dt) __nanosleep(32); }
__device__ __forceinline__ void spin_until(uint32_t t0, uint32_t dt) { while (clk32() - t0 < dt) {} }
__device__ __forceinline__ void prefetch_map(const CUtensorMap* m) { asm volatile("prefetch.tensormap [%0];" ::"l"(m) : "memory"); }
__device__ __forceinline__ void prefetch_line(const void* p) { asm volatile("prefetch.global.L2 [%0];" ::"l"(p) : "memory"); }
__device__ __forceinline__ unsigned ld_acquire(const unsigned* p) { unsigned v; asm volatile("ld.acquire.gpu.global.u32 %0, [%1];" : "=r"(v) : "l"(p) : "memory"); return v; }
__device__ __forceinline__ unsigned ld_relaxed(const unsigned* p) { unsigned v; asm volatile("ld.relaxed.gpu.global.u32 %0, [%1];" : "=r"(v) : "l"(p) : "memory"); return v; }
__device__ __forceinline__ uint32_t lds32(uint32_t a) { uint32_t v; asm volatile("ld.shared.u32 %0, [%1];" : "=r"(v) : "r"(a)); return v; }
__device__ __forceinline__ uint2 lds64(uint32_t a) { uint2 v; asm volatile("ld.shared.v2.u32 {%0,%1}, [%2];" : "=r"(v.x), "=r"(v.y) : "r"(a) : "memory"); return v; }
__device__ __forceinline__ uint4 lds128(uint32_t a) { uint4 v; asm volatile("ld.shared.v4.u32 {%0,%1,%2,%3}, [%4];" : "=r"(v.x), "=r"(v.y), "=r"(v.z), "=r"(v.w) : "r"(a) : "memory"); return v; }
__device__ __forceinline__ void sts32(uint32_t a, uint32_t v) { asm volatile("st.shared.u32 [%0], %1;" ::"r"(a), "r"(v) : "memory"); }
__device__ __forceinline__ void sts128(uint32_t a, uint4 v) { asm volatile("st.shared.v4.u32 [%0], {%1,%2,%3,%4};" ::"r"(a), "r"(v.x), "r"(v.y), "r"(v.z), "r"(v.w) : "memory"); }
__device__ __forceinline__ void ldsm4(uint32_t* r, uint32_t a) { asm volatile("ldmatrix.sync.aligned.m8n8.x4.shared.b16 {%0,%1,%2,%3}, [%4];" : "=r"(r[0]), "=r"(r[1]), "=r"(r[2]), "=r"(r[3]) : "r"(a) : "memory"); }
__device__ __forceinline__ void ldsm4t(uint32_t* r, uint32_t a) { asm volatile("ldmatrix.sync.aligned.m8n8.x4.trans.shared.b16 {%0,%1,%2,%3}, [%4];" : "=r"(r[0]), "=r"(r[1]), "=r"(r[2]), "=r"(r[3]) : "r"(a) : "memory"); }
__device__ __forceinline__ void stsm4t(uint32_t a, uint32_t r0, uint32_t r1, uint32_t r2, uint32_t r3) {
  asm volatile("stmatrix.sync.aligned.m8n8.x4.trans.shared.b16 [%0], {%1,%2,%3,%4};" ::"r"(a), "r"(r0), "r"(r1), "r"(r2), "r"(r3) : "memory");
}
__device__ __forceinline__ uint4 ldg128_nc(const void* p) { uint4 v; asm volatile("ld.global.nc.L1::no_allocate.v4.u32 {%0,%1,%2,%3}, [%4];" : "=r"(v.x), "=r"(v.y), "=r"(v.z), "=r"(v.w) : "l"(p)); return v; }
__device__ __forceinline__ void stg128(void* p, uint4 v) { asm volatile("st.global.L1::no_allocate.v4.u32 [%0], {%1,%2,%3,%4};" ::"l"(p), "r"(v.x), "r"(v.y), "r"(v.z), "r"(v.w) : "memory"); }
__device__ __forceinline__ uint32_t pack_bf16(float lo, float hi) { uint32_t r; asm("cvt.rn.bf16x2.f32 %0, %1, %2;" : "=r"(r) : "f"(hi), "f"(lo)); return r; }
__device__ __forceinline__ uint32_t bmul2(uint32_t a, uint32_t b) { uint32_t r; asm("mul.rn.bf16x2 %0, %1, %2;" : "=r"(r) : "r"(a), "r"(b)); return r; }
__device__ __forceinline__ uint32_t bfma2(uint32_t a, uint32_t b, uint32_t c) { uint32_t r; asm("fma.rn.bf16x2 %0, %1, %2, %3;" : "=r"(r) : "r"(a), "r"(b), "r"(c)); return r; }
__device__ __forceinline__ uint32_t blo2(uint32_t a) { uint32_t r; asm("{\n.reg .b16 l, h;\nmov.b32 {l, h}, %1;\nmov.b32 %0, {l, l};\n}" : "=r"(r) : "r"(a)); return r; }
__device__ __forceinline__ float bf2f(__nv_bfloat16 v) { return __bfloat162float(v); }

#define R8(d, o) "+f"(d[o]), "+f"(d[o + 1]), "+f"(d[o + 2]), "+f"(d[o + 3]), "+f"(d[o + 4]), "+f"(d[o + 5]), "+f"(d[o + 6]), "+f"(d[o + 7])
#define R16(d, o) R8(d, o), R8(d, o + 8)
#define R64(d, o) R16(d, o), R16(d, o + 16), R16(d, o + 32), R16(d, o + 48)
template <int TA> __device__ __forceinline__ void wgmma_n128(float* d, uint64_t da, uint64_t db, int scale_d) {
  asm volatile("{\n.reg .pred p;\nsetp.ne.b32 p, %66, 0;\n"
    "wgmma.mma_async.sync.aligned.m64n128k16.f32.bf16.bf16 {"
    "%0,%1,%2,%3,%4,%5,%6,%7,%8,%9,%10,%11,%12,%13,%14,%15,%16,%17,%18,%19,%20,%21,%22,%23,%24,%25,%26,%27,%28,%29,%30,%31,"
    "%32,%33,%34,%35,%36,%37,%38,%39,%40,%41,%42,%43,%44,%45,%46,%47,%48,%49,%50,%51,%52,%53,%54,%55,%56,%57,%58,%59,%60,%61,%62,%63"
    "}, %64, %65, p, 1, 1, %67, 0;\n}\n"
    : R64(d, 0)
    : "l"(da), "l"(db), "r"(scale_d), "n"(TA));
}
template <int N> __device__ __forceinline__ void fence_regs(float* d) {
#pragma unroll
  for (int i = 0; i < N; i++) asm volatile("" : "+f"(d[i])::"memory");
}
#define PMFENCE() asm volatile("pmevent 0;" ::: "memory")
__device__ __forceinline__ void cmul(float ar, float ai, float br, float bi, float& cr, float& ci) {
  cr = ar * br - ai * bi; ci = ar * bi + ai * br;
}
__device__ __forceinline__ void csq(float& r, float& i) { const float x = fmaf(r, r, -i * i), y = r * i; r = x; i = y + y; }

#define W8(d, o) "=f"(d[o]), "=f"(d[o + 1]), "=f"(d[o + 2]), "=f"(d[o + 3]), "=f"(d[o + 4]), "=f"(d[o + 5]), "=f"(d[o + 6]), "=f"(d[o + 7])
#define L16 "{%0,%1,%2,%3,%4,%5,%6,%7,%8,%9,%10,%11,%12,%13,%14,%15}"
#define L32 "{%0,%1,%2,%3,%4,%5,%6,%7,%8,%9,%10,%11,%12,%13,%14,%15,%16,%17,%18,%19,%20,%21,%22,%23,%24,%25,%26,%27,%28,%29,%30,%31}"
template <int ACC, int TB> __device__ __forceinline__ void rs_n32(float* d, const uint32_t* a, uint64_t db) {
  if constexpr (ACC) asm volatile("wgmma.mma_async.sync.aligned.m64n32k16.f32.bf16.bf16 " L16 ", {%16,%17,%18,%19}, %20, 1, 1, 1, %21;" : R16(d, 0) : "r"(a[0]), "r"(a[1]), "r"(a[2]), "r"(a[3]), "l"(db), "n"(TB));
  else asm volatile("wgmma.mma_async.sync.aligned.m64n32k16.f32.bf16.bf16 " L16 ", {%16,%17,%18,%19}, %20, 0, 1, 1, %21;" : W8(d, 0), W8(d, 8) : "r"(a[0]), "r"(a[1]), "r"(a[2]), "r"(a[3]), "l"(db), "n"(TB));
}
template <int ACC, int TB> __device__ __forceinline__ void rs_n64(float* d, const uint32_t* a, uint64_t db) {
  if constexpr (ACC) asm volatile("wgmma.mma_async.sync.aligned.m64n64k16.f32.bf16.bf16 " L32 ", {%32,%33,%34,%35}, %36, 1, 1, 1, %37;" : R16(d, 0), R16(d, 16) : "r"(a[0]), "r"(a[1]), "r"(a[2]), "r"(a[3]), "l"(db), "n"(TB));
  else asm volatile("wgmma.mma_async.sync.aligned.m64n64k16.f32.bf16.bf16 " L32 ", {%32,%33,%34,%35}, %36, 0, 1, 1, %37;" : W8(d, 0), W8(d, 8), W8(d, 16), W8(d, 24) : "r"(a[0]), "r"(a[1]), "r"(a[2]), "r"(a[3]), "l"(db), "n"(TB));
}
template <int ACC> __device__ __forceinline__ void ss_n32_tt(float* d, uint64_t da, uint64_t db) {
  if constexpr (ACC) asm volatile("wgmma.mma_async.sync.aligned.m64n32k16.f32.bf16.bf16 " L16 ", %16, %17, 1, 1, 1, 1, 1;" : R16(d, 0) : "l"(da), "l"(db));
  else asm volatile("wgmma.mma_async.sync.aligned.m64n32k16.f32.bf16.bf16 " L16 ", %16, %17, 0, 1, 1, 1, 1;" : W8(d, 0), W8(d, 8) : "l"(da), "l"(db));
}
__device__ __forceinline__ void stsm4(uint32_t a, uint32_t r0, uint32_t r1, uint32_t r2, uint32_t r3) {
  asm volatile("stmatrix.sync.aligned.m8n8.x4.shared.b16 [%0], {%1,%2,%3,%4};" ::"r"(a), "r"(r0), "r"(r1), "r"(r2), "r"(r3) : "memory");
}
template <int N> __device__ __forceinline__ void fence_u32(uint32_t* d) {
#pragma unroll
  for (int i = 0; i < N; i++) asm volatile("" : "+r"(d[i])::"memory");
}
__device__ __forceinline__ void pack32(uint32_t* f, const float* z) {
#pragma unroll
  for (int i = 0; i < 16; i++) f[i] = pack_bf16(z[2 * i], z[2 * i + 1]);
}
template <int INV> __device__ __forceinline__ void twiddle(uint32_t* f, const uint32_t* tp, const uint32_t* ts) {
#pragma unroll
  for (int i = 0; i < 8; i++) {
    uint32_t x = f[2 * i + INV], y = f[2 * i + 1 - INV];
    x = bfma2(tp[i & 3], y, x); y = bfma2(ts[i & 3], x, y); x = bfma2(tp[i & 3], y, x);
    f[2 * i + INV] = x; f[2 * i + 1 - INV] = y;
  }
}
__device__ __forceinline__ uint32_t bfnma2(uint32_t a, uint32_t b, uint32_t c) { uint32_t r; asm("{\n.reg .b32 t;\nmul.bf16x2 t, %1, %2;\nsub.bf16x2 %0, %3, t;\n}" : "=r"(r) : "r"(a), "r"(b), "r"(c)); return r; }
__device__ __forceinline__ uint32_t bfms2(uint32_t a, uint32_t b, uint32_t c) { uint32_t r; asm("{\n.reg .b32 t;\nmul.bf16x2 t, %1, %2;\nsub.bf16x2 %0, t, %3;\n}" : "=r"(r) : "r"(a), "r"(b), "r"(c)); return r; }
template <int ADD> __device__ __forceinline__ void bimac(uint32_t* o, const uint32_t* a, const uint32_t* b, const uint32_t* c) {
#pragma unroll
  for (int J = 0; J < 2; J++) {
    const uint32_t Pr = a[2 * J], Pi = a[2 * J + 1], Qr = a[2 * J + 4], Qi = a[2 * J + 5], pr = b[2 * J], pi = b[2 * J + 1], qr = b[2 * J + 4], qi = b[2 * J + 5];
    uint32_t x0, x1, x2, x3;
    if (ADD == 0) { x0 = bmul2(Pr, pr); x1 = bmul2(Pr, pi); x2 = bmul2(Pr, qr); x3 = bmul2(Pr, qi); }
    if (ADD == 1) { x0 = bfma2(Pr, pr, c[2 * J]); x1 = bfma2(Pr, pi, c[2 * J + 1]); x2 = bfma2(Pr, qr, c[2 * J + 4]); x3 = bfma2(Pr, qi, c[2 * J + 5]); }
    if (ADD == 2) { x0 = bfma2(Pr, pr, c[2 * J + 1]); x1 = bfms2(Pr, pi, c[2 * J]); x2 = bfma2(Pr, qr, c[2 * J + 5]); x3 = bfms2(Pr, qi, c[2 * J + 4]); }
    x0 = bfnma2(Pi, pi, x0); x1 = bfma2(Pi, pr, x1); x2 = bfnma2(Pi, qi, x2); x3 = bfma2(Pi, qr, x3);
    x0 = bfnma2(Qr, qr, x0); x1 = bfnma2(Qr, qi, x1); x2 = bfma2(Qr, pr, x2); x3 = bfma2(Qr, pi, x3);
    x0 = bfma2(Qi, qi, x0); x1 = bfnma2(Qi, qr, x1); x2 = bfnma2(Qi, pi, x2); x3 = bfma2(Qi, pr, x3);
    o[2 * J] = x0; o[2 * J + 1] = x1; o[2 * J + 4] = x2; o[2 * J + 5] = x3;
  }
}
__device__ __forceinline__ void sincos8k(int n, float& s, float& c) {
  const float x = (float)((n << 19) >> 19) * (6.283185307179586f / 8192.f);
  s = __sinf(x); c = __cosf(x);
}
__device__ __forceinline__ void fft_tables(uint32_t f1a, uint32_t f2a, int w, int lane, uint32_t* tp, uint32_t* ts, float& d0r, float& d0i) {
  const int c = lane & 3, f1 = 8 * w + (lane >> 2);
#pragma unroll 1
  for (int J = 3; J >= 0; J--) {
    const int a = 8 * J + 2 * c;
    float s0, c0, s1, c1;
    sincos8k(64 * (4 * f1 + 1) * a + 31 * (4 * f1 - 63), d0i, d0r); sincos8k(64 * (4 * f1 + 1) * (a + 1) + 31 * (4 * f1 - 63), s1, c1);
    d0r *= 0.125f; d0i *= 0.125f;
    sts32(f1a + w * 1024 + J * 128 + lane * 4, pack_bf16(d0r, 0.125f * c1)); sts32(f1a + w * 1024 + 512 + J * 128 + lane * 4, pack_bf16(d0i, 0.125f * s1));
    sincos8k(128 * (2 * (a & 15) + 1) * f1 - 128 * (a & 16), s0, c0); sincos8k(128 * (2 * (a & 15) + 3) * f1 - 128 * (a & 16), s1, c1);
    sts32(f2a + w * 512 + J * 128 + lane * 4, pack_bf16(c0, c1));
    sincos8k((4 * f1 - 63) * (2 * a - 31), s0, c0); sincos8k((4 * f1 - 63) * (2 * a - 29), s1, c1);
#pragma unroll
    for (int i = 3; i > 0; i--) { ts[i] = ts[i - 1]; tp[i] = tp[i - 1]; }
    ts[0] = pack_bf16(s0, s1); tp[0] = pack_bf16(-__fdividef(s0, 1.f + c0), -__fdividef(s1, 1.f + c1));
  }
  if (c != 0) d0r = d0i = 0.f;
}

__device__ __forceinline__ void ss_n16(float* d, uint64_t da, uint64_t db) {
  asm volatile("wgmma.mma_async.sync.aligned.m64n16k16.f32.bf16.bf16 {%0,%1,%2,%3,%4,%5,%6,%7}, %8, %9, 0, 1, 1, 0, 0;" : W8(d, 0) : "l"(da), "l"(db));
}
template <int N> __device__ __forceinline__ void rename_regs(float* d) {
#pragma unroll
  for (int i = 0; i < N; i++) { float t; asm volatile("mov.b32 %0, %1;" : "=f"(t) : "f"(d[i]) : "memory"); d[i] = t; }
}

template <int SWAPB>
__global__ void __cluster_dims__(2, 1, 1) __launch_bounds__(512, 1)
fused_kernel(const __grid_constant__ Params P, const __grid_constant__ CUtensorMap mX, const __grid_constant__ CUtensorMap mB,
             const __grid_constant__ CUtensorMap mCre, const __grid_constant__ CUtensorMap mCim, const __grid_constant__ CUtensorMap mXs,
             const __grid_constant__ CUtensorMap mK, const __grid_constant__ CUtensorMap mV, const __grid_constant__ CUtensorMap mQ, const __grid_constant__ CUtensorMap mS,
             const __grid_constant__ CUtensorMap mO) {
  extern __shared__ __align__(1024) uint8_t smem_raw[];
  if (threadIdx.x == 0) { prefetch_map(&mX); prefetch_map(&mB); }
  const uint32_t sb = (uint32_t)__cvta_generic_to_shared(smem_raw);
  const uint32_t bars = sb + OFF_BAR;
  const int slot = (P.slot[blockIdx.x >> 3] >> (4 * (blockIdx.x & 6))) & 63, rank = blockIdx.x & 1;
  const int j = slot & 7, tc = 2 * (slot >> 3) + rank, b = 2 * slot + rank;
  const int tid = threadIdx.x;
  const int warp = __shfl_sync(0xffffffffu, tid >> 5, 0);
  const int wg = warp >> 2;
  const uint32_t c_start = clk32();
  auto kblock = [&](int n) { return ((n & 14) == 0 || (n & 14) == 2 * j ? n ^ (2 * j) : n) & 31; };
  auto send_y = [&](int r) {
    const uint32_t src = sb + OFF_U + 4 * (rank ^ 1) * U_N8 + r * U_CH, dst = r >= 2 ? sb + OFF_U + 4 * rank * U_N8 + (r - 2) * U_CH : sb + OFF_IN + 96 + r * 2064;
#pragma unroll 1
    for (int n = 0; n < 4; n++) bulk_send(dst + n * (r >= 2 ? U_N8 : 512), src + n * U_N8, 512, bars + (B_IN + r) * 8, rank ^ 1);
  };
  auto load_q = [&](int i, int off, int bar) {
    const uint32_t fb = bars + bar * 8 + 4 * (i & 2);
    mbar_expect(fb, 4096); tma4d(sb + off + 2048 * (i & 2), &mQ, 16 * slot, 0, 4 * i, 4 * rank, fb);
  };
  auto head = [&](int n) {
    const uint32_t fb = bars + (B_FULL + n) * 8, dst = sb + OFF_RING + n * STAGE_BYTES;
    mbar_expect(fb, STAGE_BYTES);
    tma4d(dst + 16384, &mX, 64 * n, 0, 4 * tc, 0, fb);
    tma4d(dst, &mB, 64 * n, 0, 0, 8 * j, fb);
    tma4d(dst + 8192, &mB, 64 * n, 0, 0, 8 * j + 4, fb);
  };
  if (warp == 0 && elect_one()) {
#pragma unroll
    for (int s = 0; s < STAGES; s++) mbar_init(bars + (B_FULL + s) * 8, 1);
    head(0);
    asm volatile("fence.mbarrier_init.release.cluster;" ::: "memory");
  }
  if (wg == 3 && elect_one()) {
    if (warp < 15) {
#pragma unroll
      for (int s = 0; s < 13; s++) mbar_init(bars + 8 * B_XI + (warp & 3) * 104 + 8 * s, 1);
    } else {
#pragma unroll
      for (int s = B_XI + 39; s <= B_NONE; s++) mbar_init(bars + 8 * s, s < B_EMPTY ? 1 : s < B_COEF ? 2 : s == B_COEF ? 128 : 4);
    }
    asm volatile("fence.mbarrier_init.release.cluster;" ::: "memory");
  }
  __syncwarp();
  asm volatile("barrier.cluster.arrive.relaxed.aligned;" ::: "memory");
  if (warp == 0 && elect_one()) {
#pragma unroll 1
    for (int n = 1; n < HEAD; n++) { spin_until(c_start, ST_T0 + n * ST_DELAY); head(n); }
  }
  __syncwarp();
  int fl;
  uint32_t fa, fs;
  uint2 q[4][4];
  auto fin_setup = [&]() {
    asm volatile("mov.u32 %0, %%laneid;" : "=r"(fl));
    const int lc = 2 * (fl & 2) + (fl & 1) + ((fl >> 2) & 2);
    const bool own = ((fl >> 2) & 1) == rank, spare = !own && lc < 2;
    fa = (spare ? sb + OFF_IN + 96 + lc * 2064 : sb + OFF_U + (own ? 4 * rank * U_N8 : 4 * (rank ^ 1) * U_N8 - 2 * U_CH) + lc * U_CH) + (warp & 3) * 128 + (fl >> 4) * 16 + (wg & 1) * 64;
    fs = spare ? 512 : U_N8;
  };
  auto get_q = [&](int n, int off, int bar, int ph) {
#pragma unroll
    for (int u = 0; u < 2; u++) {
      mbar_wait(bars + (bar + u) * 8, ph);
#pragma unroll
      for (int r = 0; r < 4; r++) q[n + u][r] = lds64(sb + off + 4096 * u + 1024 * (warp & 3) + 256 * r + 8 * fl);
    }
  };
#define CLUSTER_WAIT() asm volatile("barrier.cluster.wait.aligned;" ::: "memory")

  if (wg == 3) {
    asm volatile("setmaxnreg.dec.sync.aligned.u32 24;");
    CLUSTER_WAIT();
    if (warp < 14) {
      if (elect_one()) {
        uint32_t so = 8 * (HEAD % STAGES), ph = HEAD < STAGES;
        auto step = [&](auto issue) {
          mbar_wait(bars + B_EMPTY * 8 + so, ph);
          issue(sb + OFF_RING + (so << 12), bars + B_FULL * 8 + so);
          so += 8;
          if (so == 8 * STAGES) { so = 0; ph ^= 1; }
        };
        if (warp == 12) {
          auto g1 = [&](int n0, int n1, int grp) {
#pragma unroll 1
            for (int n = n0; n < n1; n++) step([&](uint32_t dst, uint32_t fb) { mbar_expect(fb, STAGE_BYTES); tma4d_mc(dst + rank * 8192, &mB, n * 64, 0, 0, grp + 4 * rank, fb); });
          };
#pragma unroll 1
          for (int n = HEAD; n < STAGES; n++) { spin_until(c_start, ST_T0 + n * ST_DELAY); g1(n, n + 1, 8 * j); }
          g1(STAGES, 16, 8 * j);
          g1(0, XPOS - 16, 8 * j + 64);
          step([&](uint32_t dst, uint32_t fb) { mbar_expect(fb, STAGE_BYTES); tma4d(dst, &mXs, 128 * j, 0, 4 * tc, 0, fb); });
#pragma unroll 1
          for (int n = 0; n < 32; n += 2) {
            const int col = kblock(n) * 32;
#pragma unroll
            for (int part = 0; part < 2; part++)
              step([&](uint32_t dst, uint32_t fb) { mbar_expect(fb, STAGE_BYTES); tma5d_mc(dst + rank * 8192, part ? &mCim : &mCre, col, 0, 0, 0, 8 * j + 4 * rank, fb); });
          }
        } else {
          auto g1 = [&](int n0, int n1, int nb) {
#pragma unroll 1
            for (int n = n0; n < n1; n++) step([&](uint32_t dst, uint32_t fb) { tma4d(dst + 16384, &mX, n * 64, 0, 4 * tc, 0, fb); });
          };
          auto g2 = [&](int n0, int n1) {
#pragma unroll 1
            for (int n = n0; n < n1; n++) step([&](uint32_t dst, uint32_t fb) { bulk_load(dst + 16384, g_h + (32 * tc + kblock(n)) * 1024, 16384, fb); });
          };
#pragma unroll 1
          for (int n = HEAD; n < STAGES; n++) { spin_until(c_start, ST_T0 + n * ST_DELAY); g1(n, n + 1, 0); }
          g1(STAGES, 16, 0);
          g1(0, XPOS - 16, 16);
          step([&](uint32_t dst, uint32_t fb) { tma4d(dst + 16384, &mXs, 128 * j + 64, 0, 4 * tc, 0, fb); });
#pragma unroll 1
          for (int v = 0; v < 2; v++) {
            mbar_wait(bars + B_HP * 8, v);
            fence_proxy_async_global();
            g2(16 * v, 16 * v + 2);
            mbar_wait(bars + B_HR * 8, v);
            fence_proxy_async_global();
            g2(16 * v + 2, 16 * v + 16);
          }
        }
      }
    } else if (warp == 15) {
      mbar_wait(bars + B_COEF * 8, 0);
      const unsigned epoch = lds32(bars + B_EPOCH * 8);
#pragma unroll 1
      for (int v = 0; v < 2; v++) {
        unsigned* fp = &g_flagH[(16 * v + tc) * 32];
        if (elect_one()) {
          wait_until(v ? clk32() : c_start, (v ? PFC_T1 : PFC_T0) + (slot >> 3) * PFC_DT);
#pragma unroll
          for (int part = 0; part < 2; part++)
            asm volatile("cp.async.bulk.prefetch.tensor.5d.L2.global [%0, {%1, %2, %2, %2, %3}];" ::"l"(part ? &mCim : &mCre), "r"(512 * v + 8 * (slot & 56)), "r"(0), "r"(8 * j + 4 * rank) : "memory");
        }
        __syncwarp();
        bar_sync(4 + v, 160);
        if (elect_one()) {
          asm volatile("red.release.gpu.global.add.u32 [%0], 1;" ::"l"(fp) : "memory");
          mbar_arrive(bars + B_HP * 8);
          int it = 0;
          while (ld_acquire(fp) != 8 * epoch && ++it < (SPIN_LIMIT << 4)) __nanosleep(POLL_NS);
          mbar_arrive(bars + B_HR * 8);
        }
        __syncwarp();
      }
    } else if (elect_one()) {
      const int ch0 = 16 * slot;
      auto load_k = [&](int s, uint32_t dst) { const uint32_t fb = bars + (B_KF + s) * 8; mbar_expect(fb, 4096); tma2d(dst, &mS, 0, 64 * (8 * b + s), fb); };
      prefetch_map(&mS); prefetch_map(&mK); prefetch_map(&mV);
      wait_until(c_start, K_T0);
      load_k(0, sb + OFF_U + (4 * rank + 3) * U_N8); load_k(1, sb + OFF_U + (4 * rank + 3) * U_N8 - 4096);
      {
        uint32_t so = 16, ph = 1;
#pragma unroll 1
        for (int e = 0; e < 9; e++) {
          const uint32_t fb = bars + B_KVF * 8 + so, dst = sb + OFF_KV + (so << 10);
          wait_until(c_start, KV_T0 + (e ? 2 * e - 1 : 0) * KV_DT - (e > KV_E ? e - KV_E : 0) * 2 * (KV_DT - KV_D2));
          mbar_wait(bars + B_KVE * 8 + so, ph);
          const uint32_t c1 = clk32();
          mbar_expect(fb, e ? 8192 : 4096);
          tma3d(dst, &mK, ch0, 32 * rank - (e == 0), (4 * e - 4) & 31, fb);
          if (e > 0) { wait_until(c1, KV_DV); tma3d(dst + 4096, &mV, ch0, 32 * rank, 4 * e - 4, fb); }
          so += 8;
          if (so == 24) so = 0;
          if (so == 16) ph ^= 1;
        }
      }
      prefetch_map(&mCre); prefetch_map(&mCim); prefetch_map(&mXs); prefetch_map(&mQ); prefetch_map(&mO);
      mbar_wait(bars + B_KVE * 8, 0);
      load_k(2, sb + OFF_K); load_k(3, sb + OFF_K + 4096);
      mbar_wait(bars + (B_UF + 3) * 8, 0);
#pragma unroll 1
      for (int ch = 0; ch < 7; ch++) {
        mbar_wait(bars + (B_ST + ch) * 8, 0);
        if (ch > 2) mbar_wait(bars + (B_IN + ch - 3) * 8, 0);
        if (ch < 4) load_k(ch + 4, sb + OFF_K + (ch & 1) * 4096);
        else if (ch < 6) load_q(2 * (ch & 1), OFF_K, B_KF + 8);
        if (ch > 0) send_y(ch - 1);
        if (ch == 2) load_q(1, OFF_Q, B_QF);
        if (ch == 3) asm volatile("cp.async.bulk.prefetch.tensor.4d.L2.global [%0, {%1, %2, %3, %4}];" ::"l"(&mQ), "r"(16 * (slot & ~3)), "r"(0), "r"(16 + 4 * (slot & 3)), "r"(4 * rank) : "memory");
        if (ch == 4) { mbar_wait(bars + B_XI * 8, 0); load_q(3, OFF_Q, B_QF); }
      }
    }
    return;
  } else if (wg == 2) {
    asm volatile("setmaxnreg.inc.sync.aligned.u32 %0;" ::"n"(488 - 2 * GREG));
    const int t = tid & 127, w = warp & 3, lane = t & 31, g = lane >> 2, c = lane & 3;
    const uint4 s2[2] = {ldg128_nc(P.shift_k + (8 * b + 2 * c) * 4), ldg128_nc(P.shift_k + (8 * (b ^ 1) + 2 * c) * 4)};
    const uint32_t dskip = __bfloat16_as_ushort(P.ssm_D[8 * b + (t & 7)]);
    uint32_t tp[4] = {}, ts[4] = {};
    float d0r, d0i;
    fft_tables(sb + OFF_F1, sb + OFF_F2, w, lane, tp, ts, d0r, d0i);
    CLUSTER_WAIT();
    if (t < 12) mbar_expect(bars + (B_IN + t) * 8, t < 6 ? 2048 : t < 8 ? 4 * (U_CH + 512) : U_N8);
    if (t < 8) sts32(sb + OFF_D + 8 * t, dskip << 16);
    const uint64_t dF1b = make_desc(sb + OFF_F1, 512, 128, 0);
    const uint64_t dF2f = make_desc(sb + OFF_F2, 512, 128, 0), dF2i = make_desc(sb + OFF_F2, 128, 512, 0);
    uint32_t f1[8];
#pragma unroll
    for (int i = 0; i < 8; i++) f1[i] = lds32(sb + OFF_F1 + w * 1024 + (i & 1) * 512 + (i >> 1) * 128 + lane * 4);
    auto T1k = [&](float* z, uint64_t dk) { wg_fence(); rs_n64<0, 1>(z, f1, dk); rs_n64<1, 1>(z, f1 + 4, dk + 64); wg_commit(); };
    auto T1u = [&](float* z, uint64_t du) { wg_fence(); rs_n64<0, 0>(z, f1, du); rs_n64<1, 0>(z, f1 + 4, du + 16); wg_commit(); };
    auto T2 = [&](float* s, const uint32_t* f) {
      wg_fence();
      rs_n32<0, 1>(s, f, dF2f); rs_n32<0, 1>(s + 16, f + 8, dF2f); rs_n32<1, 1>(s, f + 4, dF2f + 64); rs_n32<1, 1>(s + 16, f + 12, dF2f + 64);
      wg_commit();
    };
    auto product = [&](uint32_t* pr, const uint32_t* kh, const uint32_t* uh) {
      bimac<0>(pr, kh, uh, pr); bimac<2>(pr + 8, kh + 8, uh, pr); bimac<1>(pr + 8, kh, uh + 8, pr + 8);
      fence_u32<16>(pr);
    };
    float zk[32] = {};
    uint32_t pr[16];
    {
      uint32_t kh0[16];
      {
        float z0[32], sk[32];
        uint32_t fk[16];
        const uint64_t dk = make_desc(sb + OFF_U + (4 * rank + 3) * U_N8, 2048, 512, 2);
        fence_proxy_async_smem();
        bar_sync(7, 128);
        mbar_wait(bars + B_KF * 8, 0);
        T1k(z0, dk);
        mbar_wait(bars + (B_KF + 1) * 8, 0);
        T1k(zk, dk - 256);
        wg_wait<0>(); fence_regs<32>(z0); fence_regs<32>(zk);
        const float dd = __uint_as_float(lds32(sb + OFF_D));
        z0[0] = fmaf(d0r, dd, z0[0]); z0[2] = fmaf(d0i, dd, z0[2]);
        pack32(fk, z0); twiddle<0>(fk, tp, ts); fence_u32<16>(fk);
        T2(sk, fk);
        wg_wait<0>(); fence_regs<32>(sk); fence_u32<16>(fk);
        pack32(kh0, sk); fence_u32<16>(kh0);
      }
      {
        uint32_t sk[2][4], kx[2][8];
#pragma unroll
        for (int o = 0; o < 2; o++) {
          sk[o][0] = __byte_perm(s2[o].x, s2[o].z, 0x5410); sk[o][1] = __byte_perm(s2[o].x, s2[o].z, 0x7632);
          sk[o][2] = __byte_perm(s2[o].y, s2[o].w, 0x5410); sk[o][3] = __byte_perm(s2[o].y, s2[o].w, 0x7632);
        }
        const uint32_t la = sb + OFF_KV + (lane >> 3) * 1024 + (8 * w + (lane & 7)) * 32 + ((rank ^ ((lane >> 2) & 1)) << 4);
        const uint32_t uo = (lane & 7) * U_CH + w * 128 + (lane >> 3) * 16;
        mbar_wait(bars + (B_KVF + 2) * 8, 0);
        ldsm4(kx[0], la + 16384); ldsm4(kx[1], (la ^ 16) + 16384);
        if (lane == 0) mbar_arrive(bars + (B_KVE + 2) * 8 + (kx[0][1] & kx[1][1] & P.zero));
        uint32_t so = 0, ph = 0;
#pragma unroll 1
        for (int n = 0; n < 4; n++) {
          const uint32_t own = sb + OFF_U + (4 * rank + n) * U_N8, box = n < 3 ? sb + OFF_U + (4 * (rank ^ 1) + n + 1) * U_N8 : sb + OFF_IN;
#pragma unroll
          for (int e = 0; e < 2; e++) {
            uint32_t vx[2][4];
            mbar_wait(bars + B_KVF * 8 + so, ph);
#pragma unroll
            for (int o = 0; o < 2; o++) { ldsm4(kx[o] + 4, (la ^ (16 * o)) + (so << 10)); ldsm4(vx[o], (la ^ (16 * o)) + (so << 10) + 4096); }
            if (lane == 0) mbar_arrive(bars + B_KVE * 8 + so + (kx[0][4] & kx[1][4] & vx[0][0] & vx[1][0] & P.zero));
#pragma unroll
            for (int o = 0; o < 2; o++) {
#pragma unroll
              for (int i = 0; i < 4; i++) vx[o][i] = bmul2(bfma2(kx[o][i + 4], sk[o][0], bfma2(kx[o][i + 3], sk[o][1], bfma2(kx[o][i + 2], sk[o][2], bmul2(kx[o][i + 1], sk[o][3])))), vx[o][i]);
              stsm4t((o ? box : own) + uo + e * 64, vx[o][0], vx[o][1], vx[o][2], vx[o][3]);
              kx[o][1] = kx[o][5]; kx[o][2] = kx[o][6]; kx[o][3] = kx[o][7];
            }
            so += 8;
            if (so == 24) so = 0;
            if (so == 16) ph ^= 1;
          }
          fence_proxy_async_smem();
          bar_sync(7, 128);
          if (w == 0 && elect_one()) {
            if (n > 0) mbar_wait(bars + B_UF * 8 + 8 * (n - 1), 0);
            bulk_send(own, box, U_N8, bars + B_UF * 8 + 8 * n, rank ^ 1);
          }
          __syncwarp();
        }
      }
      float zu[32], su[32];
      uint32_t fu[16], uh[16];
#pragma unroll
      for (int n = 0; n < 4; n++) mbar_wait(bars + (B_UF + n) * 8, 0);
      T1u(zu, make_desc(sb + OFF_U, 128, U_N8, 0));
      wg_wait<0>(); fence_regs<32>(zu);
      pack32(fu, zu); twiddle<0>(fu, tp, ts); fence_u32<16>(fu);
      T2(su, fu);
      wg_wait<0>(); fence_regs<32>(su); fence_u32<16>(fu);
      pack32(uh, su);
      product(pr, kh0, uh);
    }
    {
#define CF(i) do { if ((CFM >> (i)) & 1) PMFENCE(); } while (0)
      const uint32_t vs = w < 2 ? 512 : U_N8, vi = (w >> 1) * U_CH;
      uint32_t va = (w < 2 ? sb + OFF_VP : sb + OFF_U) + ((lane >> 4) & 1) * vs + (w & 1) * 256 + (lane & 15) * 16;
      const uint32_t ya = sb + OFF_U + (2 * w + ((lane >> 3) & 1)) * U_N8 + (lane >> 4) * 128 + (lane & 7) * 16;
      uint64_t du = make_desc(sb + OFF_U, 128, U_N8, 0), dk = make_desc(sb + OFF_K, 2048, 512, 2);
      const uint64_t dv = make_desc(sb + OFF_VP, 128, 512, 0), dks = 2 * dk + 256;
      uint32_t yp[8] = {};
      uint32_t yq = sb + OFF_Q + lane * 16, yi = ya - yq;
      auto store_y = [&]() { stsm4(yq, yp[0], yp[1], yp[2], yp[3]); stsm4(yq + 256, yp[4], yp[5], yp[6], yp[7]); };
      auto step = [&](uint32_t c8, auto fwd) {
        constexpr bool FWD = decltype(fwd)::value;
        float zu[32], sk[32], su[32], v[32], y[16];
        uint32_t kh[16], uh[16], fk[16], fu[16], fv[16];
        wg_fence();
        rs_n32<0, 0>(v, pr, dF2i); rs_n32<0, 0>(v + 16, pr + 8, dF2i); rs_n32<1, 0>(v, pr + 4, dF2i + 16); rs_n32<1, 0>(v + 16, pr + 12, dF2i + 16);
        wg_commit();
        CF(0);
        const float dd = FWD ? __uint_as_float(lds32(sb + OFF_D + 8 + c8)) : 0.f;
        store_y();
        if (FWD) {
          zk[0] = fmaf(d0r, dd, zk[0]); zk[2] = fmaf(d0i, dd, zk[2]);
          pack32(fk, zk); twiddle<0>(fk, tp, ts); fence_u32<16>(fk);
          T2(sk, fk);
          CF(2);
          mbar_wait(bars + (B_KF + 2) * 8 + c8, 0);
          wg_wait<1>();
        } else {
#pragma unroll
          for (int r = 3; r < 6; r++) mbar_wait(bars + (B_IN + r) * 8, 0);
          wg_wait<0>();
        }
        fence_regs<32>(v); fence_u32<16>(pr);
        pack32(fv, v); fence_u32<16>(fv);
        CF(4);
        if (FWD) T1u(zu, du + U_CH / 16);
        CF(5);
        if (FWD) { wg_wait<1>(); fence_regs<32>(sk); fence_u32<16>(fk); pack32(kh, sk); }
        twiddle<1>(fv, tp, ts);
        fence_u32<16>(fv);
        if (FWD) fence_u32<16>(kh);
        CF(7);
        if (FWD) T1k(zk, dk);
#pragma unroll
        for (int i = 0; i < 4; i++) stsm4(va + 2 * i * vs, fv[4 * i], fv[4 * i + 1], fv[4 * i + 2], fv[4 * i + 3]);
        if (FWD) {
          CF(8);
          wg_wait<1>(); fence_regs<32>(zu);
          pack32(fu, zu); twiddle<0>(fu, tp, ts); fence_u32<16>(fu);
          T2(su, fu);
          CF(10);
        }
        fence_proxy_async_smem();
        bar_sync(7, 128);
        wg_fence();
        ss_n32_tt<0>(y, dv, dF1b); ss_n32_tt<1>(y, dv + 16, dF1b + 64); ss_n32_tt<1>(y, du, dF1b + 128); ss_n32_tt<1>(y, du + 16, dF1b + 192);
        wg_commit();
        CF(12);
        if (FWD) {
          wg_wait<1>(); fence_regs<32>(su); fence_u32<16>(fu); fence_regs<32>(zk);
          if (t == 0) mbar_arrive(bars + B_ST * 8 + c8);
          pack32(uh, su);
          bimac<0>(pr, kh, uh, pr); bimac<2>(pr + 8, kh + 8, uh, pr); fence_u32<16>(pr);
          CF(14);
          wg_wait<0>(); fence_regs<16>(y);
          bimac<1>(pr + 8, kh, uh + 8, pr + 8); fence_u32<8>(pr + 8);
          du += U_CH / 16; dk = dks - dk;
          va += vi;
        }
        if (!FWD) {
          PMFENCE();
          fin_setup(); get_q(0, OFF_K, B_KF + 8, 0);
#pragma unroll
          for (int r = 0; r < 8; r++) q[2 + (r >> 2)][r & 3] = make_uint2(0, 0);
          wg_wait<0>(); fence_regs<16>(y);
        }
#pragma unroll
        for (int i = 0; i < 8; i++) yp[i] = pack_bf16(y[2 * i], y[2 * i + 1]);
        fence_u32<8>(yp);
        yq += yi; yi = U_CH;
      };
#pragma unroll 1
      for (uint32_t c8 = 0; c8 < 56; c8 += 8) step(c8, std::true_type());
      step(56, std::false_type());
      store_y();
    }
    fence_proxy_async_smem();
    bar_sync(7, 128);
    if (elect_one()) bulk_send(sb + OFF_U + (4 * rank + w) * U_N8 + 4 * U_CH, sb + OFF_U + (4 * (rank ^ 1) + w) * U_N8 + 6 * U_CH, U_CH + 512, bars + (B_IN + 6) * 8, rank ^ 1);
    __syncwarp();
    asm volatile("bar.arrive 9, 256;" ::: "memory");
  } else {
    asm volatile("setmaxnreg.inc.sync.aligned.u32 %0;" ::"n"(GREG));
    const int t = tid & 127, w = warp & 3, lane = t & 31, g = lane >> 2, c = lane & 3;
    if (wg == 1) {
      wait_until(c_start, COEF_T0);
      const int p = 64 * j + (t & 63) + 8 * (t & 64);
      const float Lr = bf2f(P.lam_re[p]), Li = bf2f(P.lam_im[p]);
      const uint32_t ds = __bfloat16_as_ushort(P.Dskip[128 * j + t]);
      const unsigned epoch = ld_relaxed(&g_epoch[b * 32]) + 1;
      const float dt = bf2f(__float2bfloat16_rn(expf(bf2f(P.log_dt[p]))));
      const float e = expf(dt * Lr);
      float sn, cs;
      {
        const double z = (double)(dt * Li) * 0.15915494309189535;
        sincospif(2.f * (float)(z - rint(z)), &sn, &cs);
      }
      const float lr = e * cs, li = e * sn;
      const float nr = lr - 1.0f, ni = li;
      const bool big = fabsf(Lr) >= fabsf(Li);
      const float la = big ? Lr : Li, lb = big ? Li : Lr, r = __fdiv_rn(lb, la), inv = __frcp_rn(fmaf(lb, r, la));
      const float br = (big ? fmaf(ni, r, nr) : fmaf(nr, r, ni)) * inv, bi = (big ? fmaf(-nr, r, ni) : fmaf(ni, r, -nr)) * inv;
      sts128(sb + OFF_COEF + t * 16, make_uint4(__float_as_uint(lr), __float_as_uint(li), pack_bf16(2.f * br, 2.f * br), pack_bf16(-2.f * bi, -2.f * bi)));
      sts32(sb + OFF_DS + 4 * t, ds << 16);
      if (t == 0) sts32(bars + B_EPOCH * 8, epoch);
    }
    CLUSTER_WAIT();
    if (wg == 1) mbar_arrive(bars + B_COEF * 8);
    float d[128];
    uint32_t so = 0, ph = 0, po = 0;
    uint32_t ra;
    auto set_ra = [&]() { asm volatile("mapa.shared::cluster.u32 %0, %1, %2;" : "=r"(ra) : "r"(bars + B_EMPTY * 8), "r"((t & 1) ? rank ^ 1 : rank)); };
    set_ra();
    auto release = [&](uint32_t off) { if (t < 2) asm volatile("mbarrier.arrive.shared::cluster.b64 _, [%0];" ::"r"(ra + off) : "memory"); };
    constexpr uint32_t NOBAR = 8 * (B_NONE - B_EMPTY);
    auto block = [&](auto ta, uint64_t da0, uint64_t db0, bool zero, int nn) {
      constexpr int PH = decltype(ta)::value, TA = PH > 0, KS = TA ? 128 : 2, QD = PH == 0 ? QD1 : PH == 1 ? QD2 : QD3;
      mbar_wait(bars + B_FULL * 8 + so, ph);
      const uint64_t da = da0 + (so << 8), db = db0 + (so << 8);
      wg_fence();
      wgmma_n128<TA>(d, da, db, !zero);
      wgmma_n128<TA>(d + 64, da + 512, db, !zero);
      wg_commit();
      wg_wait<1>();
      release(po);
#pragma unroll
      for (int k = 1; k < 4; k++) {
        if (QD == 2 || (QD == 4 && k == 2)) wg_fence();
        wgmma_n128<TA>(d, da + KS * k, db + 2 * k, 1);
        wgmma_n128<TA>(d + 64, da + 512 + KS * k, db + 2 * k, 1);
        if (QD == 2 || (QD == 4 && k == 1)) wg_commit();
        if ((QD == 2 && k < 3) || (QD == 4 && k == 1)) wg_wait<1>();
      }
      if (QD != 2) wg_commit();
      po = so;
      so += 8;
      if (so == 8 * STAGES) { so = 0; ph ^= 1; }
    };
    {
      so = wg ? 8 * (16 % STAGES) : 0; ph = wg ? (16 / STAGES) & 1 : 0; po = NOBAR;
      const uint64_t da0 = make_desc(sb + OFF_RING, 16, 1024, 1), db0 = make_desc(sb + OFF_RING + 16384, 16, 1024, 1);
      if (wg == 1) bar_sync(1, 256);
#pragma unroll 1
      for (int kb = 0; kb < 16; kb++) {
        block(std::integral_constant<int, 0>(), da0, db0, kb == 0, 16 * wg + kb);
      }
      asm volatile("bar.arrive %0, 256;" ::"r"(1 + wg) : "memory");
    }
    mbar_wait(bars + B_COEF * 8, 0);
    const uint32_t ca = sb + OFF_COEF + (64 * wg + 8 * w + g) * 16;
    const uint32_t tag = __shfl_sync(0xffffffffu, lds32(bars + B_EPOCH * 8) & 3, 0);
    constexpr int RE = SWAPB ? 2 : 0, IM = 2 - RE;
    const int ct = lane >> 3;
    const uint2* cp = g_carry + __shfl_sync(0xffffffffu, ((16 * wg + 2 * j) * 16 + tc - 1 - ct) * 32 + 8 * w + (lane & 7), lane);
    unsigned long long cv[4];
    auto load_carry = [&](int i) {
#pragma unroll
      for (int m = 0; m < 4; m++)
        asm volatile("{\n.reg .pred p;\nsetp.lt.s32 p, %2, %3;\n@p ld.relaxed.gpu.global.b64 %0, [%1];\n}\n" : "=l"(cv[m]) : "l"(cp + 512 * i - 128 * m), "r"(ct + 4 * m), "r"(tc) : "memory");
    };
    float lr[2], li[2], pr[2], pi[2], wr[2], wi[2], vr[2], vi[2], qr[2], qi[2], gr[2], gi[2];
#pragma unroll
    for (int i = 0; i < 2; i++) {
      const uint2 cf = lds64(ca + 512 * i);
      pr[i] = lr[i] = __uint_as_float(cf.x); pi[i] = li[i] = __uint_as_float(cf.y);
#pragma unroll
      for (int s = 0; s < 4; s++) csq(pr[i], pi[i]);
      gr[i] = pr[i]; gi[i] = pi[i];
      csq(pr[i], pi[i]);
      qr[i] = pr[i]; qi[i] = pi[i];
      csq(qr[i], qi[i]);
      asm volatile("" : "+f"(pr[i]), "+f"(pi[i]), "+f"(qr[i]), "+f"(qi[i]));
    }
    PMFENCE();
    wg_wait<0>();
    fence_regs<128>(d);
    release(po);
#pragma unroll
    for (int i = 0; i < 2; i++) {
      float* e = d + 64 * i;
      auto chain = [&](int s0, int s1, float& sr, float& si) {
        sr = e[2 * s0 + RE]; si = e[2 * s0 + IM];
#pragma unroll
        for (int s = s0 + 1; s < s1; s++) {
          const int ia = 4 * (s >> 1) + (s & 1);
          const float nr = fmaf(-li[i], si, fmaf(lr[i], sr, e[ia + RE])), ni = fmaf(li[i], sr, fmaf(lr[i], si, e[ia + IM]));
          sr = nr; si = ni;
        }
      };
      float sr, si;
      if ((GREEDY >> i) & 1) {
        float ar, ai;
        chain(0, 16, ar, ai); chain(16, 32, sr, si);
        sr = fmaf(gr[i], ar, fmaf(-gi[i], ai, sr)); si = fmaf(gr[i], ai, fmaf(gi[i], ar, si));
      } else chain(0, 32, sr, si);
      if (i == 1) { asm volatile("pmevent 0;" : "+f"(sr), "+f"(si)::"memory"); load_carry(0); }
      float ur = __shfl_up_sync(0xffffffffu, sr, 1, 4), ui = __shfl_up_sync(0xffffffffu, si, 1, 4);
      if (c >= 1) { sr = fmaf(pr[i], ur, fmaf(-pi[i], ui, sr)); si = fmaf(pr[i], ui, fmaf(pi[i], ur, si)); }
      ur = __shfl_up_sync(0xffffffffu, sr, 2, 4); ui = __shfl_up_sync(0xffffffffu, si, 2, 4);
      if (c >= 2) { sr = fmaf(qr[i], ur, fmaf(-qi[i], ui, sr)); si = fmaf(qr[i], ui, fmaf(qi[i], ur, si)); }
      ur = __shfl_sync(0xffffffffu, sr, 4 * lane + 3); ui = __shfl_sync(0xffffffffu, si, 4 * lane + 3);
      asm volatile("{\n.reg .pred p;\n.reg .b64 v;\nsetp.lt.u32 p, %3, 8;\nmov.b64 v, {%1,%2};\n@p st.relaxed.gpu.global.b64 [%0], v;\n}\n"
                   ::"l"(cp + 512 * i + 32), "r"((__float_as_uint(ur) & ~3u) | tag), "r"(__float_as_uint(ui)), "r"(lane) : "memory");
      PMFENCE();
      ur = __shfl_up_sync(0xffffffffu, sr, 1, 4); ui = __shfl_up_sync(0xffffffffu, si, 1, 4);
      if (c >= 1) { e[RE] = fmaf(lr[i], ur, fmaf(-li[i], ui, e[RE])); e[IM] = fmaf(lr[i], ui, fmaf(li[i], ur, e[IM])); }
      asm volatile("" : "+f"(e[RE]), "+f"(e[IM]));
    }
#pragma unroll
    for (int i = 0; i < 2; i++) {
      wr[i] = (c & 1) ? pr[i] : 1.f; wi[i] = (c & 1) ? pi[i] : 0.f;
      if (c & 2) { float x, y; cmul(wr[i], wi[i], qr[i], qi[i], x, y); wr[i] = x; wi[i] = y; }
      vr[i] = wr[i]; vi[i] = wi[i];
      csq(vr[i], vi[i]); csq(vr[i], vi[i]);
      csq(qr[i], qi[i]); csq(qr[i], qi[i]); csq(qr[i], qi[i]);
      const int src = 4 * (lane & 7) + ct;
      vr[i] = __shfl_sync(0xffffffffu, vr[i], src); vi[i] = __shfl_sync(0xffffffffu, vi[i], src);
      qr[i] = __shfl_sync(0xffffffffu, qr[i], src); qi[i] = __shfl_sync(0xffffffffu, qi[i], src);
    }
    uint4* hp = g_h + (32 * tc + 16 * wg + 2 * j) * 1024 + 64 * w + 4 * g + (c ^ (g >> 1));
#pragma unroll
    for (int i = 0; i < 2; i++) {
      float* e = d + 64 * i;
      PMFENCE();
      auto ready = [&]() {
        uint32_t bad = 0;
#pragma unroll
        for (int m = 0; m < 4; m++) if (ct + 4 * m < tc) bad |= (uint32_t)cv[m] ^ tag;
        return __all_sync(0xffffffffu, (bad & 3) == 0);
      };
      if (!ready()) {
        int n = 0;
#pragma unroll 1
        do load_carry(i); while (!ready() && ++n <= (SPIN_LIMIT << 4));
      }
      float hr = 0.f, hi = 0.f;
#pragma unroll
      for (int m = 3; m >= 0; m--) {
        const float x = __uint_as_float((uint32_t)cv[m]), y = __uint_as_float((uint32_t)(cv[m] >> 32));
        const float nr = m == 3 ? x : fmaf(qr[i], hr, fmaf(-qi[i], hi, x)), ni = m == 3 ? y : fmaf(qr[i], hi, fmaf(qi[i], hr, y));
        if (ct + 4 * m < tc) { hr = nr; hi = ni; }
      }
      { float x, y; cmul(hr, hi, vr[i], vi[i], x, y); hr = x; hi = y; }
      const uint4 cf = lds128(ca + 512 * i);
      lr[i] = __uint_as_float(cf.x); li[i] = __uint_as_float(cf.y);
      const uint32_t gp = cf.z, gms = cf.w;
      hr += __shfl_xor_sync(0xffffffffu, hr, 8); hi += __shfl_xor_sync(0xffffffffu, hi, 8);
      hr = __shfl_sync(0xffffffffu, hr, g) + __shfl_sync(0xffffffffu, hr, g + 16); hi = __shfl_sync(0xffffffffu, hi, g) + __shfl_sync(0xffffffffu, hi, g + 16);
      float sr, si;
      cmul(wr[i], wi[i], hr, hi, sr, si);
#pragma unroll
      for (int i8 = 0; i8 < 4; i8++) {
        asm volatile("pmevent 0;" : "+f"(sr), "+f"(si)::"memory");
        if (i == 0 && i8 == 1) load_carry(1);
#pragma unroll
        for (int s = 8 * i8; s < 8 * i8 + 8; s++) {
          const int ia = 4 * (s >> 1) + (s & 1);
          const float nr = fmaf(-li[i], si, fmaf(lr[i], sr, e[ia + RE])), ni = fmaf(li[i], sr, fmaf(lr[i], si, e[ia + IM]));
          sr = nr; si = ni;
          e[ia + RE] = nr; e[ia + IM] = ni;
        }
        uint32_t hp0[4], hp1[4];
#pragma unroll
        for (int m = 0; m < 4; m++) {
          const float* f = e + 16 * i8 + 4 * m;
          const uint32_t x = pack_bf16(f[RE], f[RE + 1]), y = pack_bf16(f[IM], f[IM + 1]);
          hp0[m] = bfma2(gp, x, bmul2(gms, y)); hp1[m] = bfnma2(gp, y, bmul2(gms, x));
        }
        uint4* o = hp + 512 * (i8 >> 1) + 256 * i + 32 * (i8 & 1);
        stg128(o, make_uint4(hp0[0], hp0[1], hp0[2], hp0[3]));
        stg128(o + 1024, make_uint4(hp1[0], hp1[1], hp1[2], hp1[3]));
      }
    }
    const int trow = 128 * tc + 64 * (w & 1) + 8 * (w >> 1) + g;
    const int dcol = 128 * j + 4 * c;
    asm volatile("bar.arrive %0, 160;" ::"r"(4 + wg) : "memory");
    if (wg == 0) {
      set_ra();
      {
        const uint32_t dt = sb + OFF_Q + 4096;
        mbar_wait(bars + (B_UF + 3) * 8, 0);
        const int n = t & 15, k = 2 * (n & 6) + 2 * (n >> 3) + (n & 1);
        const uint32_t dv = lds32(sb + OFF_DS + (t & ~15) * 4 + 4 * k) >> (16 - 16 * (k & 1));
#pragma unroll
        for (int u = 0; u < 2; u++) {
          const int m = (k >> 1) - 4 * u;
          sts128(dt + (t >> 4) * 512 + u * 256 + n * 16, make_uint4(m == 0 ? dv : 0, m == 1 ? dv : 0, m == 2 ? dv : 0, m == 3 ? dv : 0));
        }
        fence_proxy_async_smem();
        bar_sync(2, 256);
        mbar_wait(bars + (B_FULL + XPOS % STAGES) * 8, (XPOS / STAGES) & 1);
        const uint64_t dx = make_desc(sb + OFF_RING + (XPOS % STAGES) * STAGE_BYTES, 16, 1024, 1), dd = make_desc(dt, 256, 128, 0);
        wg_fence();
#pragma unroll
        for (int u = 0; u < 16; u++) ss_n16(d + 8 * u, dx + ((u >> 2) & 1) * 1024 + (u >> 3) * 512 + (u & 3) * 2, dd + (u & 7) * 32);
        wg_commit();
        wg_wait<0>();
        rename_regs<128>(d);
        release(8 * (XPOS % STAGES));
        if (t == 0) mbar_arrive(bars + B_XI * 8);
      }
      so = 8 * (33 % STAGES); ph = (33 / STAGES) & 1; po = NOBAR;
      const uint64_t da0 = make_desc(sb + OFF_RING + 16384, 512, 1024, 2), db0 = make_desc(sb + OFF_RING, 16, 1024, 1);
#pragma unroll 1
      for (int kb = 0; kb < QSW; kb++) block(std::integral_constant<int, 1>(), da0, db0, false, 32 + kb);
#pragma unroll 1
      for (int kb = QSW; kb < 32 - TAILB; kb++) block(std::integral_constant<int, 2>(), da0, db0, false, 32 + kb);
      float* op = P.out + (size_t)trow * 2048 + 1024 + dcol;
      auto mma = [&](int i, int kb, int k0, int k1) {
        const int s = (33 + kb) % STAGES;
        wg_fence();
#pragma unroll
        for (int k = k0; k < k1; k++) wgmma_n128<1>(d + 64 * i, da0 + s * 2048 + 512 * i + 128 * k, db0 + (i ? 0 : P.zero) + s * 2048 + 2 * k, 1);
        wg_commit();
      };
      auto store = [&](int i, int J0, int J1) {
#pragma unroll
        for (int J = J0; J < J1; J++) {
#pragma unroll
          for (int h = 0; h < 2; h++) {
            const float* e = d + 64 * i + 8 * J + 2 * h;
            stg128(op + (size_t)(16 * i + 32 * h) * 2048 + 16 * J, make_uint4(__float_as_uint(e[0]), __float_as_uint(e[1]), __float_as_uint(e[4]), __float_as_uint(e[5])));
          }
        }
        PMFENCE();
      };
      constexpr int K0 = 32 - TAILB;
#pragma unroll
      for (int kb = K0; kb < 32; kb++) {
        mbar_wait(bars + (B_FULL + (33 + kb) % STAGES) * 8, ((33 + kb) / STAGES) & 1);
        if (TAILB == 5 && kb == K0) { mma(0, kb, 0, 2); wg_wait<1>(); release(po); mma(0, kb, 2, 4); }
        else mma(0, kb, 0, 4);
      }
      mma(1, K0, 0, 4);
      wg_wait<1>();
      fence_regs<64>(d);
#pragma unroll
      for (int kb = K0 + 1; kb < 32; kb++) {
        mma(1, kb, 0, 4);
        store(0, T_ST * (kb - K0 - 1), kb == 31 ? 8 : T_ST * (kb - K0));
      }
      wg_wait<0>();
      fence_regs<64>(d + 64);
      store(1, 0, 8);
      if (t == 0) g_epoch[b * 32] = lds32(bars + B_EPOCH * 8);
      return;
    }
    asm volatile("setmaxnreg.dec.sync.aligned.u32 %0;" ::"n"(488 - 2 * GREG));
    fin_setup();
#pragma unroll
    for (int n = 0; n < 4; n += 2) {
      get_q(n, OFF_Q, B_QF, n >> 1);
      uint32_t dep = P.zero;
#pragma unroll
      for (int r = 0; r < 8; r++) dep &= q[n + (r >> 2)][r & 3].x;
      bar_sync(6 + dep, 128);
      if (w < 2 && elect_one()) load_q(5 + 2 * w - (n >> 1), OFF_Q, B_QF + n);
      __syncwarp();
    }
#pragma unroll 1
    for (int r = 0; r < 6; r++) mbar_wait(bars + (B_IN + r) * 8, 0);
    bar_sync(9, 256);
  }
  {
    const int w = warp & 3, h = wg & 1, lane = fl;
    const uint32_t ob0 = sb + (h ? OFF_F1 : OFF_K) + 1024 * w, ob1 = sb + (h ? OFF_VP : OFF_K + 4096) + 1024 * w;
    uint32_t y[2][8];
    auto get_y = [&](int n) { ldsm4t(y[n & 1], fa + n * fs); ldsm4t(y[n & 1] + 4, fa + n * fs + 32); };
    mbar_wait(bars + B_HR * 8, 1);
    mbar_wait(bars + (B_IN + 6) * 8, 0);
    get_y(0);
#pragma unroll
    for (int n = 0; n < 4; n++) {
      uint32_t* o = y[n & 1];
#pragma unroll
      for (int r = 0; r < 4; r++) { o[2 * r] = bmul2(o[2 * r], q[n][r].x); o[2 * r + 1] = bmul2(o[2 * r + 1], q[n][r].y); }
      if (n > 0 && lane == 0) asm volatile("cp.async.bulk.wait_group.read 0;" ::: "memory");
      __syncwarp();
#pragma unroll
      for (int r = 0; r < 4; r++)
        sts128((r & 2 ? ob1 : ob0) + (r & 1) * 512 + lane * 16, make_uint4(o[2 * r] << 16, o[2 * r] & 0xffff0000u, o[2 * r + 1] << 16, o[2 * r + 1] & 0xffff0000u));
      fence_proxy_async_smem();
      __syncwarp();
      if (lane == 0) {
#pragma unroll
        for (int u = 0; u < 2; u++)
          asm volatile("cp.async.bulk.tensor.3d.global.shared::cta.bulk_group [%0, {%2, %3, %4}], [%1];"
                       ::"l"(&mO), "r"(u ? ob1 : ob0), "r"(32 * slot), "r"(32 * rank + 8 * w), "r"(8 * n + 4 * h + 2 * u) : "memory");
        asm volatile("cp.async.bulk.commit_group;" ::: "memory");
      }
      __syncwarp();
      if (n < 3) get_y(n + 1);
      if (n == 1 && !h) get_q(2, OFF_Q, B_QF + 2, 0);
    }
    if (warp == 8 && lane == 0) mbar_arrive_cta(bars + B_ACK * 8, rank ^ 1);
    if (lane == 0) asm volatile("cp.async.bulk.wait_group 0;" ::: "memory");
    mbar_wait(bars + B_ACK * 8, 0);
  }
}

typedef CUresult (*EncodeFn)(CUtensorMap*, CUtensorMapDataType, cuuint32_t, void*, const cuuint64_t*, const cuuint64_t*, const cuuint32_t*,
                             const cuuint32_t*, CUtensorMapInterleave, CUtensorMapSwizzle, CUtensorMapL2promotion, CUtensorMapFloatOOBfill);

bool encode(EncodeFn fn, CUtensorMap* m, int rank, const void* base, const cuuint64_t* dims, const cuuint64_t* strides, const cuuint32_t* box, CUtensorMapSwizzle swz,
            CUtensorMapL2promotion promo = CU_TENSOR_MAP_L2_PROMOTION_L2_128B) {
  const cuuint32_t es[5] = {1, 1, 1, 1, 1};
  return fn(m, CU_TENSOR_MAP_DATA_TYPE_BFLOAT16, rank, const_cast<void*>(base), dims, strides, box, es, CU_TENSOR_MAP_INTERLEAVE_NONE, swz,
            promo, CU_TENSOR_MAP_FLOAT_OOB_FILL_NONE) == CUDA_SUCCESS;
}

}

extern "C" void kernel_launch(void* const* d_in, const int* in_sizes, int n_in, void* d_out, int out_size) {
  (void)in_sizes; (void)n_in; (void)out_size;
  typedef const __nv_bfloat16* In;
  const In q = (In)d_in[0], k = (In)d_in[1], v = (In)d_in[2], ssm_k = (In)d_in[4], x = (In)d_in[6], B_re = (In)d_in[9], B_im = (In)d_in[10], C_re = (In)d_in[11], C_im = (In)d_in[12];
  Params P = {};
  P.shift_k = (In)d_in[3]; P.ssm_D = (In)d_in[5]; P.lam_re = (In)d_in[7]; P.lam_im = (In)d_in[8]; P.log_dt = (In)d_in[13]; P.Dskip = (In)d_in[14];
  P.out = (float*)d_out;
  for (int cl = 0; cl < 64; cl++) P.slot[cl >> 2] |= (cl < 4 ? 4 + cl : cl < 36 ? 8 * ((cl - 4) & 7) + ((cl - 4) >> 3) : 8 * (1 + (cl - 36) % 7) + 4 + (cl - 36) / 7) << (8 * (cl & 3));
  const bool swapB = (uintptr_t)B_im < (uintptr_t)B_re;

  EncodeFn fn = nullptr;
  cudaDriverEntryPointQueryResult qr;
  cudaGetDriverEntryPoint("cuTensorMapEncodeTiled", (void**)&fn, cudaEnableDefault, &qr);
  if (!fn) return;

  CUtensorMap mX, mB, mCre, mCim, mXs, mK, mV, mQ, mS, mO;
  bool ok = true;
  {
    const cuuint64_t dims[4] = {1024, 2, 64, 16}, str[3] = {2048, 32 * 2048, 2 * 2048};
    const cuuint32_t box[4] = {64, 2, 4, 16};
    ok &= encode(fn, &mX, 4, x, dims, str, box, CU_TENSOR_MAP_SWIZZLE_128B);
  }
  {
    const uintptr_t lo = swapB ? (uintptr_t)B_im : (uintptr_t)B_re, hi = swapB ? (uintptr_t)B_re : (uintptr_t)B_im;
    const cuuint64_t dims[4] = {1024, 8, 2, 128}, str[3] = {2048, (cuuint64_t)(hi - lo), 8 * 2048};
    const cuuint32_t box[4] = {64, 8, 2, 4};
    ok &= encode(fn, &mB, 4, (const void*)lo, dims, str, box, CU_TENSOR_MAP_SWIZZLE_128B);
  }
  {
    const cuuint64_t dims[5] = {1024, 2, 4, 2, 64}, str[4] = {2048, 4 * 2048, 2 * 2048, 16 * 2048};
    const cuuint32_t box[5] = {64, 2, 4, 2, 4};
    ok &= encode(fn, &mCre, 5, C_re, dims, str, box, CU_TENSOR_MAP_SWIZZLE_128B);
    ok &= encode(fn, &mCim, 5, C_im, dims, str, box, CU_TENSOR_MAP_SWIZZLE_128B);
  }
  {
    const cuuint64_t dims[4] = {1024, 8, 64, 4}, str[3] = {2048, 32 * 2048, 8 * 2048};
    const cuuint32_t box[4] = {64, 8, 4, 4};
    ok &= encode(fn, &mXs, 4, x, dims, str, box, CU_TENSOR_MAP_SWIZZLE_128B);
  }
  {
    const cuuint64_t dims[3] = {1024, 64, 32}, str[2] = {32 * 2048, 2048};
    const cuuint32_t box[3] = {16, 32, 4};
    const cuuint64_t dimq[4] = {1024, 8, 32, 8}, strq[3] = {32 * 2048, 2048, 256 * 2048};
    const cuuint32_t boxq[4] = {16, 8, 4, 4};
    ok &= encode(fn, &mQ, 4, q, dimq, strq, boxq, CU_TENSOR_MAP_SWIZZLE_NONE);
    ok &= encode(fn, &mK, 3, k, dims, str, box, CU_TENSOR_MAP_SWIZZLE_32B);
    ok &= encode(fn, &mV, 3, v, dims, str, box, CU_TENSOR_MAP_SWIZZLE_32B);
  }
  {
    const cuuint64_t dims[2] = {32, 65536}, str[1] = {64};
    const cuuint32_t box[2] = {32, 64};
    ok &= encode(fn, &mS, 2, ssm_k, dims, str, box, CU_TENSOR_MAP_SWIZZLE_64B);
  }
  {
    const cuuint64_t dims[3] = {2048, 64, 32}, str[2] = {32 * 8192, 8192};
    const cuuint32_t box[3] = {32, 8, 2};
    ok &= encode(fn, &mO, 3, d_out, dims, str, box, CU_TENSOR_MAP_SWIZZLE_NONE);
  }
  if (!ok) return;
  auto kern = swapB ? fused_kernel<1> : fused_kernel<0>;
  cudaFuncSetAttribute(kern, cudaFuncAttributeMaxDynamicSharedMemorySize, SMEM_BYTES);
  kern<<<NCTA, 512, SMEM_BYTES, cudaStreamPerThread>>>(P, mX, mB, mCre, mCim, mXs, mK, mV, mQ, mS, mO);
}
```

```cpp
#include <cuda_runtime.h>
#include <cuda_bf16.h>
#include <cuda.h>
#include <stdint.h>
#include <type_traits>

namespace {

constexpr int D_DIM = 1024;
constexpr int NCTA = 128;

constexpr int STAGES = 5, STAGE_BYTES = 32768;
constexpr int OFF_RING = 0;
constexpr int OFF_F1 = STAGES * STAGE_BYTES, OFF_F2 = OFF_F1 + 4096, OFF_K = OFF_F2 + 2048, OFF_VP = OFF_K + 8192, OFF_Q = OFF_VP + 4096, OFF_IN = OFF_Q + 8192;
constexpr int OFF_KV = OFF_K;
constexpr int U_CH = 528, U_N8 = 8 * U_CH, OFF_U = OFF_IN + U_N8;
constexpr int OFF_COEF = OFF_U + 8 * U_N8;
constexpr int OFF_DS = OFF_COEF + 2048, OFF_D = OFF_DS + 512;
constexpr int OFF_BAR = OFF_D + 64;
constexpr int SMEM_BYTES = OFF_BAR + 512;
static_assert(SMEM_BYTES <= 232448 && OFF_K % 1024 == 0 && (OFF_U + 3 * U_N8) % 512 == 0 && (4 * U_N8) % 512 == 0, "smem map");
constexpr int B_FULL = 0, B_XI = 5, B_HR = 6, B_HP = 7, B_KVF = 8, B_QF = 11, B_IN = 15, B_UF = 23, B_ACK = 27, B_KF = 28, B_ST = 38,
              B_EMPTY = 45, B_COEF = 50, B_KVE = 51, B_NONE = 54, B_EPOCH = 55;

constexpr int QD1 = 8;
constexpr int QD2 = 2;
constexpr int QD3 = 8;
constexpr int QSW = 16;
constexpr int HEAD = 3;
constexpr int ST_T0 = 200;
constexpr int ST_DELAY = 300;
constexpr int XPOS = 32;
constexpr int K_T0 = 800;
constexpr int KV_T0 = 1500;
constexpr int KV_DT = 620;
constexpr int KV_DV = 450;
constexpr int POLL_NS = 30;
constexpr int GREEDY = 1;
constexpr int TAILB = 5;
constexpr int GREG = 168;
constexpr int COEF_T0 = 2500;
constexpr int T_ST = 2;
constexpr int PFC_T0 = 13500;
constexpr int PFC_T1 = 1500;
constexpr int PFC_DT = 400;
constexpr int KV_E = 6;
constexpr int KV_D2 = 300;
constexpr int CFM = 0x40f1;
constexpr int SPIN_LIMIT = 1 << 14;

struct Params {
  unsigned slot[16];
  unsigned zero;
  const __nv_bfloat16 *shift_k, *ssm_D, *lam_re, *lam_im, *log_dt, *Dskip;
  float* out;
};

__device__ __align__(1024) uint4 g_h[16 * 32 * 1024];
__device__ __align__(128) uint2 g_carry[32 * 16 * 32];
__device__ unsigned g_flagH[2 * 16 * 32];
__device__ unsigned g_epoch[NCTA * 32];

__device__ __forceinline__ uint64_t make_desc(uint32_t addr, uint32_t lbo, uint32_t sbo, uint32_t swz) {
  return (uint64_t)((addr & 0x3FFFF) >> 4) | ((uint64_t)(lbo >> 4) << 16) | ((uint64_t)(sbo >> 4) << 32) | ((uint64_t)swz << 62);
}
__device__ __forceinline__ void wg_fence() { asm volatile("wgmma.fence.sync.aligned;" ::: "memory"); }
__device__ __forceinline__ void wg_commit() { asm volatile("wgmma.commit_group.sync.aligned;" ::: "memory"); }
template <int N> __device__ __forceinline__ void wg_wait() { asm volatile("wgmma.wait_group.sync.aligned %0;" ::"n"(N) : "memory"); }
__device__ __forceinline__ void mbar_init(uint32_t bar, int cnt) { asm volatile("mbarrier.init.shared::cta.b64 [%0], %1;" ::"r"(bar), "r"(cnt) : "memory"); }
__device__ __forceinline__ void mbar_expect(uint32_t bar, uint32_t bytes) { asm volatile("mbarrier.arrive.expect_tx.shared::cta.b64 _, [%0], %1;" ::"r"(bar), "r"(bytes) : "memory"); }
__device__ __forceinline__ bool mbar_try(uint32_t bar, uint32_t parity) {
  uint32_t ok;
  asm volatile("{\n.reg .pred p;\nmbarrier.try_wait.parity.shared::cta.b64 p, [%1], %2;\nselp.u32 %0, 1, 0, p;\n}\n" : "=r"(ok) : "r"(bar), "r"(parity) : "memory");
  return ok;
}
__device__ __forceinline__ void mbar_wait(uint32_t bar, uint32_t parity) {
  if (__builtin_expect(!mbar_try(bar, parity), 0)) {
#pragma unroll 1
    for (int n = 0; n < SPIN_LIMIT && !mbar_try(bar, parity); n++) {}
  }
}
__device__ __forceinline__ void mbar_arrive(uint32_t bar) { asm volatile("mbarrier.arrive.shared::cta.b64 _, [%0];" ::"r"(bar) : "memory"); }
__device__ __forceinline__ void mbar_arrive_cta(uint32_t bar, uint32_t cta) {
  asm volatile("{\n.reg .b32 ra;\nmapa.shared::cluster.u32 ra, %0, %1;\nmbarrier.arrive.shared::cluster.b64 _, [ra];\n}\n" ::"r"(bar), "r"(cta) : "memory");
}
__device__ __forceinline__ bool elect_one() {
  uint32_t p;
  asm volatile("{\n.reg .pred P;\nelect.sync _|P, 0xffffffff;\nselp.u32 %0, 1, 0, P;\n}\n" : "=r"(p));
  return p != 0;
}
__device__ __forceinline__ void bar_sync(int id, int n) { asm volatile("bar.sync %0, %1;" ::"r"(id), "r"(n) : "memory"); }
#define TMA_LD(dim) "cp.async.bulk.tensor." dim ".shared::cluster.global.mbarrier::complete_tx::bytes"
__device__ __forceinline__ void tma2d(uint32_t dst, const CUtensorMap* m, int c0, int c1, uint32_t bar) {
  asm volatile(TMA_LD("2d") " [%0], [%1, {%3, %4}], [%2];" ::"r"(dst), "l"(m), "r"(bar), "r"(c0), "r"(c1) : "memory");
}
__device__ __forceinline__ void tma3d(uint32_t dst, const CUtensorMap* m, int c0, int c1, int c2, uint32_t bar) {
  asm volatile(TMA_LD("3d") " [%0], [%1, {%3, %4, %5}], [%2];" ::"r"(dst), "l"(m), "r"(bar), "r"(c0), "r"(c1), "r"(c2) : "memory");
}
__device__ __forceinline__ void tma4d(uint32_t dst, const CUtensorMap* m, int c0, int c1, int c2, int c3, uint32_t bar) {
  asm volatile(TMA_LD("4d") " [%0], [%1, {%3, %4, %5, %6}], [%2];" ::"r"(dst), "l"(m), "r"(bar), "r"(c0), "r"(c1), "r"(c2), "r"(c3) : "memory");
}
__device__ __forceinline__ void tma4d_mc(uint32_t dst, const CUtensorMap* m, int c0, int c1, int c2, int c3, uint32_t bar) {
  asm volatile(TMA_LD("4d") ".multicast::cluster [%0], [%1, {%3, %4, %5, %6}], [%2], %7;" ::"r"(dst), "l"(m), "r"(bar), "r"(c0), "r"(c1), "r"(c2), "r"(c3), "h"((uint16_t)3) : "memory");
}
__device__ __forceinline__ void tma5d_mc(uint32_t dst, const CUtensorMap* m, int c0, int c1, int c2, int c3, int c4, uint32_t bar) {
  asm volatile(TMA_LD("5d") ".multicast::cluster [%0], [%1, {%3, %4, %5, %6, %7}], [%2], %8;" ::"r"(dst), "l"(m), "r"(bar), "r"(c0), "r"(c1), "r"(c2), "r"(c3), "r"(c4), "h"((uint16_t)3) : "memory");
}
__device__ __forceinline__ void bulk_load(uint32_t dst, const void* src, uint32_t bytes, uint32_t bar) {
  asm volatile("cp.async.bulk.shared::cluster.global.mbarrier::complete_tx::bytes [%0], [%1], %2, [%3];" ::"r"(dst), "l"(src), "r"(bytes), "r"(bar) : "memory");
}
__device__ __forceinline__ void bulk_send(uint32_t dst, uint32_t src, uint32_t bytes, uint32_t bar, uint32_t cta) {
  asm volatile("{\n.reg .b32 rd, rb;\nmapa.shared::cluster.u32 rd, %0, %3;\nmapa.shared::cluster.u32 rb, %2, %3;\n"
               "cp.async.bulk.shared::cluster.shared::cta.mbarrier::complete_tx::bytes [rd], [%1], %4, [rb];\n}\n"
               ::"r"(dst), "r"(src), "r"(bar), "r"(cta), "r"(bytes) : "memory");
}
__device__ __forceinline__ void fence_proxy_async_smem() { asm volatile("fence.proxy.async.shared::cta;" ::: "memory"); }
__device__ __forceinline__ void fence_proxy_async_global() { asm volatile("fence.proxy.async.global;" ::: "memory"); }
__device__ __forceinline__ uint32_t clk32() { uint32_t c; asm volatile("mov.u32 %0, %%clock;" : "=r"(c)::"memory"); return c; }
__device__ __forceinline__ void wait_until(uint32_t t0, uint32_t dt) { while (clk32() - t0 < dt) __nanosleep(32); }
__device__ __forceinline__ void spin_until(uint32_t t0, uint32_t dt) { while (clk32() - t0 < dt) {} }
__device__ __forceinline__ void prefetch_map(const CUtensorMap* m) { asm volatile("prefetch.tensormap [%0];" ::"l"(m) : "memory"); }
__device__ __forceinline__ void prefetch_line(const void* p) { asm volatile("prefetch.global.L2 [%0];" ::"l"(p) : "memory"); }
__device__ __forceinline__ unsigned ld_acquire(const unsigned* p) { unsigned v; asm volatile("ld.acquire.gpu.global.u32 %0, [%1];" : "=r"(v) : "l"(p) : "memory"); return v; }
__device__ __forceinline__ unsigned ld_relaxed(const unsigned* p) { unsigned v; asm volatile("ld.relaxed.gpu.global.u32 %0, [%1];" : "=r"(v) : "l"(p) : "memory"); return v; }
__device__ __forceinline__ uint32_t lds32(uint32_t a) { uint32_t v; asm volatile("ld.shared.u32 %0, [%1];" : "=r"(v) : "r"(a)); return v; }
__device__ __forceinline__ uint2 lds64(uint32_t a) { uint2 v; asm volatile("ld.shared.v2.u32 {%0,%1}, [%2];" : "=r"(v.x), "=r"(v.y) : "r"(a) : "memory"); return v; }
__device__ __forceinline__ uint4 lds128(uint32_t a) { uint4 v; asm volatile("ld.shared.v4.u32 {%0,%1,%2,%3}, [%4];" : "=r"(v.x), "=r"(v.y), "=r"(v.z), "=r"(v.w) : "r"(a) : "memory"); return v; }
__device__ __forceinline__ void sts32(uint32_t a, uint32_t v) { asm volatile("st.shared.u32 [%0], %1;" ::"r"(a), "r"(v) : "memory"); }
__device__ __forceinline__ void sts128(uint32_t a, uint4 v) { asm volatile("st.shared.v4.u32 [%0], {%1,%2,%3,%4};" ::"r"(a), "r"(v.x), "r"(v.y), "r"(v.z), "r"(v.w) : "memory"); }
__device__ __forceinline__ void ldsm4(uint32_t* r, uint32_t a) { asm volatile("ldmatrix.sync.aligned.m8n8.x4.shared.b16 {%0,%1,%2,%3}, [%4];" : "=r"(r[0]), "=r"(r[1]), "=r"(r[2]), "=r"(r[3]) : "r"(a) : "memory"); }
__device__ __forceinline__ void ldsm4t(uint32_t* r, uint32_t a) { asm volatile("ldmatrix.sync.aligned.m8n8.x4.trans.shared.b16 {%0,%1,%2,%3}, [%4];" : "=r"(r[0]), "=r"(r[1]), "=r"(r[2]), "=r"(r[3]) : "r"(a) : "memory"); }
__device__ __forceinline__ void stsm4t(uint32_t a, uint32_t r0, uint32_t r1, uint32_t r2, uint32_t r3) {
  asm volatile("stmatrix.sync.aligned.m8n8.x4.trans.shared.b16 [%0], {%1,%2,%3,%4};" ::"r"(a), "r"(r0), "r"(r1), "r"(r2), "r"(r3) : "memory");
}
__device__ __forceinline__ uint4 ldg128_nc(const void* p) { uint4 v; asm volatile("ld.global.nc.L1::no_allocate.v4.u32 {%0,%1,%2,%3}, [%4];" : "=r"(v.x), "=r"(v.y), "=r"(v.z), "=r"(v.w) : "l"(p)); return v; }
__device__ __forceinline__ void stg128(void* p, uint4 v) { asm volatile("st.global.L1::no_allocate.v4.u32 [%0], {%1,%2,%3,%4};" ::"l"(p), "r"(v.x), "r"(v.y), "r"(v.z), "r"(v.w) : "memory"); }
__device__ __forceinline__ uint32_t pack_bf16(float lo, float hi) { uint32_t r; asm("cvt.rn.bf16x2.f32 %0, %1, %2;" : "=r"(r) : "f"(hi), "f"(lo)); return r; }
__device__ __forceinline__ uint32_t bmul2(uint32_t a, uint32_t b) { uint32_t r; asm("mul.rn.bf16x2 %0, %1, %2;" : "=r"(r) : "r"(a), "r"(b)); return r; }
__device__ __forceinline__ uint32_t bfma2(uint32_t a, uint32_t b, uint32_t c) { uint32_t r; asm("fma.rn.bf16x2 %0, %1, %2, %3;" : "=r"(r) : "r"(a), "r"(b), "r"(c)); return r; }
__device__ __forceinline__ uint32_t blo2(uint32_t a) { uint32_t r; asm("{\n.reg .b16 l, h;\nmov.b32 {l, h}, %1;\nmov.b32 %0, {l, l};\n}" : "=r"(r) : "r"(a)); return r; }
__device__ __forceinline__ float bf2f(__nv_bfloat16 v) { return __bfloat162float(v); }

#define R8(d, o) "+f"(d[o]), "+f"(d[o + 1]), "+f"(d[o + 2]), "+f"(d[o + 3]), "+f"(d[o + 4]), "+f"(d[o + 5]), "+f"(d[o + 6]), "+f"(d[o + 7])
#define R16(d, o) R8(d, o), R8(d, o + 8)
#define R64(d, o) R16(d, o), R16(d, o + 16), R16(d, o + 32), R16(d, o + 48)
template <int TA> __device__ __forceinline__ void wgmma_n128(float* d, uint64_t da, uint64_t db, int scale_d) {
  asm volatile("{\n.reg .pred p;\nsetp.ne.b32 p, %66, 0;\n"
    "wgmma.mma_async.sync.aligned.m64n128k16.f32.bf16.bf16 {"
    "%0,%1,%2,%3,%4,%5,%6,%7,%8,%9,%10,%11,%12,%13,%14,%15,%16,%17,%18,%19,%20,%21,%22,%23,%24,%25,%26,%27,%28,%29,%30,%31,"
    "%32,%33,%34,%35,%36,%37,%38,%39,%40,%41,%42,%43,%44,%45,%46,%47,%48,%49,%50,%51,%52,%53,%54,%55,%56,%57,%58,%59,%60,%61,%62,%63"
    "}, %64, %65, p, 1, 1, %67, 0;\n}\n"
    : R64(d, 0)
    : "l"(da), "l"(db), "r"(scale_d), "n"(TA));
}
template <int N> __device__ __forceinline__ void fence_regs(float* d) {
#pragma unroll
  for (int i = 0; i < N; i++) asm volatile("" : "+f"(d[i])::"memory");
}
#define PMFENCE() asm volatile("pmevent 0;" ::: "memory")
__device__ __forceinline__ void cmul(float ar, float ai, float br, float bi, float& cr, float& ci) {
  cr = ar * br - ai * bi; ci = ar * bi + ai * br;
}
__device__ __forceinline__ void csq(float& r, float& i) { const float x = fmaf(r, r, -i * i), y = r * i; r = x; i = y + y; }

#define W8(d, o) "=f"(d[o]), "=f"(d[o + 1]), "=f"(d[o + 2]), "=f"(d[o + 3]), "=f"(d[o + 4]), "=f"(d[o + 5]), "=f"(d[o + 6]), "=f"(d[o + 7])
#define L16 "{%0,%1,%2,%3,%4,%5,%6,%7,%8,%9,%10,%11,%12,%13,%14,%15}"
#define L32 "{%0,%1,%2,%3,%4,%5,%6,%7,%8,%9,%10,%11,%12,%13,%14,%15,%16,%17,%18,%19,%20,%21,%22,%23,%24,%25,%26,%27,%28,%29,%30,%31}"
template <int ACC, int TB> __device__ __forceinline__ void rs_n32(float* d, const uint32_t* a, uint64_t db) {
  if constexpr (ACC) asm volatile("wgmma.mma_async.sync.aligned.m64n32k16.f32.bf16.bf16 " L16 ", {%16,%17,%18,%19}, %20, 1, 1, 1, %21;" : R16(d, 0) : "r"(a[0]), "r"(a[1]), "r"(a[2]), "r"(a[3]), "l"(db), "n"(TB));
  else asm volatile("wgmma.mma_async.sync.aligned.m64n32k16.f32.bf16.bf16 " L16 ", {%16,%17,%18,%19}, %20, 0, 1, 1, %21;" : W8(d, 0), W8(d, 8) : "r"(a[0]), "r"(a[1]), "r"(a[2]), "r"(a[3]), "l"(db), "n"(TB));
}
template <int ACC, int TB> __device__ __forceinline__ void rs_n64(float* d, const uint32_t* a, uint64_t db) {
  if constexpr (ACC) asm volatile("wgmma.mma_async.sync.aligned.m64n64k16.f32.bf16.bf16 " L32 ", {%32,%33,%34,%35}, %36, 1, 1, 1, %37;" : R16(d, 0), R16(d, 16) : "r"(a[0]), "r"(a[1]), "r"(a[2]), "r"(a[3]), "l"(db), "n"(TB));
  else asm volatile("wgmma.mma_async.sync.aligned.m64n64k16.f32.bf16.bf16 " L32 ", {%32,%33,%34,%35}, %36, 0, 1, 1, %37;" : W8(d, 0), W8(d, 8), W8(d, 16), W8(d, 24) : "r"(a[0]), "r"(a[1]), "r"(a[2]), "r"(a[3]), "l"(db), "n"(TB));
}
template <int ACC> __device__ __forceinline__ void ss_n32_tt(float* d, uint64_t da, uint64_t db) {
  if constexpr (ACC) asm volatile("wgmma.mma_async.sync.aligned.m64n32k16.f32.bf16.bf16 " L16 ", %16, %17, 1, 1, 1, 1, 1;" : R16(d, 0) : "l"(da), "l"(db));
  else asm volatile("wgmma.mma_async.sync.aligned.m64n32k16.f32.bf16.bf16 " L16 ", %16, %17, 0, 1, 1, 1, 1;" : W8(d, 0), W8(d, 8) : "l"(da), "l"(db));
}
__device__ __forceinline__ void stsm4(uint32_t a, uint32_t r0, uint32_t r1, uint32_t r2, uint32_t r3) {
  asm volatile("stmatrix.sync.aligned.m8n8.x4.shared.b16 [%0], {%1,%2,%3,%4};" ::"r"(a), "r"(r0), "r"(r1), "r"(r2), "r"(r3) : "memory");
}
template <int N> __device__ __forceinline__ void fence_u32(uint32_t* d) {
#pragma unroll
  for (int i = 0; i < N; i++) asm volatile("" : "+r"(d[i])::"memory");
}
__device__ __forceinline__ void pack32(uint32_t* f, const float* z) {
#pragma unroll
  for (int i = 0; i < 16; i++) f[i] = pack_bf16(z[2 * i], z[2 * i + 1]);
}
template <int INV> __device__ __forceinline__ void twiddle(uint32_t* f, const uint32_t* tp, const uint32_t* ts) {
#pragma unroll
  for (int i = 0; i < 8; i++) {
    uint32_t x = f[2 * i + INV], y = f[2 * i + 1 - INV];
    x = bfma2(tp[i & 3], y, x); y = bfma2(ts[i & 3], x, y); x = bfma2(tp[i & 3], y, x);
    f[2 * i + INV] = x; f[2 * i + 1 - INV] = y;
  }
}
__device__ __forceinline__ uint32_t bfnma2(uint32_t a, uint32_t b, uint32_t c) { uint32_t r; asm("{\n.reg .b32 t;\nmul.bf16x2 t, %1, %2;\nsub.bf16x2 %0, %3, t;\n}" : "=r"(r) : "r"(a), "r"(b), "r"(c)); return r; }
__device__ __forceinline__ uint32_t bfms2(uint32_t a, uint32_t b, uint32_t c) { uint32_t r; asm("{\n.reg .b32 t;\nmul.bf16x2 t, %1, %2;\nsub.bf16x2 %0, t, %3;\n}" : "=r"(r) : "r"(a), "r"(b), "r"(c)); return r; }
template <int ADD> __device__ __forceinline__ void bimac(uint32_t* o, const uint32_t* a, const uint32_t* b, const uint32_t* c) {
#pragma unroll
  for (int J = 0; J < 2; J++) {
    const uint32_t Pr = a[2 * J], Pi = a[2 * J + 1], Qr = a[2 * J + 4], Qi = a[2 * J + 5], pr = b[2 * J], pi = b[2 * J + 1], qr = b[2 * J + 4], qi = b[2 * J + 5];
    uint32_t x0, x1, x2, x3;
    if (ADD == 0) { x0 = bmul2(Pr, pr); x1 = bmul2(Pr, pi); x2 = bmul2(Pr, qr); x3 = bmul2(Pr, qi); }
    if (ADD == 1) { x0 = bfma2(Pr, pr, c[2 * J]); x1 = bfma2(Pr, pi, c[2 * J + 1]); x2 = bfma2(Pr, qr, c[2 * J + 4]); x3 = bfma2(Pr, qi, c[2 * J + 5]); }
    if (ADD == 2) { x0 = bfma2(Pr, pr, c[2 * J + 1]); x1 = bfms2(Pr, pi, c[2 * J]); x2 = bfma2(Pr, qr, c[2 * J + 5]); x3 = bfms2(Pr, qi, c[2 * J + 4]); }
    x0 = bfnma2(Pi, pi, x0); x1 = bfma2(Pi, pr, x1); x2 = bfnma2(Pi, qi, x2); x3 = bfma2(Pi, qr, x3);
    x0 = bfnma2(Qr, qr, x0); x1 = bfnma2(Qr, qi, x1); x2 = bfma2(Qr, pr, x2); x3 = bfma2(Qr, pi, x3);
    x0 = bfma2(Qi, qi, x0); x1 = bfnma2(Qi, qr, x1); x2 = bfnma2(Qi, pi, x2); x3 = bfma2(Qi, pr, x3);
    o[2 * J] = x0; o[2 * J + 1] = x1; o[2 * J + 4] = x2; o[2 * J + 5] = x3;
  }
}
__device__ __forceinline__ void sincos8k(int n, float& s, float& c) {
  const float x = (float)((n << 19) >> 19) * (6.283185307179586f / 8192.f);
  s = __sinf(x); c = __cosf(x);
}
__device__ __forceinline__ void fft_tables(uint32_t f1a, uint32_t f2a, int w, int lane, uint32_t* tp, uint32_t* ts, float& d0r, float& d0i) {
  const int c = lane & 3, f1 = 8 * w + (lane >> 2);
#pragma unroll 1
  for (int J = 3; J >= 0; J--) {
    const int a = 8 * J + 2 * c;
    float s0, c0, s1, c1;
    sincos8k(64 * (4 * f1 + 1) * a + 31 * (4 * f1 - 63), d0i, d0r); sincos8k(64 * (4 * f1 + 1) * (a + 1) + 31 * (4 * f1 - 63), s1, c1);
    d0r *= 0.125f; d0i *= 0.125f;
    sts32(f1a + w * 1024 + J * 128 + lane * 4, pack_bf16(d0r, 0.125f * c1)); sts32(f1a + w * 1024 + 512 + J * 128 + lane * 4, pack_bf16(d0i, 0.125f * s1));
    sincos8k(128 * (2 * (a & 15) + 1) * f1 - 128 * (a & 16), s0, c0); sincos8k(128 * (2 * (a & 15) + 3) * f1 - 128 * (a & 16), s1, c1);
    sts32(f2a + w * 512 + J * 128 + lane * 4, pack_bf16(c0, c1));
    sincos8k((4 * f1 - 63) * (2 * a - 31), s0, c0); sincos8k((4 * f1 - 63) * (2 * a - 29), s1, c1);
#pragma unroll
    for (int i = 3; i > 0; i--) { ts[i] = ts[i - 1]; tp[i] = tp[i - 1]; }
    ts[0] = pack_bf16(s0, s1); tp[0] = pack_bf16(-__fdividef(s0, 1.f + c0), -__fdividef(s1, 1.f + c1));
  }
  if (c != 0) d0r = d0i = 0.f;
}

__device__ __forceinline__ void ss_n16_in(float* d, uint64_t da, uint64_t db, uint32_t zero) {
  asm volatile("{\n.reg .pred p;\nsetp.ne.b32 p, %10, 0;\nwgmma.mma_async.sync.aligned.m64n16k16.f32.bf16.bf16 {%0,%1,%2,%3,%4,%5,%6,%7}, %8, %9, p, 1, 1, 0, 0;\n}\n" : R8(d, 0) : "l"(da), "l"(db), "r"(zero));
}
__device__ __forceinline__ void ss_n16(float* d, uint64_t da, uint64_t db) {
  asm volatile("wgmma.mma_async.sync.aligned.m64n16k16.f32.bf16.bf16 {%0,%1,%2,%3,%4,%5,%6,%7}, %8, %9, 0, 1, 1, 0, 0;" : W8(d, 0) : "l"(da), "l"(db));
}
template <int N> __device__ __forceinline__ void rename_regs(float* d) {
#pragma unroll
  for (int i = 0; i < N; i++) { float t; asm volatile("mov.b32 %0, %1;" : "=f"(t) : "f"(d[i]) : "memory"); d[i] = t; }
}

template <int SWAPB>
__global__ void __cluster_dims__(2, 1, 1) __launch_bounds__(512, 1)
fused_kernel(const __grid_constant__ Params P, const __grid_constant__ CUtensorMap mX, const __grid_constant__ CUtensorMap mB,
             const __grid_constant__ CUtensorMap mCre, const __grid_constant__ CUtensorMap mCim, const __grid_constant__ CUtensorMap mXs,
             const __grid_constant__ CUtensorMap mK, const __grid_constant__ CUtensorMap mV, const __grid_constant__ CUtensorMap mQ, const __grid_constant__ CUtensorMap mS,
             const __grid_constant__ CUtensorMap mO) {
  extern __shared__ __align__(1024) uint8_t smem_raw[];
  if (threadIdx.x == 0) { prefetch_map(&mX); prefetch_map(&mB); }
  const uint32_t sb = (uint32_t)__cvta_generic_to_shared(smem_raw);
  const uint32_t bars = sb + OFF_BAR;
  const int slot = (P.slot[blockIdx.x >> 3] >> (4 * (blockIdx.x & 6))) & 63, rank = blockIdx.x & 1;
  const int j = slot & 7, tc = 2 * (slot >> 3) + rank, b = 2 * slot + rank;
  const int tid = threadIdx.x;
  const int warp = __shfl_sync(0xffffffffu, tid >> 5, 0);
  const int wg = warp >> 2;
  const uint32_t c_start = clk32();
  auto kblock = [&](int n) { return ((n & 14) == 0 || (n & 14) == 2 * j ? n ^ (2 * j) : n) & 31; };
  auto send_y = [&](int r) {
    const uint32_t src = sb + OFF_U + 4 * (rank ^ 1) * U_N8 + r * U_CH, dst = r >= 2 ? sb + OFF_U + 4 * rank * U_N8 + (r - 2) * U_CH : sb + OFF_IN + 96 + r * 2064;
#pragma unroll 1
    for (int n = 0; n < 4; n++) bulk_send(dst + n * (r >= 2 ? U_N8 : 512), src + n * U_N8, 512, bars + (B_IN + r) * 8, rank ^ 1);
  };
  auto load_q = [&](int i, int off, int bar) {
    const uint32_t fb = bars + bar * 8 + 4 * (i & 2);
    mbar_expect(fb, 4096); tma4d(sb + off + 2048 * (i & 2), &mQ, 16 * slot, 0, 4 * i, 4 * rank, fb);
  };
  auto head = [&](int n) {
    const uint32_t fb = bars + (B_FULL + n) * 8, dst = sb + OFF_RING + n * STAGE_BYTES;
    mbar_expect(fb, STAGE_BYTES);
    tma4d(dst + 16384, &mX, 64 * n, 0, 4 * tc, 0, fb);
    tma4d(dst, &mB, 64 * n, 0, 0, 8 * j, fb);
    tma4d(dst + 8192, &mB, 64 * n, 0, 0, 8 * j + 4, fb);
  };
  if (warp == 0 && elect_one()) {
#pragma unroll
    for (int s = 0; s < STAGES; s++) mbar_init(bars + (B_FULL + s) * 8, 1);
    head(0);
    asm volatile("fence.mbarrier_init.release.cluster;" ::: "memory");
  }
  if (wg == 3 && elect_one()) {
    if (warp < 15) {
#pragma unroll
      for (int s = 0; s < 13; s++) mbar_init(bars + 8 * B_XI + (warp & 3) * 104 + 8 * s, 1);
    } else {
#pragma unroll
      for (int s = B_XI + 39; s <= B_NONE; s++) mbar_init(bars + 8 * s, s < B_EMPTY ? 1 : s < B_COEF ? 2 : s == B_COEF ? 128 : 4);
    }
    asm volatile("fence.mbarrier_init.release.cluster;" ::: "memory");
  }
  __syncwarp();
  asm volatile("barrier.cluster.arrive.relaxed.aligned;" ::: "memory");
  if (warp == 0 && elect_one()) {
#pragma unroll 1
    for (int n = 1; n < HEAD; n++) { spin_until(c_start, ST_T0 + n * ST_DELAY); head(n); }
  }
  __syncwarp();
  int fl;
  uint32_t fa, fs;
  uint2 q[4][4];
  auto fin_setup = [&]() {
    asm volatile("mov.u32 %0, %%laneid;" : "=r"(fl));
    const int lc = 2 * (fl & 2) + (fl & 1) + ((fl >> 2) & 2);
    const bool own = ((fl >> 2) & 1) == rank, spare = !own && lc < 2;
    fa = (spare ? sb + OFF_IN + 96 + lc * 2064 : sb + OFF_U + (own ? 4 * rank * U_N8 : 4 * (rank ^ 1) * U_N8 - 2 * U_CH) + lc * U_CH) + (warp & 3) * 128 + (fl >> 4) * 16 + (wg & 1) * 64;
    fs = spare ? 512 : U_N8;
  };
  auto get_q = [&](int n, int off, int bar, int ph) {
#pragma unroll
    for (int u = 0; u < 2; u++) {
      mbar_wait(bars + (bar + u) * 8, ph);
#pragma unroll
      for (int r = 0; r < 4; r++) q[n + u][r] = lds64(sb + off + 4096 * u + 1024 * (warp & 3) + 256 * r + 8 * fl);
    }
  };
#define CLUSTER_WAIT() asm volatile("barrier.cluster.wait.aligned;" ::: "memory")

  if (wg == 3) {
    asm volatile("setmaxnreg.dec.sync.aligned.u32 24;");
    CLUSTER_WAIT();
    if (warp < 14) {
      if (elect_one()) {
        uint32_t so = 8 * (HEAD % STAGES), ph = HEAD < STAGES;
        auto step = [&](auto issue) {
          mbar_wait(bars + B_EMPTY * 8 + so, ph);
          issue(sb + OFF_RING + (so << 12), bars + B_FULL * 8 + so);
          so += 8;
          if (so == 8 * STAGES) { so = 0; ph ^= 1; }
        };
        if (warp == 12) {
          auto g1 = [&](int n0, int n1, int grp) {
#pragma unroll 1
            for (int n = n0; n < n1; n++) step([&](uint32_t dst, uint32_t fb) { mbar_expect(fb, STAGE_BYTES); tma4d_mc(dst + rank * 8192, &mB, n * 64, 0, 0, grp + 4 * rank, fb); });
          };
#pragma unroll 1
          for (int n = HEAD; n < STAGES; n++) { spin_until(c_start, ST_T0 + n * ST_DELAY); g1(n, n + 1, 8 * j); }
          g1(STAGES, 16, 8 * j);
          g1(0, XPOS - 16, 8 * j + 64);
          step([&](uint32_t dst, uint32_t fb) { mbar_expect(fb, STAGE_BYTES); tma4d(dst, &mXs, 128 * j, 0, 4 * tc, 0, fb); });
#pragma unroll 1
          for (int n = 0; n < 32; n += 2) {
            const int col = kblock(n) * 32;
#pragma unroll
            for (int part = 0; part < 2; part++)
              step([&](uint32_t dst, uint32_t fb) { mbar_expect(fb, STAGE_BYTES); tma5d_mc(dst + rank * 8192, part ? &mCim : &mCre, col, 0, 0, 0, 8 * j + 4 * rank, fb); });
          }
        } else {
          auto g1 = [&](int n0, int n1, int nb) {
#pragma unroll 1
            for (int n = n0; n < n1; n++) step([&](uint32_t dst, uint32_t fb) { tma4d(dst + 16384, &mX, n * 64, 0, 4 * tc, 0, fb); });
          };
          auto g2 = [&](int n0, int n1) {
#pragma unroll 1
            for (int n = n0; n < n1; n++) step([&](uint32_t dst, uint32_t fb) { bulk_load(dst + 16384, g_h + (32 * tc + kblock(n)) * 1024, 16384, fb); });
          };
#pragma unroll 1
          for (int n = HEAD; n < STAGES; n++) { spin_until(c_start, ST_T0 + n * ST_DELAY); g1(n, n + 1, 0); }
          g1(STAGES, 16, 0);
          g1(0, XPOS - 16, 16);
          step([&](uint32_t dst, uint32_t fb) { tma4d(dst + 16384, &mXs, 128 * j + 64, 0, 4 * tc, 0, fb); });
#pragma unroll 1
          for (int v = 0; v < 2; v++) {
            mbar_wait(bars + B_HP * 8, v);
            fence_proxy_async_global();
            g2(16 * v, 16 * v + 2);
            mbar_wait(bars + B_HR * 8, v);
            fence_proxy_async_global();
            g2(16 * v + 2, 16 * v + 16);
          }
        }
      }
    } else if (warp == 15) {
      mbar_wait(bars + B_COEF * 8, 0);
      const unsigned epoch = lds32(bars + B_EPOCH * 8);
#pragma unroll 1
      for (int v = 0; v < 2; v++) {
        unsigned* fp = &g_flagH[(16 * v + tc) * 32];
        if (elect_one()) {
          wait_until(v ? clk32() : c_start, (v ? PFC_T1 : PFC_T0) + (slot >> 3) * PFC_DT);
#pragma unroll
          for (int part = 0; part < 2; part++)
            asm volatile("cp.async.bulk.prefetch.tensor.5d.L2.global [%0, {%1, %2, %2, %2, %3}];" ::"l"(part ? &mCim : &mCre), "r"(512 * v + 8 * (slot & 56)), "r"(0), "r"(8 * j + 4 * rank) : "memory");
        }
        __syncwarp();
        bar_sync(4 + v, 160);
        if (elect_one()) {
          asm volatile("red.release.gpu.global.add.u32 [%0], 1;" ::"l"(fp) : "memory");
          mbar_arrive(bars + B_HP * 8);
          int it = 0;
          while (ld_acquire(fp) != 8 * epoch && ++it < (SPIN_LIMIT << 4)) __nanosleep(POLL_NS);
          mbar_arrive(bars + B_HR * 8);
        }
        __syncwarp();
      }
    } else if (elect_one()) {
      const int ch0 = 16 * slot;
      auto load_k = [&](int s, uint32_t dst) { const uint32_t fb = bars + (B_KF + s) * 8; mbar_expect(fb, 4096); tma2d(dst, &mS, 0, 64 * (8 * b + s), fb); };
      prefetch_map(&mS); prefetch_map(&mK); prefetch_map(&mV);
      wait_until(c_start, K_T0);
      load_k(0, sb + OFF_U + (4 * rank + 3) * U_N8); load_k(1, sb + OFF_U + (4 * rank + 3) * U_N8 - 4096);
      {
        uint32_t so = 16, ph = 1;
#pragma unroll 1
        for (int e = 0; e < 9; e++) {
          const uint32_t fb = bars + B_KVF * 8 + so, dst = sb + OFF_KV + (so << 10);
          wait_until(c_start, KV_T0 + (e ? 2 * e - 1 : 0) * KV_DT - (e > KV_E ? e - KV_E : 0) * 2 * (KV_DT - KV_D2));
          mbar_wait(bars + B_KVE * 8 + so, ph);
          const uint32_t c1 = clk32();
          mbar_expect(fb, e ? 8192 : 4096);
          tma3d(dst, &mK, ch0, 32 * rank - (e == 0), (4 * e - 4) & 31, fb);
          if (e > 0) { wait_until(c1, KV_DV); tma3d(dst + 4096, &mV, ch0, 32 * rank, 4 * e - 4, fb); }
          so += 8;
          if (so == 24) so = 0;
          if (so == 16) ph ^= 1;
        }
      }
      prefetch_map(&mCre); prefetch_map(&mCim); prefetch_map(&mXs); prefetch_map(&mQ); prefetch_map(&mO);
      mbar_wait(bars + B_KVE * 8, 0);
      load_k(2, sb + OFF_K); load_k(3, sb + OFF_K + 4096);
      mbar_wait(bars + (B_UF + 3) * 8, 0);
#pragma unroll 1
      for (int ch = 0; ch < 7; ch++) {
        mbar_wait(bars + (B_ST + ch) * 8, 0);
        if (ch > 2) mbar_wait(bars + (B_IN + ch - 3) * 8, 0);
        if (ch < 4) load_k(ch + 4, sb + OFF_K + (ch & 1) * 4096);
        else if (ch < 6) load_q(2 * (ch & 1), OFF_K, B_KF + 8);
        if (ch > 0) send_y(ch - 1);
        if (ch == 2) load_q(1, OFF_Q, B_QF);
        if (ch == 3) asm volatile("cp.async.bulk.prefetch.tensor.4d.L2.global [%0, {%1, %2, %3, %4}];" ::"l"(&mQ), "r"(16 * (slot & ~3)), "r"(0), "r"(16 + 4 * (slot & 3)), "r"(4 * rank) : "memory");
        if (ch == 4) { mbar_wait(bars + B_XI * 8, 0); load_q(3, OFF_Q, B_QF); }
      }
    }
    return;
  } else if (wg == 2) {
    asm volatile("setmaxnreg.inc.sync.aligned.u32 %0;" ::"n"(488 - 2 * GREG));
    const int t = tid & 127, w = warp & 3, lane = t & 31, g = lane >> 2, c = lane & 3;
    const uint4 s2[2] = {ldg128_nc(P.shift_k + (8 * b + 2 * c) * 4), ldg128_nc(P.shift_k + (8 * (b ^ 1) + 2 * c) * 4)};
    const uint32_t dskip = __bfloat16_as_ushort(P.ssm_D[8 * b + (t & 7)]);
    uint32_t tp[4] = {}, ts[4] = {};
    float d0r, d0i;
    fft_tables(sb + OFF_F1, sb + OFF_F2, w, lane, tp, ts, d0r, d0i);
    CLUSTER_WAIT();
    if (t < 12) mbar_expect(bars + (B_IN + t) * 8, t < 6 ? 2048 : t < 8 ? 4 * (U_CH + 512) : U_N8);
    if (t < 8) sts32(sb + OFF_D + 8 * t, dskip << 16);
    const uint64_t dF1b = make_desc(sb + OFF_F1, 512, 128, 0);
    const uint64_t dF2f = make_desc(sb + OFF_F2, 512, 128, 0), dF2i = make_desc(sb + OFF_F2, 128, 512, 0);
    uint32_t f1[8];
#pragma unroll
    for (int i = 0; i < 8; i++) f1[i] = lds32(sb + OFF_F1 + w * 1024 + (i & 1) * 512 + (i >> 1) * 128 + lane * 4);
    auto T1k = [&](float* z, uint64_t dk) { wg_fence(); rs_n64<0, 1>(z, f1, dk); rs_n64<1, 1>(z, f1 + 4, dk + 64); wg_commit(); };
    auto T1u = [&](float* z, uint64_t du) { wg_fence(); rs_n64<0, 0>(z, f1, du); rs_n64<1, 0>(z, f1 + 4, du + 16); wg_commit(); };
    auto T2 = [&](float* s, const uint32_t* f) {
      wg_fence();
      rs_n32<0, 1>(s, f, dF2f); rs_n32<0, 1>(s + 16, f + 8, dF2f); rs_n32<1, 1>(s, f + 4, dF2f + 64); rs_n32<1, 1>(s + 16, f + 12, dF2f + 64);
      wg_commit();
    };
    auto product = [&](uint32_t* pr, const uint32_t* kh, const uint32_t* uh) {
      bimac<0>(pr, kh, uh, pr); bimac<2>(pr + 8, kh + 8, uh, pr); bimac<1>(pr + 8, kh, uh + 8, pr + 8);
      fence_u32<16>(pr);
    };
    float zk[32] = {};
    uint32_t pr[16];
    {
      uint32_t kh0[16];
      {
        float z0[32], sk[32];
        uint32_t fk[16];
        const uint64_t dk = make_desc(sb + OFF_U + (4 * rank + 3) * U_N8, 2048, 512, 2);
        fence_proxy_async_smem();
        bar_sync(7, 128);
        mbar_wait(bars + B_KF * 8, 0);
        T1k(z0, dk);
        mbar_wait(bars + (B_KF + 1) * 8, 0);
        T1k(zk, dk - 256);
        wg_wait<0>(); fence_regs<32>(z0); fence_regs<32>(zk);
        const float dd = __uint_as_float(lds32(sb + OFF_D));
        z0[0] = fmaf(d0r, dd, z0[0]); z0[2] = fmaf(d0i, dd, z0[2]);
        pack32(fk, z0); twiddle<0>(fk, tp, ts); fence_u32<16>(fk);
        T2(sk, fk);
        wg_wait<0>(); fence_regs<32>(sk); fence_u32<16>(fk);
        pack32(kh0, sk); fence_u32<16>(kh0);
      }
      {
        uint32_t sk[2][4], kx[2][8];
#pragma unroll
        for (int o = 0; o < 2; o++) {
          sk[o][0] = __byte_perm(s2[o].x, s2[o].z, 0x5410); sk[o][1] = __byte_perm(s2[o].x, s2[o].z, 0x7632);
          sk[o][2] = __byte_perm(s2[o].y, s2[o].w, 0x5410); sk[o][3] = __byte_perm(s2[o].y, s2[o].w, 0x7632);
        }
        const uint32_t la = sb + OFF_KV + (lane >> 3) * 1024 + (8 * w + (lane & 7)) * 32 + ((rank ^ ((lane >> 2) & 1)) << 4);
        const uint32_t uo = (lane & 7) * U_CH + w * 128 + (lane >> 3) * 16;
        mbar_wait(bars + (B_KVF + 2) * 8, 0);
        ldsm4(kx[0], la + 16384); ldsm4(kx[1], (la ^ 16) + 16384);
        if (lane == 0) mbar_arrive(bars + (B_KVE + 2) * 8 + (kx[0][1] & kx[1][1] & P.zero));
        uint32_t so = 0, ph = 0;
#pragma unroll 1
        for (int n = 0; n < 4; n++) {
          const uint32_t own = sb + OFF_U + (4 * rank + n) * U_N8, box = n < 3 ? sb + OFF_U + (4 * (rank ^ 1) + n + 1) * U_N8 : sb + OFF_IN;
#pragma unroll
          for (int e = 0; e < 2; e++) {
            uint32_t vx[2][4];
            mbar_wait(bars + B_KVF * 8 + so, ph);
#pragma unroll
            for (int o = 0; o < 2; o++) { ldsm4(kx[o] + 4, (la ^ (16 * o)) + (so << 10)); ldsm4(vx[o], (la ^ (16 * o)) + (so << 10) + 4096); }
            if (lane == 0) mbar_arrive(bars + B_KVE * 8 + so + (kx[0][4] & kx[1][4] & vx[0][0] & vx[1][0] & P.zero));
#pragma unroll
            for (int o = 0; o < 2; o++) {
#pragma unroll
              for (int i = 0; i < 4; i++) vx[o][i] = bmul2(bfma2(kx[o][i + 4], sk[o][0], bfma2(kx[o][i + 3], sk[o][1], bfma2(kx[o][i + 2], sk[o][2], bmul2(kx[o][i + 1], sk[o][3])))), vx[o][i]);
              stsm4t((o ? box : own) + uo + e * 64, vx[o][0], vx[o][1], vx[o][2], vx[o][3]);
              kx[o][1] = kx[o][5]; kx[o][2] = kx[o][6]; kx[o][3] = kx[o][7];
            }
            so += 8;
            if (so == 24) so = 0;
            if (so == 16) ph ^= 1;
          }
          fence_proxy_async_smem();
          bar_sync(7, 128);
          if (w == 0 && elect_one()) {
            if (n > 0) mbar_wait(bars + B_UF * 8 + 8 * (n - 1), 0);
            bulk_send(own, box, U_N8, bars + B_UF * 8 + 8 * n, rank ^ 1);
          }
          __syncwarp();
        }
      }
      float zu[32], su[32];
      uint32_t fu[16], uh[16];
#pragma unroll
      for (int n = 0; n < 4; n++) mbar_wait(bars + (B_UF + n) * 8, 0);
      T1u(zu, make_desc(sb + OFF_U, 128, U_N8, 0));
      wg_wait<0>(); fence_regs<32>(zu);
      pack32(fu, zu); twiddle<0>(fu, tp, ts); fence_u32<16>(fu);
      T2(su, fu);
      wg_wait<0>(); fence_regs<32>(su); fence_u32<16>(fu);
      pack32(uh, su);
      product(pr, kh0, uh);
    }
    {
#define CF(i) do { if ((CFM >> (i)) & 1) PMFENCE(); } while (0)
      const uint32_t vs = w < 2 ? 512 : U_N8, vi = (w >> 1) * U_CH;
      uint32_t va = (w < 2 ? sb + OFF_VP : sb + OFF_U) + ((lane >> 4) & 1) * vs + (w & 1) * 256 + (lane & 15) * 16;
      const uint32_t ya = sb + OFF_U + (2 * w + ((lane >> 3) & 1)) * U_N8 + (lane >> 4) * 128 + (lane & 7) * 16;
      uint64_t du = make_desc(sb + OFF_U, 128, U_N8, 0), dk = make_desc(sb + OFF_K, 2048, 512, 2);
      const uint64_t dv = make_desc(sb + OFF_VP, 128, 512, 0), dks = 2 * dk + 256;
      uint32_t yp[8] = {};
      uint32_t yq = sb + OFF_Q + lane * 16, yi = ya - yq;
      auto store_y = [&]() { stsm4(yq, yp[0], yp[1], yp[2], yp[3]); stsm4(yq + 256, yp[4], yp[5], yp[6], yp[7]); };
      auto step = [&](uint32_t c8, auto fwd) {
        constexpr bool FWD = decltype(fwd)::value;
        float zu[32], sk[32], su[32], v[32], y[16];
        uint32_t kh[16], uh[16], fk[16], fu[16], fv[16];
        wg_fence();
        rs_n32<0, 0>(v, pr, dF2i); rs_n32<0, 0>(v + 16, pr + 8, dF2i); rs_n32<1, 0>(v, pr + 4, dF2i + 16); rs_n32<1, 0>(v + 16, pr + 12, dF2i + 16);
        wg_commit();
        CF(0);
        const float dd = FWD ? __uint_as_float(lds32(sb + OFF_D + 8 + c8)) : 0.f;
        store_y();
        if (FWD) {
          zk[0] = fmaf(d0r, dd, zk[0]); zk[2] = fmaf(d0i, dd, zk[2]);
          pack32(fk, zk); twiddle<0>(fk, tp, ts); fence_u32<16>(fk);
          T2(sk, fk);
          CF(2);
          mbar_wait(bars + (B_KF + 2) * 8 + c8, 0);
          wg_wait<1>();
        } else {
#pragma unroll
          for (int r = 3; r < 6; r++) mbar_wait(bars + (B_IN + r) * 8, 0);
          wg_wait<0>();
        }
        fence_regs<32>(v); fence_u32<16>(pr);
        pack32(fv, v); fence_u32<16>(fv);
        CF(4);
        if (FWD) T1u(zu, du + U_CH / 16);
        CF(5);
        if (FWD) { wg_wait<1>(); fence_regs<32>(sk); fence_u32<16>(fk); pack32(kh, sk); }
        twiddle<1>(fv, tp, ts);
        fence_u32<16>(fv);
        if (FWD) fence_u32<16>(kh);
        CF(7);
        if (FWD) T1k(zk, dk);
#pragma unroll
        for (int i = 0; i < 4; i++) stsm4(va + 2 * i * vs, fv[4 * i], fv[4 * i + 1], fv[4 * i + 2], fv[4 * i + 3]);
        if (FWD) {
          CF(8);
          wg_wait<1>(); fence_regs<32>(zu);
          pack32(fu, zu); twiddle<0>(fu, tp, ts); fence_u32<16>(fu);
          T2(su, fu);
          CF(10);
        }
        fence_proxy_async_smem();
        bar_sync(7, 128);
        wg_fence();
        ss_n32_tt<0>(y, dv, dF1b); ss_n32_tt<1>(y, dv + 16, dF1b + 64); ss_n32_tt<1>(y, du, dF1b + 128); ss_n32_tt<1>(y, du + 16, dF1b + 192);
        wg_commit();
        CF(12);
        if (FWD) {
          wg_wait<1>(); fence_regs<32>(su); fence_u32<16>(fu); fence_regs<32>(zk);
          if (t == 0) mbar_arrive(bars + B_ST * 8 + c8);
          pack32(uh, su);
          bimac<0>(pr, kh, uh, pr); bimac<2>(pr + 8, kh + 8, uh, pr); fence_u32<16>(pr);
          CF(14);
          wg_wait<0>(); fence_regs<16>(y);
          bimac<1>(pr + 8, kh, uh + 8, pr + 8); fence_u32<8>(pr + 8);
          du += U_CH / 16; dk = dks - dk;
          va += vi;
        }
        if (!FWD) {
          PMFENCE();
          fin_setup(); get_q(0, OFF_K, B_KF + 8, 0);
#pragma unroll
          for (int r = 0; r < 8; r++) q[2 + (r >> 2)][r & 3] = make_uint2(0, 0);
          wg_wait<0>(); fence_regs<16>(y);
        }
#pragma unroll
        for (int i = 0; i < 8; i++) yp[i] = pack_bf16(y[2 * i], y[2 * i + 1]);
        fence_u32<8>(yp);
        yq += yi; yi = U_CH;
      };
#pragma unroll 1
      for (uint32_t c8 = 0; c8 < 56; c8 += 8) step(c8, std::true_type());
      step(56, std::false_type());
      store_y();
    }
    fence_proxy_async_smem();
    bar_sync(7, 128);
    if (elect_one()) bulk_send(sb + OFF_U + (4 * rank + w) * U_N8 + 4 * U_CH, sb + OFF_U + (4 * (rank ^ 1) + w) * U_N8 + 6 * U_CH, U_CH + 512, bars + (B_IN + 6) * 8, rank ^ 1);
    __syncwarp();
    asm volatile("bar.arrive 9, 256;" ::: "memory");
  } else {
    asm volatile("setmaxnreg.inc.sync.aligned.u32 %0;" ::"n"(GREG));
    const int t = tid & 127, w = warp & 3, lane = t & 31, g = lane >> 2, c = lane & 3;
    if (wg == 1) {
      wait_until(c_start, COEF_T0);
      const int p = 64 * j + (t & 63) + 8 * (t & 64);
      const float Lr = bf2f(P.lam_re[p]), Li = bf2f(P.lam_im[p]);
      const uint32_t ds = __bfloat16_as_ushort(P.Dskip[128 * j + t]);
      const unsigned epoch = ld_relaxed(&g_epoch[b * 32]) + 1;
      const float dt = bf2f(__float2bfloat16_rn(expf(bf2f(P.log_dt[p]))));
      const float e = expf(dt * Lr);
      float sn, cs;
      {
        const double z = (double)(dt * Li) * 0.15915494309189535;
        sincospif(2.f * (float)(z - rint(z)), &sn, &cs);
      }
      const float lr = e * cs, li = e * sn;
      const float nr = lr - 1.0f, ni = li;
      const bool big = fabsf(Lr) >= fabsf(Li);
      const float la = big ? Lr : Li, lb = big ? Li : Lr, r = __fdiv_rn(lb, la), inv = __frcp_rn(fmaf(lb, r, la));
      const float br = (big ? fmaf(ni, r, nr) : fmaf(nr, r, ni)) * inv, bi = (big ? fmaf(-nr, r, ni) : fmaf(ni, r, -nr)) * inv;
      sts128(sb + OFF_COEF + t * 16, make_uint4(__float_as_uint(lr), __float_as_uint(li), pack_bf16(2.f * br, 2.f * br), pack_bf16(-2.f * bi, -2.f * bi)));
      sts32(sb + OFF_DS + 4 * t, ds << 16);
      if (t == 0) sts32(bars + B_EPOCH * 8, epoch);
    }
    CLUSTER_WAIT();
    if (wg == 1) mbar_arrive(bars + B_COEF * 8);
    float d[128];
    uint32_t so = 0, ph = 0, po = 0;
    uint32_t ra;
    auto set_ra = [&]() { asm volatile("mapa.shared::cluster.u32 %0, %1, %2;" : "=r"(ra) : "r"(bars + B_EMPTY * 8), "r"((t & 1) ? rank ^ 1 : rank)); };
    set_ra();
    auto release = [&](uint32_t off) { if (t < 2) asm volatile("mbarrier.arrive.shared::cluster.b64 _, [%0];" ::"r"(ra + off) : "memory"); };
    constexpr uint32_t NOBAR = 8 * (B_NONE - B_EMPTY);
    auto block = [&](auto ta, uint64_t da0, uint64_t db0, bool zero, int nn) {
      constexpr int PH = decltype(ta)::value, TA = PH > 0, KS = TA ? 128 : 2, QD = PH == 0 ? QD1 : PH == 1 ? QD2 : QD3;
      mbar_wait(bars + B_FULL * 8 + so, ph);
      const uint64_t da = da0 + (so << 8), db = db0 + (so << 8);
      wg_fence();
      wgmma_n128<TA>(d, da, db, !zero);
      wgmma_n128<TA>(d + 64, da + 512, db, !zero);
      wg_commit();
      wg_wait<1>();
      release(po);
#pragma unroll
      for (int k = 1; k < 4; k++) {
        if (QD == 2 || (QD == 4 && k == 2)) wg_fence();
        wgmma_n128<TA>(d, da + KS * k, db + 2 * k, 1);
        wgmma_n128<TA>(d + 64, da + 512 + KS * k, db + 2 * k, 1);
        if (QD == 2 || (QD == 4 && k == 1)) wg_commit();
        if ((QD == 2 && k < 3) || (QD == 4 && k == 1)) wg_wait<1>();
      }
      if (QD != 2) wg_commit();
      po = so;
      so += 8;
      if (so == 8 * STAGES) { so = 0; ph ^= 1; }
    };
    {
      so = wg ? 8 * (16 % STAGES) : 0; ph = wg ? (16 / STAGES) & 1 : 0; po = NOBAR;
      const uint64_t da0 = make_desc(sb + OFF_RING, 16, 1024, 1), db0 = make_desc(sb + OFF_RING + 16384, 16, 1024, 1);
      if (wg == 1) bar_sync(1, 256);
#pragma unroll 1
      for (int kb = 0; kb < 16; kb++) {
        block(std::integral_constant<int, 0>(), da0, db0, kb == 0, 16 * wg + kb);
      }
      asm volatile("bar.arrive %0, 256;" ::"r"(1 + wg) : "memory");
    }
    mbar_wait(bars + B_COEF * 8, 0);
    const uint32_t ca = sb + OFF_COEF + (64 * wg + 8 * w + g) * 16;
    const uint32_t tag = __shfl_sync(0xffffffffu, lds32(bars + B_EPOCH * 8) & 3, 0);
    constexpr int RE = SWAPB ? 2 : 0, IM = 2 - RE;
    const int ct = lane >> 3;
    const uint2* cp = g_carry + __shfl_sync(0xffffffffu, ((16 * wg + 2 * j) * 16 + tc - 1 - ct) * 32 + 8 * w + (lane & 7), lane);
    unsigned long long cv[4];
    const int nv = tc - ct;
    auto load_carry = [&](int i) {
#pragma unroll
      for (int m = 0; m < 4; m++)
        asm volatile("{\n.reg .pred p;\nsetp.gt.s32 p, %2, %3;\n@p ld.relaxed.gpu.global.b64 %0, [%1];\n}\n" : "+l"(cv[m]) : "l"(cp + 512 * i - 128 * m), "r"(nv), "r"(4 * m) : "memory");
    };
    float lr[2], li[2], pr[2], pi[2], wr[2], wi[2], vr[2], vi[2], qr[2], qi[2], gr[2], gi[2];
#pragma unroll
    for (int i = 0; i < 2; i++) {
      const uint2 cf = lds64(ca + 512 * i);
      pr[i] = lr[i] = __uint_as_float(cf.x); pi[i] = li[i] = __uint_as_float(cf.y);
#pragma unroll
      for (int s = 0; s < 4; s++) csq(pr[i], pi[i]);
      gr[i] = pr[i]; gi[i] = pi[i];
      csq(pr[i], pi[i]);
      qr[i] = pr[i]; qi[i] = pi[i];
      csq(qr[i], qi[i]);
      asm volatile("" : "+f"(pr[i]), "+f"(pi[i]), "+f"(qr[i]), "+f"(qi[i]));
    }
    PMFENCE();
    wg_wait<0>();
    fence_regs<128>(d);
    release(po);
#pragma unroll
    for (int i = 0; i < 2; i++) {
      float* e = d + 64 * i;
      auto chain = [&](int s0, int s1, float& sr, float& si) {
        sr = e[2 * s0 + RE]; si = e[2 * s0 + IM];
#pragma unroll
        for (int s = s0 + 1; s < s1; s++) {
          const int ia = 4 * (s >> 1) + (s & 1);
          const float nr = fmaf(-li[i], si, fmaf(lr[i], sr, e[ia + RE])), ni = fmaf(li[i], sr, fmaf(lr[i], si, e[ia + IM]));
          sr = nr; si = ni;
        }
      };
      float sr, si;
      if ((GREEDY >> i) & 1) {
        float ar, ai;
        chain(0, 16, ar, ai); chain(16, 32, sr, si);
        sr = fmaf(gr[i], ar, fmaf(-gi[i], ai, sr)); si = fmaf(gr[i], ai, fmaf(gi[i], ar, si));
      } else chain(0, 32, sr, si);
      if (i == 1) { asm volatile("pmevent 0;" : "+f"(sr), "+f"(si)::"memory"); cv[0] = cv[1] = cv[2] = cv[3] = tag; load_carry(0); }
      float ur = __shfl_up_sync(0xffffffffu, sr, 1, 4), ui = __shfl_up_sync(0xffffffffu, si, 1, 4);
      if (c >= 1) { sr = fmaf(pr[i], ur, fmaf(-pi[i], ui, sr)); si = fmaf(pr[i], ui, fmaf(pi[i], ur, si)); }
      ur = __shfl_up_sync(0xffffffffu, sr, 2, 4); ui = __shfl_up_sync(0xffffffffu, si, 2, 4);
      if (c >= 2) { sr = fmaf(qr[i], ur, fmaf(-qi[i], ui, sr)); si = fmaf(qr[i], ui, fmaf(qi[i], ur, si)); }
      ur = __shfl_sync(0xffffffffu, sr, 4 * lane + 3); ui = __shfl_sync(0xffffffffu, si, 4 * lane + 3);
      asm volatile("{\n.reg .pred p;\n.reg .b64 v;\nsetp.lt.u32 p, %3, 8;\nmov.b64 v, {%1,%2};\n@p st.relaxed.gpu.global.b64 [%0], v;\n}\n"
                   ::"l"(cp + 512 * i + 32), "r"((__float_as_uint(ur) & ~3u) | tag), "r"(__float_as_uint(ui)), "r"(lane) : "memory");
      PMFENCE();
      ur = __shfl_up_sync(0xffffffffu, sr, 1, 4); ui = __shfl_up_sync(0xffffffffu, si, 1, 4);
      if (c >= 1) { e[RE] = fmaf(lr[i], ur, fmaf(-li[i], ui, e[RE])); e[IM] = fmaf(lr[i], ui, fmaf(li[i], ur, e[IM])); }
      asm volatile("" : "+f"(e[RE]), "+f"(e[IM]));
    }
#pragma unroll
    for (int i = 0; i < 2; i++) {
      wr[i] = (c & 1) ? pr[i] : 1.f; wi[i] = (c & 1) ? pi[i] : 0.f;
      if (c & 2) { float x, y; cmul(wr[i], wi[i], qr[i], qi[i], x, y); wr[i] = x; wi[i] = y; }
      vr[i] = wr[i]; vi[i] = wi[i];
      csq(vr[i], vi[i]); csq(vr[i], vi[i]);
      csq(qr[i], qi[i]); csq(qr[i], qi[i]); csq(qr[i], qi[i]);
      const int src = 4 * (lane & 7) + ct;
      vr[i] = __shfl_sync(0xffffffffu, vr[i], src); vi[i] = __shfl_sync(0xffffffffu, vi[i], src);
      qr[i] = __shfl_sync(0xffffffffu, qr[i], src); qi[i] = __shfl_sync(0xffffffffu, qi[i], src);
    }
    uint4* hp = g_h + (32 * tc + 16 * wg + 2 * j) * 1024 + 64 * w + 4 * g + (c ^ (g >> 1));
    float sr[2], si[2];
    uint32_t gp[2], gm[2];
    auto carry_in = [&](int i) {
      auto ready = [&]() { return __all_sync(0xffffffffu, ((((uint32_t)cv[0] ^ tag) | ((uint32_t)cv[1] ^ tag) | ((uint32_t)cv[2] ^ tag) | ((uint32_t)cv[3] ^ tag)) & 3) == 0); };
      if (!ready()) {
        int n = 0;
#pragma unroll 1
        do load_carry(i); while (!ready() && ++n <= (SPIN_LIMIT << 4));
      }
      float hr = __uint_as_float((uint32_t)cv[3]), hi = __uint_as_float((uint32_t)(cv[3] >> 32));
#pragma unroll
      for (int m = 2; m >= 0; m--) {
        const float nr = fmaf(qr[i], hr, fmaf(-qi[i], hi, __uint_as_float((uint32_t)cv[m]))), ni = fmaf(qr[i], hi, fmaf(qi[i], hr, __uint_as_float((uint32_t)(cv[m] >> 32))));
        hr = nr; hi = ni;
      }
      { float x, y; cmul(hr, hi, vr[i], vi[i], x, y); hr = x; hi = y; }
      const uint4 cf = lds128(ca + 512 * i);
      lr[i] = __uint_as_float(cf.x); li[i] = __uint_as_float(cf.y); gp[i] = cf.z; gm[i] = cf.w;
      hr += __shfl_xor_sync(0xffffffffu, hr, 8); hi += __shfl_xor_sync(0xffffffffu, hi, 8);
      hr = __shfl_sync(0xffffffffu, hr, g) + __shfl_sync(0xffffffffu, hr, g + 16); hi = __shfl_sync(0xffffffffu, hi, g) + __shfl_sync(0xffffffffu, hi, g + 16);
      cmul(wr[i], wi[i], hr, hi, sr[i], si[i]);
    };
    PMFENCE();
    carry_in(0);
#pragma unroll
    for (int u = 0; u < 8; u++) {
      const int i = u >> 2, i8 = u & 3;
      float* e = d + 64 * i;
      asm volatile("pmevent 0;" : "+f"(sr[i]), "+f"(si[i])::"memory");
      if (u == 1) load_carry(1);
      if (u == 3) carry_in(1);
#pragma unroll
      for (int s = 8 * i8; s < 8 * i8 + 8; s++) {
        const int ia = 4 * (s >> 1) + (s & 1);
        const float nr = fmaf(-li[i], si[i], fmaf(lr[i], sr[i], e[ia + RE])), ni = fmaf(li[i], sr[i], fmaf(lr[i], si[i], e[ia + IM]));
        sr[i] = nr; si[i] = ni;
        e[ia + RE] = nr; e[ia + IM] = ni;
      }
      uint32_t hq[8];
#pragma unroll
      for (int m = 0; m < 4; m++) {
        const float* f = e + 16 * i8 + 4 * m;
        const uint32_t x = pack_bf16(f[RE], f[RE + 1]), y = pack_bf16(f[IM], f[IM + 1]);
        hq[m] = bfma2(gp[i], x, bmul2(gm[i], y)); hq[4 + m] = bfnma2(gp[i], y, bmul2(gm[i], x));
      }
      uint4* o = hp + 512 * (i8 >> 1) + 256 * i + 32 * (i8 & 1);
      stg128(o, make_uint4(hq[0], hq[1], hq[2], hq[3]));
      stg128(o + 1024, make_uint4(hq[4], hq[5], hq[6], hq[7]));
#pragma unroll
      for (int m = 0; m < 8; m++) d[16 * u + m] = __uint_as_float(hq[m]);
      fence_regs<8>(d + 16 * u);
    }
    const int trow = 128 * tc + 64 * (w & 1) + 8 * (w >> 1) + g;
    const int dcol = 128 * j + 4 * c;
    asm volatile("bar.arrive %0, 160;" ::"r"(4 + wg) : "memory");
    if (wg == 0) {
      set_ra();
      {
        const uint32_t dt = sb + OFF_Q + 4096;
        mbar_wait(bars + (B_UF + 3) * 8, 0);
        const int n = t & 15, k = 2 * (n & 6) + 2 * (n >> 3) + (n & 1);
        const uint32_t dv = lds32(sb + OFF_DS + (t & ~15) * 4 + 4 * k) >> (16 - 16 * (k & 1));
#pragma unroll
        for (int u = 0; u < 2; u++) {
          const int m = (k >> 1) - 4 * u;
          sts128(dt + (t >> 4) * 512 + u * 256 + n * 16, make_uint4(m == 0 ? dv : 0, m == 1 ? dv : 0, m == 2 ? dv : 0, m == 3 ? dv : 0));
        }
        fence_proxy_async_smem();
        bar_sync(2, 256);
        mbar_wait(bars + (B_FULL + XPOS % STAGES) * 8, (XPOS / STAGES) & 1);
        const uint64_t dx = make_desc(sb + OFF_RING + (XPOS % STAGES) * STAGE_BYTES, 16, 1024, 1), dd = make_desc(dt, 256, 128, 0);
        wg_fence();
#pragma unroll
        for (int u = 0; u < 16; u++) {
          const uint64_t da = dx + ((u >> 2) & 1) * 1024 + (u >> 3) * 512 + (u & 3) * 2, db = dd + (u & 7) * 32;
          if (u & 1) ss_n16(d + 8 * u, da, db); else ss_n16_in(d + 8 * u, da, db, P.zero);
        }
        wg_commit();
        wg_wait<0>();
        rename_regs<128>(d);
        release(8 * (XPOS % STAGES));
        if (t == 0) mbar_arrive(bars + B_XI * 8);
      }
      so = 8 * (33 % STAGES); ph = (33 / STAGES) & 1; po = NOBAR;
      const uint64_t da0 = make_desc(sb + OFF_RING + 16384, 512, 1024, 2), db0 = make_desc(sb + OFF_RING, 16, 1024, 1);
#pragma unroll 1
      for (int kb = 0; kb < QSW; kb++) block(std::integral_constant<int, 1>(), da0, db0, false, 32 + kb);
#pragma unroll 1
      for (int kb = QSW; kb < 32 - TAILB; kb++) block(std::integral_constant<int, 2>(), da0, db0, false, 32 + kb);
      float* op = P.out + (size_t)trow * 2048 + 1024 + dcol;
      auto mma = [&](int i, int kb, int k0, int k1) {
        const int s = (33 + kb) % STAGES;
        wg_fence();
#pragma unroll
        for (int k = k0; k < k1; k++) wgmma_n128<1>(d + 64 * i, da0 + s * 2048 + 512 * i + 128 * k, db0 + (i ? 0 : P.zero) + s * 2048 + 2 * k, 1);
        wg_commit();
      };
      auto store = [&](int i, int J0, int J1) {
#pragma unroll
        for (int J = J0; J < J1; J++) {
#pragma unroll
          for (int h = 0; h < 2; h++) {
            const float* e = d + 64 * i + 8 * J + 2 * h;
            stg128(op + (size_t)(16 * i + 32 * h) * 2048 + 16 * J, make_uint4(__float_as_uint(e[0]), __float_as_uint(e[1]), __float_as_uint(e[4]), __float_as_uint(e[5])));
          }
        }
        PMFENCE();
      };
      constexpr int K0 = 32 - TAILB;
#pragma unroll
      for (int kb = K0; kb < 32; kb++) {
        mbar_wait(bars + (B_FULL + (33 + kb) % STAGES) * 8, ((33 + kb) / STAGES) & 1);
        if (TAILB == 5 && kb == K0) { mma(0, kb, 0, 2); wg_wait<1>(); release(po); mma(0, kb, 2, 4); }
        else mma(0, kb, 0, 4);
      }
      mma(1, K0, 0, 4);
      wg_wait<1>();
      fence_regs<64>(d);
#pragma unroll
      for (int kb = K0 + 1; kb < 32; kb++) {
        mma(1, kb, 0, 4);
        store(0, T_ST * (kb - K0 - 1), kb == 31 ? 8 : T_ST * (kb - K0));
      }
      wg_wait<0>();
      fence_regs<64>(d + 64);
      store(1, 0, 8);
      if (t == 0) g_epoch[b * 32] = lds32(bars + B_EPOCH * 8);
      return;
    }
    asm volatile("setmaxnreg.dec.sync.aligned.u32 %0;" ::"n"(488 - 2 * GREG));
    fin_setup();
#pragma unroll
    for (int n = 0; n < 4; n += 2) {
      get_q(n, OFF_Q, B_QF, n >> 1);
      uint32_t dep = P.zero;
#pragma unroll
      for (int r = 0; r < 8; r++) dep &= q[n + (r >> 2)][r & 3].x;
      bar_sync(6 + dep, 128);
      if (w < 2 && elect_one()) load_q(5 + 2 * w - (n >> 1), OFF_Q, B_QF + n);
      __syncwarp();
    }
#pragma unroll 1
    for (int r = 0; r < 6; r++) mbar_wait(bars + (B_IN + r) * 8, 0);
    bar_sync(9, 256);
  }
  {
    const int w = warp & 3, h = wg & 1, lane = fl;
    const uint32_t ob0 = sb + (h ? OFF_F1 : OFF_K) + 1024 * w, ob1 = sb + (h ? OFF_VP : OFF_K + 4096) + 1024 * w;
    uint32_t y[2][8];
    auto get_y = [&](int n) { ldsm4t(y[n & 1], fa + n * fs); ldsm4t(y[n & 1] + 4, fa + n * fs + 32); };
    mbar_wait(bars + B_HR * 8, 1);
    mbar_wait(bars + (B_IN + 6) * 8, 0);
    get_y(0);
#pragma unroll
    for (int n = 0; n < 4; n++) {
      uint32_t* o = y[n & 1];
#pragma unroll
      for (int r = 0; r < 4; r++) { o[2 * r] = bmul2(o[2 * r], q[n][r].x); o[2 * r + 1] = bmul2(o[2 * r + 1], q[n][r].y); }
      if (n > 0 && lane == 0) asm volatile("cp.async.bulk.wait_group.read 0;" ::: "memory");
      __syncwarp();
#pragma unroll
      for (int r = 0; r < 4; r++)
        sts128((r & 2 ? ob1 : ob0) + (r & 1) * 512 + lane * 16, make_uint4(o[2 * r] << 16, o[2 * r] & 0xffff0000u, o[2 * r + 1] << 16, o[2 * r + 1] & 0xffff0000u));
      fence_proxy_async_smem();
      __syncwarp();
      if (lane == 0) {
#pragma unroll
        for (int u = 0; u < 2; u++)
          asm volatile("cp.async.bulk.tensor.3d.global.shared::cta.bulk_group [%0, {%2, %3, %4}], [%1];"
                       ::"l"(&mO), "r"(u ? ob1 : ob0), "r"(32 * slot), "r"(32 * rank + 8 * w), "r"(8 * n + 4 * h + 2 * u) : "memory");
        asm volatile("cp.async.bulk.commit_group;" ::: "memory");
      }
      __syncwarp();
      if (n < 3) get_y(n + 1);
      if (n == 1 && !h) get_q(2, OFF_Q, B_QF + 2, 0);
    }
    if (warp == 8 && lane == 0) mbar_arrive_cta(bars + B_ACK * 8, rank ^ 1);
    if (lane == 0) asm volatile("cp.async.bulk.wait_group 0;" ::: "memory");
    mbar_wait(bars + B_ACK * 8, 0);
  }
}

typedef CUresult (*EncodeFn)(CUtensorMap*, CUtensorMapDataType, cuuint32_t, void*, const cuuint64_t*, const cuuint64_t*, const cuuint32_t*,
                             const cuuint32_t*, CUtensorMapInterleave, CUtensorMapSwizzle, CUtensorMapL2promotion, CUtensorMapFloatOOBfill);

bool encode(EncodeFn fn, CUtensorMap* m, int rank, const void* base, const cuuint64_t* dims, const cuuint64_t* strides, const cuuint32_t* box, CUtensorMapSwizzle swz,
            CUtensorMapL2promotion promo = CU_TENSOR_MAP_L2_PROMOTION_L2_128B) {
  const cuuint32_t es[5] = {1, 1, 1, 1, 1};
  return fn(m, CU_TENSOR_MAP_DATA_TYPE_BFLOAT16, rank, const_cast<void*>(base), dims, strides, box, es, CU_TENSOR_MAP_INTERLEAVE_NONE, swz,
            promo, CU_TENSOR_MAP_FLOAT_OOB_FILL_NONE) == CUDA_SUCCESS;
}

}

extern "C" void kernel_launch(void* const* d_in, const int* in_sizes, int n_in, void* d_out, int out_size) {
  (void)in_sizes; (void)n_in; (void)out_size;
  typedef const __nv_bfloat16* In;
  const In q = (In)d_in[0], k = (In)d_in[1], v = (In)d_in[2], ssm_k = (In)d_in[4], x = (In)d_in[6], B_re = (In)d_in[9], B_im = (In)d_in[10], C_re = (In)d_in[11], C_im = (In)d_in[12];
  Params P = {};
  P.shift_k = (In)d_in[3]; P.ssm_D = (In)d_in[5]; P.lam_re = (In)d_in[7]; P.lam_im = (In)d_in[8]; P.log_dt = (In)d_in[13]; P.Dskip = (In)d_in[14];
  P.out = (float*)d_out;
  for (int cl = 0; cl < 64; cl++) P.slot[cl >> 2] |= (cl < 4 ? 4 + cl : cl < 36 ? 8 * ((cl - 4) & 7) + ((cl - 4) >> 3) : 8 * (1 + (cl - 36) % 7) + 4 + (cl - 36) / 7) << (8 * (cl & 3));
  const bool swapB = (uintptr_t)B_im < (uintptr_t)B_re;

  EncodeFn fn = nullptr;
  cudaDriverEntryPointQueryResult qr;
  cudaGetDriverEntryPoint("cuTensorMapEncodeTiled", (void**)&fn, cudaEnableDefault, &qr);
  if (!fn) return;

  CUtensorMap mX, mB, mCre, mCim, mXs, mK, mV, mQ, mS, mO;
  bool ok = true;
  {
    const cuuint64_t dims[4] = {1024, 2, 64, 16}, str[3] = {2048, 32 * 2048, 2 * 2048};
    const cuuint32_t box[4] = {64, 2, 4, 16};
    ok &= encode(fn, &mX, 4, x, dims, str, box, CU_TENSOR_MAP_SWIZZLE_128B);
  }
  {
    const uintptr_t lo = swapB ? (uintptr_t)B_im : (uintptr_t)B_re, hi = swapB ? (uintptr_t)B_re : (uintptr_t)B_im;
    const cuuint64_t dims[4] = {1024, 8, 2, 128}, str[3] = {2048, (cuuint64_t)(hi - lo), 8 * 2048};
    const cuuint32_t box[4] = {64, 8, 2, 4};
    ok &= encode(fn, &mB, 4, (const void*)lo, dims, str, box, CU_TENSOR_MAP_SWIZZLE_128B);
  }
  {
    const cuuint64_t dims[5] = {1024, 2, 4, 2, 64}, str[4] = {2048, 4 * 2048, 2 * 2048, 16 * 2048};
    const cuuint32_t box[5] = {64, 2, 4, 2, 4};
    ok &= encode(fn, &mCre, 5, C_re, dims, str, box, CU_TENSOR_MAP_SWIZZLE_128B);
    ok &= encode(fn, &mCim, 5, C_im, dims, str, box, CU_TENSOR_MAP_SWIZZLE_128B);
  }
  {
    const cuuint64_t dims[4] = {1024, 8, 64, 4}, str[3] = {2048, 32 * 2048, 8 * 2048};
    const cuuint32_t box[4] = {64, 8, 4, 4};
    ok &= encode(fn, &mXs, 4, x, dims, str, box, CU_TENSOR_MAP_SWIZZLE_128B);
  }
  {
    const cuuint64_t dims[3] = {1024, 64, 32}, str[2] = {32 * 2048, 2048};
    const cuuint32_t box[3] = {16, 32, 4};
    const cuuint64_t dimq[4] = {1024, 8, 32, 8}, strq[3] = {32 * 2048, 2048, 256 * 2048};
    const cuuint32_t boxq[4] = {16, 8, 4, 4};
    ok &= encode(fn, &mQ, 4, q, dimq, strq, boxq, CU_TENSOR_MAP_SWIZZLE_NONE);
    ok &= encode(fn, &mK, 3, k, dims, str, box, CU_TENSOR_MAP_SWIZZLE_32B);
    ok &= encode(fn, &mV, 3, v, dims, str, box, CU_TENSOR_MAP_SWIZZLE_32B);
  }
  {
    const cuuint64_t dims[2] = {32, 65536}, str[1] = {64};
    const cuuint32_t box[2] = {32, 64};
    ok &= encode(fn, &mS, 2, ssm_k, dims, str, box, CU_TENSOR_MAP_SWIZZLE_64B);
  }
  {
    const cuuint64_t dims[3] = {2048, 64, 32}, str[2] = {32 * 8192, 8192};
    const cuuint32_t box[3] = {32, 8, 2};
    ok &= encode(fn, &mO, 3, d_out, dims, str, box, CU_TENSOR_MAP_SWIZZLE_NONE);
  }
  if (!ok) return;
  auto kern = swapB ? fused_kernel<1> : fused_kernel<0>;
  cudaFuncSetAttribute(kern, cudaFuncAttributeMaxDynamicSharedMemorySize, SMEM_BYTES);
  kern<<<NCTA, 512, SMEM_BYTES, cudaStreamPerThread>>>(P, mX, mB, mCre, mCim, mXs, mK, mV, mQ, mS, mO);
}
```

```cpp
#include <cuda_runtime.h>
#include <cuda_bf16.h>
#include <cuda.h>
#include <stdint.h>
#include <type_traits>

namespace {

constexpr int D_DIM = 1024;
constexpr int NCTA = 128;

constexpr int STAGES = 5, STAGE_BYTES = 32768;
constexpr int OFF_RING = 0;
constexpr int OFF_F1 = STAGES * STAGE_BYTES, OFF_F2 = OFF_F1 + 4096, OFF_K = OFF_F2 + 2048, OFF_VP = OFF_K + 8192, OFF_Q = OFF_VP + 4096, OFF_IN = OFF_Q + 8192;
constexpr int OFF_KV = OFF_K;
constexpr int U_CH = 528, U_N8 = 8 * U_CH, OFF_U = OFF_IN + U_N8;
constexpr int OFF_COEF = OFF_U + 8 * U_N8;
constexpr int OFF_DS = OFF_COEF + 2048, OFF_D = OFF_DS + 512;
constexpr int OFF_BAR = OFF_D + 64;
constexpr int SMEM_BYTES = OFF_BAR + 512;
static_assert(SMEM_BYTES <= 232448 && OFF_K % 1024 == 0 && (OFF_U + 3 * U_N8) % 512 == 0 && (4 * U_N8) % 512 == 0, "smem map");
constexpr int B_FULL = 0, B_XI = 5, B_HR = 6, B_HP = 7, B_KVF = 8, B_QF = 11, B_IN = 15, B_UF = 23, B_ACK = 27, B_KF = 28, B_ST = 38,
              B_EMPTY = 45, B_COEF = 50, B_KVE = 51, B_NONE = 54, B_EPOCH = 55;

constexpr int QD1 = 8;
constexpr int QD2 = 2;
constexpr int QD3 = 8;
constexpr int QSW = 16;
constexpr int HEAD = 3;
constexpr int ST_T0 = 200;
constexpr int ST_DELAY = 300;
constexpr int XPOS = 32;
constexpr int K_T0 = 800;
constexpr int KV_T0 = 1500;
constexpr int KV_DT = 620;
constexpr int KV_DV = 450;
constexpr int POLL_NS = 30;
constexpr int GREEDY = 1;
constexpr int TAILB = 5;
constexpr int GREG = 168;
constexpr int COEF_T0 = 2500;
constexpr int T_ST = 2;
constexpr int PFC_T0 = 13500;
constexpr int PFC_T1 = 1500;
constexpr int PFC_DT = 400;
constexpr int KV_E = 6;
constexpr int KV_D2 = 300;
constexpr int CFM = 0x40f1;
constexpr int SPIN_LIMIT = 1 << 14;

struct Params {
  unsigned slot[16];
  unsigned zero;
  const __nv_bfloat16 *shift_k, *ssm_D, *lam_re, *lam_im, *log_dt, *Dskip;
  float* out;
};

__device__ __align__(1024) uint4 g_h[16 * 32 * 1024];
__device__ __align__(128) uint2 g_carry[32 * 16 * 32];
__device__ __align__(128) unsigned g_flagH[16 * 32];

__device__ __forceinline__ uint64_t make_desc(uint32_t addr, uint32_t lbo, uint32_t sbo, uint32_t swz) {
  return (uint64_t)((addr & 0x3FFFF) >> 4) | ((uint64_t)(lbo >> 4) << 16) | ((uint64_t)(sbo >> 4) << 32) | ((uint64_t)swz << 62);
}
__device__ __forceinline__ void wg_fence() { asm volatile("wgmma.fence.sync.aligned;" ::: "memory"); }
__device__ __forceinline__ void wg_commit() { asm volatile("wgmma.commit_group.sync.aligned;" ::: "memory"); }
template <int N> __device__ __forceinline__ void wg_wait() { asm volatile("wgmma.wait_group.sync.aligned %0;" ::"n"(N) : "memory"); }
__device__ __forceinline__ void mbar_init(uint32_t bar, int cnt) { asm volatile("mbarrier.init.shared::cta.b64 [%0], %1;" ::"r"(bar), "r"(cnt) : "memory"); }
__device__ __forceinline__ void mbar_expect(uint32_t bar, uint32_t bytes) { asm volatile("mbarrier.arrive.expect_tx.shared::cta.b64 _, [%0], %1;" ::"r"(bar), "r"(bytes) : "memory"); }
__device__ __forceinline__ bool mbar_try(uint32_t bar, uint32_t parity) {
  uint32_t ok;
  asm volatile("{\n.reg .pred p;\nmbarrier.try_wait.parity.shared::cta.b64 p, [%1], %2;\nselp.u32 %0, 1, 0, p;\n}\n" : "=r"(ok) : "r"(bar), "r"(parity) : "memory");
  return ok;
}
__device__ __forceinline__ void mbar_wait(uint32_t bar, uint32_t parity) {
  if (__builtin_expect(!mbar_try(bar, parity), 0)) {
#pragma unroll 1
    for (int n = 0; n < SPIN_LIMIT && !mbar_try(bar, parity); n++) {}
  }
}
__device__ __forceinline__ void mbar_arrive(uint32_t bar) { asm volatile("mbarrier.arrive.shared::cta.b64 _, [%0];" ::"r"(bar) : "memory"); }
__device__ __forceinline__ void mbar_arrive_cta(uint32_t bar, uint32_t cta) {
  asm volatile("{\n.reg .b32 ra;\nmapa.shared::cluster.u32 ra, %0, %1;\nmbarrier.arrive.shared::cluster.b64 _, [ra];\n}\n" ::"r"(bar), "r"(cta) : "memory");
}
__device__ __forceinline__ bool elect_one() {
  uint32_t p;
  asm volatile("{\n.reg .pred P;\nelect.sync _|P, 0xffffffff;\nselp.u32 %0, 1, 0, P;\n}\n" : "=r"(p));
  return p != 0;
}
__device__ __forceinline__ void bar_sync(int id, int n) { asm volatile("bar.sync %0, %1;" ::"r"(id), "r"(n) : "memory"); }
#define TMA_LD(dim) "cp.async.bulk.tensor." dim ".shared::cluster.global.mbarrier::complete_tx::bytes"
__device__ __forceinline__ void tma2d(uint32_t dst, const CUtensorMap* m, int c0, int c1, uint32_t bar) {
  asm volatile(TMA_LD("2d") " [%0], [%1, {%3, %4}], [%2];" ::"r"(dst), "l"(m), "r"(bar), "r"(c0), "r"(c1) : "memory");
}
__device__ __forceinline__ void tma3d(uint32_t dst, const CUtensorMap* m, int c0, int c1, int c2, uint32_t bar) {
  asm volatile(TMA_LD("3d") " [%0], [%1, {%3, %4, %5}], [%2];" ::"r"(dst), "l"(m), "r"(bar), "r"(c0), "r"(c1), "r"(c2) : "memory");
}
__device__ __forceinline__ void tma4d(uint32_t dst, const CUtensorMap* m, int c0, int c1, int c2, int c3, uint32_t bar) {
  asm volatile(TMA_LD("4d") " [%0], [%1, {%3, %4, %5, %6}], [%2];" ::"r"(dst), "l"(m), "r"(bar), "r"(c0), "r"(c1), "r"(c2), "r"(c3) : "memory");
}
__device__ __forceinline__ void tma4d_mc(uint32_t dst, const CUtensorMap* m, int c0, int c1, int c2, int c3, uint32_t bar) {
  asm volatile(TMA_LD("4d") ".multicast::cluster [%0], [%1, {%3, %4, %5, %6}], [%2], %7;" ::"r"(dst), "l"(m), "r"(bar), "r"(c0), "r"(c1), "r"(c2), "r"(c3), "h"((uint16_t)3) : "memory");
}
__device__ __forceinline__ void tma5d_mc(uint32_t dst, const CUtensorMap* m, int c0, int c1, int c2, int c3, int c4, uint32_t bar) {
  asm volatile(TMA_LD("5d") ".multicast::cluster [%0], [%1, {%3, %4, %5, %6, %7}], [%2], %8;" ::"r"(dst), "l"(m), "r"(bar), "r"(c0), "r"(c1), "r"(c2), "r"(c3), "r"(c4), "h"((uint16_t)3) : "memory");
}
__device__ __forceinline__ void bulk_load(uint32_t dst, const void* src, uint32_t bytes, uint32_t bar) {
  asm volatile("cp.async.bulk.shared::cluster.global.mbarrier::complete_tx::bytes [%0], [%1], %2, [%3];" ::"r"(dst), "l"(src), "r"(bytes), "r"(bar) : "memory");
}
__device__ __forceinline__ void bulk_send(uint32_t dst, uint32_t src, uint32_t bytes, uint32_t bar, uint32_t cta) {
  asm volatile("{\n.reg .b32 rd, rb;\nmapa.shared::cluster.u32 rd, %0, %3;\nmapa.shared::cluster.u32 rb, %2, %3;\n"
               "cp.async.bulk.shared::cluster.shared::cta.mbarrier::complete_tx::bytes [rd], [%1], %4, [rb];\n}\n"
               ::"r"(dst), "r"(src), "r"(bar), "r"(cta), "r"(bytes) : "memory");
}
__device__ __forceinline__ void fence_proxy_async_smem() { asm volatile("fence.proxy.async.shared::cta;" ::: "memory"); }
__device__ __forceinline__ void fence_proxy_async_global() { asm volatile("fence.proxy.async.global;" ::: "memory"); }
__device__ __forceinline__ uint32_t clk32() { uint32_t c; asm volatile("mov.u32 %0, %%clock;" : "=r"(c)::"memory"); return c; }
__device__ __forceinline__ void wait_until(uint32_t t0, uint32_t dt) { while (clk32() - t0 < dt) __nanosleep(32); }
__device__ __forceinline__ void spin_until(uint32_t t0, uint32_t dt) { while (clk32() - t0 < dt) {} }
__device__ __forceinline__ void prefetch_map(const CUtensorMap* m) { asm volatile("prefetch.tensormap [%0];" ::"l"(m) : "memory"); }
__device__ __forceinline__ void prefetch_line(const void* p) { asm volatile("prefetch.global.L2 [%0];" ::"l"(p) : "memory"); }
__device__ __forceinline__ unsigned ld_acquire(const unsigned* p) { unsigned v; asm volatile("ld.acquire.gpu.global.u32 %0, [%1];" : "=r"(v) : "l"(p) : "memory"); return v; }
__device__ __forceinline__ unsigned ld_relaxed(const unsigned* p) { unsigned v; asm volatile("ld.relaxed.gpu.global.u32 %0, [%1];" : "=r"(v) : "l"(p) : "memory"); return v; }
__device__ __forceinline__ uint32_t lds32(uint32_t a) { uint32_t v; asm volatile("ld.shared.u32 %0, [%1];" : "=r"(v) : "r"(a)); return v; }
__device__ __forceinline__ uint2 lds64(uint32_t a) { uint2 v; asm volatile("ld.shared.v2.u32 {%0,%1}, [%2];" : "=r"(v.x), "=r"(v.y) : "r"(a) : "memory"); return v; }
__device__ __forceinline__ uint4 lds128(uint32_t a) { uint4 v; asm volatile("ld.shared.v4.u32 {%0,%1,%2,%3}, [%4];" : "=r"(v.x), "=r"(v.y), "=r"(v.z), "=r"(v.w) : "r"(a) : "memory"); return v; }
__device__ __forceinline__ void sts32(uint32_t a, uint32_t v) { asm volatile("st.shared.u32 [%0], %1;" ::"r"(a), "r"(v) : "memory"); }
__device__ __forceinline__ void sts128(uint32_t a, uint4 v) { asm volatile("st.shared.v4.u32 [%0], {%1,%2,%3,%4};" ::"r"(a), "r"(v.x), "r"(v.y), "r"(v.z), "r"(v.w) : "memory"); }
__device__ __forceinline__ void ldsm4(uint32_t* r, uint32_t a) { asm volatile("ldmatrix.sync.aligned.m8n8.x4.shared.b16 {%0,%1,%2,%3}, [%4];" : "=r"(r[0]), "=r"(r[1]), "=r"(r[2]), "=r"(r[3]) : "r"(a) : "memory"); }
__device__ __forceinline__ void ldsm4t(uint32_t* r, uint32_t a) { asm volatile("ldmatrix.sync.aligned.m8n8.x4.trans.shared.b16 {%0,%1,%2,%3}, [%4];" : "=r"(r[0]), "=r"(r[1]), "=r"(r[2]), "=r"(r[3]) : "r"(a) : "memory"); }
__device__ __forceinline__ void stsm4t(uint32_t a, uint32_t r0, uint32_t r1, uint32_t r2, uint32_t r3) {
  asm volatile("stmatrix.sync.aligned.m8n8.x4.trans.shared.b16 [%0], {%1,%2,%3,%4};" ::"r"(a), "r"(r0), "r"(r1), "r"(r2), "r"(r3) : "memory");
}
__device__ __forceinline__ uint4 ldg128_nc(const void* p) { uint4 v; asm volatile("ld.global.nc.L1::no_allocate.v4.u32 {%0,%1,%2,%3}, [%4];" : "=r"(v.x), "=r"(v.y), "=r"(v.z), "=r"(v.w) : "l"(p)); return v; }
__device__ __forceinline__ void stg128(void* p, uint4 v) { asm volatile("st.global.L1::no_allocate.v4.u32 [%0], {%1,%2,%3,%4};" ::"l"(p), "r"(v.x), "r"(v.y), "r"(v.z), "r"(v.w) : "memory"); }
__device__ __forceinline__ uint32_t pack_bf16(float lo, float hi) { uint32_t r; asm("cvt.rn.bf16x2.f32 %0, %1, %2;" : "=r"(r) : "f"(hi), "f"(lo)); return r; }
__device__ __forceinline__ uint32_t bmul2(uint32_t a, uint32_t b) { uint32_t r; asm("mul.rn.bf16x2 %0, %1, %2;" : "=r"(r) : "r"(a), "r"(b)); return r; }
__device__ __forceinline__ uint32_t bfma2(uint32_t a, uint32_t b, uint32_t c) { uint32_t r; asm("fma.rn.bf16x2 %0, %1, %2, %3;" : "=r"(r) : "r"(a), "r"(b), "r"(c)); return r; }
__device__ __forceinline__ uint32_t blo2(uint32_t a) { uint32_t r; asm("{\n.reg .b16 l, h;\nmov.b32 {l, h}, %1;\nmov.b32 %0, {l, l};\n}" : "=r"(r) : "r"(a)); return r; }
__device__ __forceinline__ float bf2f(__nv_bfloat16 v) { return __bfloat162float(v); }

#define R8(d, o) "+f"(d[o]), "+f"(d[o + 1]), "+f"(d[o + 2]), "+f"(d[o + 3]), "+f"(d[o + 4]), "+f"(d[o + 5]), "+f"(d[o + 6]), "+f"(d[o + 7])
#define R16(d, o) R8(d, o), R8(d, o + 8)
#define R64(d, o) R16(d, o), R16(d, o + 16), R16(d, o + 32), R16(d, o + 48)
template <int TA> __device__ __forceinline__ void wgmma_n128(float* d, uint64_t da, uint64_t db, int scale_d) {
  asm volatile("{\n.reg .pred p;\nsetp.ne.b32 p, %66, 0;\n"
    "wgmma.mma_async.sync.aligned.m64n128k16.f32.bf16.bf16 {"
    "%0,%1,%2,%3,%4,%5,%6,%7,%8,%9,%10,%11,%12,%13,%14,%15,%16,%17,%18,%19,%20,%21,%22,%23,%24,%25,%26,%27,%28,%29,%30,%31,"
    "%32,%33,%34,%35,%36,%37,%38,%39,%40,%41,%42,%43,%44,%45,%46,%47,%48,%49,%50,%51,%52,%53,%54,%55,%56,%57,%58,%59,%60,%61,%62,%63"
    "}, %64, %65, p, 1, 1, %67, 0;\n}\n"
    : R64(d, 0)
    : "l"(da), "l"(db), "r"(scale_d), "n"(TA));
}
template <int N> __device__ __forceinline__ void fence_regs(float* d) {
#pragma unroll
  for (int i = 0; i < N; i++) asm volatile("" : "+f"(d[i])::"memory");
}
#define PMFENCE() asm volatile("pmevent 0;" ::: "memory")
__device__ __forceinline__ void cmul(float ar, float ai, float br, float bi, float& cr, float& ci) {
  cr = ar * br - ai * bi; ci = ar * bi + ai * br;
}
__device__ __forceinline__ void csq(float& r, float& i) { const float x = fmaf(r, r, -i * i), y = r * i; r = x; i = y + y; }

#define W8(d, o) "=f"(d[o]), "=f"(d[o + 1]), "=f"(d[o + 2]), "=f"(d[o + 3]), "=f"(d[o + 4]), "=f"(d[o + 5]), "=f"(d[o + 6]), "=f"(d[o + 7])
#define L16 "{%0,%1,%2,%3,%4,%5,%6,%7,%8,%9,%10,%11,%12,%13,%14,%15}"
#define L32 "{%0,%1,%2,%3,%4,%5,%6,%7,%8,%9,%10,%11,%12,%13,%14,%15,%16,%17,%18,%19,%20,%21,%22,%23,%24,%25,%26,%27,%28,%29,%30,%31}"
template <int ACC, int TB> __device__ __forceinline__ void rs_n32(float* d, const uint32_t* a, uint64_t db) {
  if constexpr (ACC) asm volatile("wgmma.mma_async.sync.aligned.m64n32k16.f32.bf16.bf16 " L16 ", {%16,%17,%18,%19}, %20, 1, 1, 1, %21;" : R16(d, 0) : "r"(a[0]), "r"(a[1]), "r"(a[2]), "r"(a[3]), "l"(db), "n"(TB));
  else asm volatile("wgmma.mma_async.sync.aligned.m64n32k16.f32.bf16.bf16 " L16 ", {%16,%17,%18,%19}, %20, 0, 1, 1, %21;" : W8(d, 0), W8(d, 8) : "r"(a[0]), "r"(a[1]), "r"(a[2]), "r"(a[3]), "l"(db), "n"(TB));
}
template <int ACC, int TB> __device__ __forceinline__ void rs_n64(float* d, const uint32_t* a, uint64_t db) {
  if constexpr (ACC) asm volatile("wgmma.mma_async.sync.aligned.m64n64k16.f32.bf16.bf16 " L32 ", {%32,%33,%34,%35}, %36, 1, 1, 1, %37;" : R16(d, 0), R16(d, 16) : "r"(a[0]), "r"(a[1]), "r"(a[2]), "r"(a[3]), "l"(db), "n"(TB));
  else asm volatile("wgmma.mma_async.sync.aligned.m64n64k16.f32.bf16.bf16 " L32 ", {%32,%33,%34,%35}, %36, 0, 1, 1, %37;" : W8(d, 0), W8(d, 8), W8(d, 16), W8(d, 24) : "r"(a[0]), "r"(a[1]), "r"(a[2]), "r"(a[3]), "l"(db), "n"(TB));
}
template <int ACC> __device__ __forceinline__ void ss_n32_tt(float* d, uint64_t da, uint64_t db) {
  if constexpr (ACC) asm volatile("wgmma.mma_async.sync.aligned.m64n32k16.f32.bf16.bf16 " L16 ", %16, %17, 1, 1, 1, 1, 1;" : R16(d, 0) : "l"(da), "l"(db));
  else asm volatile("wgmma.mma_async.sync.aligned.m64n32k16.f32.bf16.bf16 " L16 ", %16, %17, 0, 1, 1, 1, 1;" : W8(d, 0), W8(d, 8) : "l"(da), "l"(db));
}
__device__ __forceinline__ void stsm4(uint32_t a, uint32_t r0, uint32_t r1, uint32_t r2, uint32_t r3) {
  asm volatile("stmatrix.sync.aligned.m8n8.x4.shared.b16 [%0], {%1,%2,%3,%4};" ::"r"(a), "r"(r0), "r"(r1), "r"(r2), "r"(r3) : "memory");
}
template <int N> __device__ __forceinline__ void fence_u32(uint32_t* d) {
#pragma unroll
  for (int i = 0; i < N; i++) asm volatile("" : "+r"(d[i])::"memory");
}
__device__ __forceinline__ void pack32(uint32_t* f, const float* z) {
#pragma unroll
  for (int i = 0; i < 16; i++) f[i] = pack_bf16(z[2 * i], z[2 * i + 1]);
}
template <int INV> __device__ __forceinline__ void twiddle(uint32_t* f, const uint32_t* tp, const uint32_t* ts) {
#pragma unroll
  for (int i = 0; i < 8; i++) {
    uint32_t x = f[2 * i + INV], y = f[2 * i + 1 - INV];
    x = bfma2(tp[i & 3], y, x); y = bfma2(ts[i & 3], x, y); x = bfma2(tp[i & 3], y, x);
    f[2 * i + INV] = x; f[2 * i + 1 - INV] = y;
  }
}
__device__ __forceinline__ uint32_t bfnma2(uint32_t a, uint32_t b, uint32_t c) { uint32_t r; asm("{\n.reg .b32 t;\nmul.bf16x2 t, %1, %2;\nsub.bf16x2 %0, %3, t;\n}" : "=r"(r) : "r"(a), "r"(b), "r"(c)); return r; }
__device__ __forceinline__ uint32_t bfms2(uint32_t a, uint32_t b, uint32_t c) { uint32_t r; asm("{\n.reg .b32 t;\nmul.bf16x2 t, %1, %2;\nsub.bf16x2 %0, t, %3;\n}" : "=r"(r) : "r"(a), "r"(b), "r"(c)); return r; }
template <int ADD> __device__ __forceinline__ void bimac(uint32_t* o, const uint32_t* a, const uint32_t* b, const uint32_t* c) {
#pragma unroll
  for (int J = 0; J < 2; J++) {
    const uint32_t Pr = a[2 * J], Pi = a[2 * J + 1], Qr = a[2 * J + 4], Qi = a[2 * J + 5], pr = b[2 * J], pi = b[2 * J + 1], qr = b[2 * J + 4], qi = b[2 * J + 5];
    uint32_t x0, x1, x2, x3;
    if (ADD == 0) { x0 = bmul2(Pr, pr); x1 = bmul2(Pr, pi); x2 = bmul2(Pr, qr); x3 = bmul2(Pr, qi); }
    if (ADD == 1) { x0 = bfma2(Pr, pr, c[2 * J]); x1 = bfma2(Pr, pi, c[2 * J + 1]); x2 = bfma2(Pr, qr, c[2 * J + 4]); x3 = bfma2(Pr, qi, c[2 * J + 5]); }
    if (ADD == 2) { x0 = bfma2(Pr, pr, c[2 * J + 1]); x1 = bfms2(Pr, pi, c[2 * J]); x2 = bfma2(Pr, qr, c[2 * J + 5]); x3 = bfms2(Pr, qi, c[2 * J + 4]); }
    x0 = bfnma2(Pi, pi, x0); x1 = bfma2(Pi, pr, x1); x2 = bfnma2(Pi, qi, x2); x3 = bfma2(Pi, qr, x3);
    x0 = bfnma2(Qr, qr, x0); x1 = bfnma2(Qr, qi, x1); x2 = bfma2(Qr, pr, x2); x3 = bfma2(Qr, pi, x3);
    x0 = bfma2(Qi, qi, x0); x1 = bfnma2(Qi, qr, x1); x2 = bfnma2(Qi, pi, x2); x3 = bfma2(Qi, pr, x3);
    o[2 * J] = x0; o[2 * J + 1] = x1; o[2 * J + 4] = x2; o[2 * J + 5] = x3;
  }
}
__device__ __forceinline__ void sincos8k(int n, float& s, float& c) {
  const float x = (float)((n << 19) >> 19) * (6.283185307179586f / 8192.f);
  s = __sinf(x); c = __cosf(x);
}
__device__ __forceinline__ void fft_tables(uint32_t f1a, uint32_t f2a, int w, int lane, uint32_t* tp, uint32_t* ts, float& d0r, float& d0i) {
  const int c = lane & 3, f1 = 8 * w + (lane >> 2);
#pragma unroll 1
  for (int J = 3; J >= 0; J--) {
    const int a = 8 * J + 2 * c;
    float s0, c0, s1, c1;
    sincos8k(64 * (4 * f1 + 1) * a + 31 * (4 * f1 - 63), d0i, d0r); sincos8k(64 * (4 * f1 + 1) * (a + 1) + 31 * (4 * f1 - 63), s1, c1);
    d0r *= 0.125f; d0i *= 0.125f;
    sts32(f1a + w * 1024 + J * 128 + lane * 4, pack_bf16(d0r, 0.125f * c1)); sts32(f1a + w * 1024 + 512 + J * 128 + lane * 4, pack_bf16(d0i, 0.125f * s1));
    sincos8k(128 * (2 * (a & 15) + 1) * f1 - 128 * (a & 16), s0, c0); sincos8k(128 * (2 * (a & 15) + 3) * f1 - 128 * (a & 16), s1, c1);
    sts32(f2a + w * 512 + J * 128 + lane * 4, pack_bf16(c0, c1));
    sincos8k((4 * f1 - 63) * (2 * a - 31), s0, c0); sincos8k((4 * f1 - 63) * (2 * a - 29), s1, c1);
#pragma unroll
    for (int i = 3; i > 0; i--) { ts[i] = ts[i - 1]; tp[i] = tp[i - 1]; }
    ts[0] = pack_bf16(s0, s1); tp[0] = pack_bf16(-__fdividef(s0, 1.f + c0), -__fdividef(s1, 1.f + c1));
  }
  if (c != 0) d0r = d0i = 0.f;
}

__device__ __forceinline__ void ss_n16_in(float* d, uint64_t da, uint64_t db, uint32_t zero) {
  asm volatile("{\n.reg .pred p;\nsetp.ne.b32 p, %10, 0;\nwgmma.mma_async.sync.aligned.m64n16k16.f32.bf16.bf16 {%0,%1,%2,%3,%4,%5,%6,%7}, %8, %9, p, 1, 1, 0, 0;\n}\n" : R8(d, 0) : "l"(da), "l"(db), "r"(zero));
}
__device__ __forceinline__ void ss_n16(float* d, uint64_t da, uint64_t db) {
  asm volatile("wgmma.mma_async.sync.aligned.m64n16k16.f32.bf16.bf16 {%0,%1,%2,%3,%4,%5,%6,%7}, %8, %9, 0, 1, 1, 0, 0;" : W8(d, 0) : "l"(da), "l"(db));
}
template <int N> __device__ __forceinline__ void rename_regs(float* d) {
#pragma unroll
  for (int i = 0; i < N; i++) { float t; asm volatile("mov.b32 %0, %1;" : "=f"(t) : "f"(d[i]) : "memory"); d[i] = t; }
}

template <int SWAPB>
__global__ void __cluster_dims__(2, 1, 1) __launch_bounds__(512, 1)
fused_kernel(const __grid_constant__ Params P, const __grid_constant__ CUtensorMap mX, const __grid_constant__ CUtensorMap mB,
             const __grid_constant__ CUtensorMap mCre, const __grid_constant__ CUtensorMap mCim, const __grid_constant__ CUtensorMap mXs,
             const __grid_constant__ CUtensorMap mK, const __grid_constant__ CUtensorMap mV, const __grid_constant__ CUtensorMap mQ, const __grid_constant__ CUtensorMap mS,
             const __grid_constant__ CUtensorMap mO) {
  extern __shared__ __align__(1024) uint8_t smem_raw[];
  if (threadIdx.x == 0) { prefetch_map(&mX); prefetch_map(&mB); }
  const uint32_t sb = (uint32_t)__cvta_generic_to_shared(smem_raw);
  const uint32_t bars = sb + OFF_BAR;
  const int slot = (P.slot[blockIdx.x >> 3] >> (4 * (blockIdx.x & 6))) & 63, rank = blockIdx.x & 1;
  const int j = slot & 7, tc = 2 * (slot >> 3) + rank, b = 2 * slot + rank;
  const int tid = threadIdx.x;
  const int warp = __shfl_sync(0xffffffffu, tid >> 5, 0);
  const int wg = warp >> 2;
  const uint32_t c_start = clk32();
  auto kblock = [&](int n) { return ((n & 14) == 0 || (n & 14) == 2 * j ? n ^ (2 * j) : n) & 31; };
  auto send_y = [&](int r) {
    const uint32_t src = sb + OFF_U + 4 * (rank ^ 1) * U_N8 + r * U_CH, dst = r >= 2 ? sb + OFF_U + 4 * rank * U_N8 + (r - 2) * U_CH : sb + OFF_IN + 96 + r * 2064;
#pragma unroll 1
    for (int n = 0; n < 4; n++) bulk_send(dst + n * (r >= 2 ? U_N8 : 512), src + n * U_N8, 512, bars + (B_IN + r) * 8, rank ^ 1);
  };
  auto load_q = [&](int i, int off, int bar) {
    const uint32_t fb = bars + bar * 8 + 4 * (i & 2);
    mbar_expect(fb, 4096); tma4d(sb + off + 2048 * (i & 2), &mQ, 16 * slot, 0, 4 * i, 4 * rank, fb);
  };
  auto head = [&](int n) {
    const uint32_t fb = bars + (B_FULL + n) * 8, dst = sb + OFF_RING + n * STAGE_BYTES;
    mbar_expect(fb, STAGE_BYTES);
    tma4d(dst + 16384, &mX, 64 * n, 0, 4 * tc, 0, fb);
    tma4d(dst, &mB, 64 * n, 0, 0, 8 * j, fb);
    tma4d(dst + 8192, &mB, 64 * n, 0, 0, 8 * j + 4, fb);
  };
  if (warp == 0 && elect_one()) {
#pragma unroll
    for (int s = 0; s < STAGES; s++) mbar_init(bars + (B_FULL + s) * 8, 1);
    head(0);
    asm volatile("fence.mbarrier_init.release.cluster;" ::: "memory");
  }
  if (wg == 3 && elect_one()) {
    if (warp < 15) {
#pragma unroll
      for (int s = 0; s < 13; s++) mbar_init(bars + 8 * B_XI + (warp & 3) * 104 + 8 * s, 1);
    } else {
#pragma unroll
      for (int s = B_XI + 39; s <= B_NONE; s++) mbar_init(bars + 8 * s, s < B_EMPTY ? 1 : s < B_COEF ? 2 : s == B_COEF ? 128 : 4);
    }
    asm volatile("fence.mbarrier_init.release.cluster;" ::: "memory");
  }
  __syncwarp();
  asm volatile("barrier.cluster.arrive.relaxed.aligned;" ::: "memory");
  if (warp == 0 && elect_one()) {
#pragma unroll 1
    for (int n = 1; n < HEAD; n++) { spin_until(c_start, ST_T0 + n * ST_DELAY); head(n); }
  }
  __syncwarp();
  int fl;
  uint32_t fa, fs;
  uint2 q[4][4];
  auto fin_setup = [&]() {
    asm volatile("mov.u32 %0, %%laneid;" : "=r"(fl));
    const int lc = 2 * (fl & 2) + (fl & 1) + ((fl >> 2) & 2);
    const bool own = ((fl >> 2) & 1) == rank, spare = !own && lc < 2;
    fa = (spare ? sb + OFF_IN + 96 + lc * 2064 : sb + OFF_U + (own ? 4 * rank * U_N8 : 4 * (rank ^ 1) * U_N8 - 2 * U_CH) + lc * U_CH) + (warp & 3) * 128 + (fl >> 4) * 16 + (wg & 1) * 64;
    fs = spare ? 512 : U_N8;
  };
  auto get_q = [&](int n, int off, int bar, int ph) {
#pragma unroll
    for (int u = 0; u < 2; u++) {
      mbar_wait(bars + (bar + u) * 8, ph);
#pragma unroll
      for (int r = 0; r < 4; r++) q[n + u][r] = lds64(sb + off + 4096 * u + 1024 * (warp & 3) + 256 * r + 8 * fl);
    }
  };
#define CLUSTER_WAIT() asm volatile("barrier.cluster.wait.aligned;" ::: "memory")

  if (wg == 3) {
    asm volatile("setmaxnreg.dec.sync.aligned.u32 24;");
    CLUSTER_WAIT();
    if (warp < 14) {
      if (elect_one()) {
        uint32_t so = 8 * (HEAD % STAGES), ph = HEAD < STAGES;
        auto step = [&](auto issue) {
          mbar_wait(bars + B_EMPTY * 8 + so, ph);
          issue(sb + OFF_RING + (so << 12), bars + B_FULL * 8 + so);
          so += 8;
          if (so == 8 * STAGES) { so = 0; ph ^= 1; }
        };
        if (warp == 12) {
          auto g1 = [&](int n0, int n1, int grp) {
#pragma unroll 1
            for (int n = n0; n < n1; n++) step([&](uint32_t dst, uint32_t fb) { mbar_expect(fb, STAGE_BYTES); tma4d_mc(dst + rank * 8192, &mB, n * 64, 0, 0, grp + 4 * rank, fb); });
          };
#pragma unroll 1
          for (int n = HEAD; n < STAGES; n++) { spin_until(c_start, ST_T0 + n * ST_DELAY); g1(n, n + 1, 8 * j); }
          g1(STAGES, 16, 8 * j);
          g1(0, XPOS - 16, 8 * j + 64);
          step([&](uint32_t dst, uint32_t fb) { mbar_expect(fb, STAGE_BYTES); tma4d(dst, &mXs, 128 * j, 0, 4 * tc, 0, fb); });
#pragma unroll 1
          for (int n = 0; n < 32; n += 2) {
            const int col = kblock(n) * 32;
#pragma unroll
            for (int part = 0; part < 2; part++)
              step([&](uint32_t dst, uint32_t fb) { mbar_expect(fb, STAGE_BYTES); tma5d_mc(dst + rank * 8192, part ? &mCim : &mCre, col, 0, 0, 0, 8 * j + 4 * rank, fb); });
          }
        } else {
          auto g1 = [&](int n0, int n1, int nb) {
#pragma unroll 1
            for (int n = n0; n < n1; n++) step([&](uint32_t dst, uint32_t fb) { tma4d(dst + 16384, &mX, n * 64, 0, 4 * tc, 0, fb); });
          };
          auto g2 = [&](int n0, int n1) {
#pragma unroll 1
            for (int n = n0; n < n1; n++) step([&](uint32_t dst, uint32_t fb) { bulk_load(dst + 16384, g_h + (32 * tc + kblock(n)) * 1024, 16384, fb); });
          };
#pragma unroll 1
          for (int n = HEAD; n < STAGES; n++) { spin_until(c_start, ST_T0 + n * ST_DELAY); g1(n, n + 1, 0); }
          g1(STAGES, 16, 0);
          g1(0, XPOS - 16, 16);
          step([&](uint32_t dst, uint32_t fb) { tma4d(dst + 16384, &mXs, 128 * j + 64, 0, 4 * tc, 0, fb); });
#pragma unroll 1
          for (int v = 0; v < 2; v++) {
            mbar_wait(bars + B_HP * 8, v);
            fence_proxy_async_global();
            g2(16 * v, 16 * v + 2);
            mbar_wait(bars + B_HR * 8, v);
            fence_proxy_async_global();
            g2(16 * v + 2, 16 * v + 16);
          }
        }
      }
    } else if (warp == 15) {
      mbar_wait(bars + B_COEF * 8, 0);
      const unsigned epoch = lds32(bars + B_EPOCH * 8);
#pragma unroll 1
      for (int v = 0; v < 2; v++) {
        unsigned* fp = &g_flagH[tc * 32 + v];
        if (elect_one()) {
          wait_until(v ? clk32() : c_start, (v ? PFC_T1 : PFC_T0) + (slot >> 3) * PFC_DT);
#pragma unroll
          for (int part = 0; part < 2; part++)
            asm volatile("cp.async.bulk.prefetch.tensor.5d.L2.global [%0, {%1, %2, %2, %2, %3}];" ::"l"(part ? &mCim : &mCre), "r"(512 * v + 8 * (slot & 56)), "r"(0), "r"(8 * j + 4 * rank) : "memory");
        }
        __syncwarp();
        bar_sync(4 + v, 160);
        if (elect_one()) {
          asm volatile("red.release.gpu.global.add.u32 [%0], 1;" ::"l"(fp) : "memory");
          mbar_arrive(bars + B_HP * 8);
          int it = 0;
          while (ld_acquire(fp) != 8 * epoch && ++it < (SPIN_LIMIT << 4)) __nanosleep(POLL_NS);
          mbar_arrive(bars + B_HR * 8);
        }
        __syncwarp();
      }
    } else if (elect_one()) {
      const int ch0 = 16 * slot;
      auto load_k = [&](int s, uint32_t dst) { const uint32_t fb = bars + (B_KF + s) * 8; mbar_expect(fb, 4096); tma2d(dst, &mS, 0, 64 * (8 * b + s), fb); };
      prefetch_map(&mS); prefetch_map(&mK); prefetch_map(&mV);
      wait_until(c_start, K_T0);
      load_k(0, sb + OFF_U + (4 * rank + 3) * U_N8); load_k(1, sb + OFF_U + (4 * rank + 3) * U_N8 - 4096);
      {
        uint32_t so = 16, ph = 1;
#pragma unroll 1
        for (int e = 0; e < 9; e++) {
          const uint32_t fb = bars + B_KVF * 8 + so, dst = sb + OFF_KV + (so << 10);
          wait_until(c_start, KV_T0 + (e ? 2 * e - 1 : 0) * KV_DT - (e > KV_E ? e - KV_E : 0) * 2 * (KV_DT - KV_D2));
          mbar_wait(bars + B_KVE * 8 + so, ph);
          const uint32_t c1 = clk32();
          mbar_expect(fb, e ? 8192 : 4096);
          tma3d(dst, &mK, ch0, 32 * rank - (e == 0), (4 * e - 4) & 31, fb);
          if (e > 0) { wait_until(c1, KV_DV); tma3d(dst + 4096, &mV, ch0, 32 * rank, 4 * e - 4, fb); }
          so += 8;
          if (so == 24) so = 0;
          if (so == 16) ph ^= 1;
        }
      }
      prefetch_map(&mCre); prefetch_map(&mCim); prefetch_map(&mXs); prefetch_map(&mQ); prefetch_map(&mO);
      mbar_wait(bars + B_KVE * 8, 0);
      load_k(2, sb + OFF_K); load_k(3, sb + OFF_K + 4096);
      mbar_wait(bars + (B_UF + 3) * 8, 0);
#pragma unroll 1
      for (int ch = 0; ch < 7; ch++) {
        mbar_wait(bars + (B_ST + ch) * 8, 0);
        if (ch > 2) mbar_wait(bars + (B_IN + ch - 3) * 8, 0);
        if (ch < 4) load_k(ch + 4, sb + OFF_K + (ch & 1) * 4096);
        else if (ch < 6) load_q(2 * (ch & 1), OFF_K, B_KF + 8);
        if (ch > 0) send_y(ch - 1);
        if (ch == 2) load_q(1, OFF_Q, B_QF);
        if (ch == 3) asm volatile("cp.async.bulk.prefetch.tensor.4d.L2.global [%0, {%1, %2, %3, %4}];" ::"l"(&mQ), "r"(16 * (slot & ~3)), "r"(0), "r"(16 + 4 * (slot & 3)), "r"(4 * rank) : "memory");
        if (ch == 4) { mbar_wait(bars + B_XI * 8, 0); load_q(3, OFF_Q, B_QF); }
      }
    }
    return;
  } else if (wg == 2) {
    asm volatile("setmaxnreg.inc.sync.aligned.u32 %0;" ::"n"(488 - 2 * GREG));
    const int t = tid & 127, w = warp & 3, lane = t & 31, g = lane >> 2, c = lane & 3;
    const uint4 s2[2] = {ldg128_nc(P.shift_k + (8 * b + 2 * c) * 4), ldg128_nc(P.shift_k + (8 * (b ^ 1) + 2 * c) * 4)};
    const uint32_t dskip = __bfloat16_as_ushort(P.ssm_D[8 * b + (t & 7)]);
    uint32_t tp[4] = {}, ts[4] = {};
    float d0r, d0i;
    fft_tables(sb + OFF_F1, sb + OFF_F2, w, lane, tp, ts, d0r, d0i);
    CLUSTER_WAIT();
    if (t < 12) mbar_expect(bars + (B_IN + t) * 8, t < 6 ? 2048 : t < 8 ? 4 * (U_CH + 512) : U_N8);
    if (t < 8) sts32(sb + OFF_D + 8 * t, dskip << 16);
    const uint64_t dF1b = make_desc(sb + OFF_F1, 512, 128, 0);
    const uint64_t dF2f = make_desc(sb + OFF_F2, 512, 128, 0), dF2i = make_desc(sb + OFF_F2, 128, 512, 0);
    uint32_t f1[8];
#pragma unroll
    for (int i = 0; i < 8; i++) f1[i] = lds32(sb + OFF_F1 + w * 1024 + (i & 1) * 512 + (i >> 1) * 128 + lane * 4);
    auto T1k = [&](float* z, uint64_t dk) { wg_fence(); rs_n64<0, 1>(z, f1, dk); rs_n64<1, 1>(z, f1 + 4, dk + 64); wg_commit(); };
    auto T1u = [&](float* z, uint64_t du) { wg_fence(); rs_n64<0, 0>(z, f1, du); rs_n64<1, 0>(z, f1 + 4, du + 16); wg_commit(); };
    auto T2 = [&](float* s, const uint32_t* f) {
      wg_fence();
      rs_n32<0, 1>(s, f, dF2f); rs_n32<0, 1>(s + 16, f + 8, dF2f); rs_n32<1, 1>(s, f + 4, dF2f + 64); rs_n32<1, 1>(s + 16, f + 12, dF2f + 64);
      wg_commit();
    };
    auto product = [&](uint32_t* pr, const uint32_t* kh, const uint32_t* uh) {
      bimac<0>(pr, kh, uh, pr); bimac<2>(pr + 8, kh + 8, uh, pr); bimac<1>(pr + 8, kh, uh + 8, pr + 8);
      fence_u32<16>(pr);
    };
    float zk[32] = {};
    uint32_t pr[16];
    {
      uint32_t kh0[16];
      {
        float z0[32], sk[32];
        uint32_t fk[16];
        const uint64_t dk = make_desc(sb + OFF_U + (4 * rank + 3) * U_N8, 2048, 512, 2);
        fence_proxy_async_smem();
        bar_sync(7, 128);
        mbar_wait(bars + B_KF * 8, 0);
        T1k(z0, dk);
        mbar_wait(bars + (B_KF + 1) * 8, 0);
        T1k(zk, dk - 256);
        wg_wait<0>(); fence_regs<32>(z0); fence_regs<32>(zk);
        const float dd = __uint_as_float(lds32(sb + OFF_D));
        z0[0] = fmaf(d0r, dd, z0[0]); z0[2] = fmaf(d0i, dd, z0[2]);
        pack32(fk, z0); twiddle<0>(fk, tp, ts); fence_u32<16>(fk);
        T2(sk, fk);
        wg_wait<0>(); fence_regs<32>(sk); fence_u32<16>(fk);
        pack32(kh0, sk); fence_u32<16>(kh0);
      }
      {
        uint32_t sk[2][4], kx[2][8];
#pragma unroll
        for (int o = 0; o < 2; o++) {
          sk[o][0] = __byte_perm(s2[o].x, s2[o].z, 0x5410); sk[o][1] = __byte_perm(s2[o].x, s2[o].z, 0x7632);
          sk[o][2] = __byte_perm(s2[o].y, s2[o].w, 0x5410); sk[o][3] = __byte_perm(s2[o].y, s2[o].w, 0x7632);
        }
        const uint32_t la = sb + OFF_KV + (lane >> 3) * 1024 + (8 * w + (lane & 7)) * 32 + ((rank ^ ((lane >> 2) & 1)) << 4);
        const uint32_t uo = (lane & 7) * U_CH + w * 128 + (lane >> 3) * 16;
        mbar_wait(bars + (B_KVF + 2) * 8, 0);
        ldsm4(kx[0], la + 16384); ldsm4(kx[1], (la ^ 16) + 16384);
        if (lane == 0) mbar_arrive(bars + (B_KVE + 2) * 8 + (kx[0][1] & kx[1][1] & P.zero));
        uint32_t so = 0, ph = 0;
#pragma unroll 1
        for (int n = 0; n < 4; n++) {
          const uint32_t own = sb + OFF_U + (4 * rank + n) * U_N8, box = n < 3 ? sb + OFF_U + (4 * (rank ^ 1) + n + 1) * U_N8 : sb + OFF_IN;
#pragma unroll
          for (int e = 0; e < 2; e++) {
            uint32_t vx[2][4];
            mbar_wait(bars + B_KVF * 8 + so, ph);
#pragma unroll
            for (int o = 0; o < 2; o++) { ldsm4(kx[o] + 4, (la ^ (16 * o)) + (so << 10)); ldsm4(vx[o], (la ^ (16 * o)) + (so << 10) + 4096); }
            if (lane == 0) mbar_arrive(bars + B_KVE * 8 + so + (kx[0][4] & kx[1][4] & vx[0][0] & vx[1][0] & P.zero));
#pragma unroll
            for (int o = 0; o < 2; o++) {
#pragma unroll
              for (int i = 0; i < 4; i++) vx[o][i] = bmul2(bfma2(kx[o][i + 4], sk[o][0], bfma2(kx[o][i + 3], sk[o][1], bfma2(kx[o][i + 2], sk[o][2], bmul2(kx[o][i + 1], sk[o][3])))), vx[o][i]);
              stsm4t((o ? box : own) + uo + e * 64, vx[o][0], vx[o][1], vx[o][2], vx[o][3]);
              kx[o][1] = kx[o][5]; kx[o][2] = kx[o][6]; kx[o][3] = kx[o][7];
            }
            so += 8;
            if (so == 24) so = 0;
            if (so == 16) ph ^= 1;
          }
          fence_proxy_async_smem();
          bar_sync(7, 128);
          if (w == 0 && elect_one()) {
            if (n > 0) mbar_wait(bars + B_UF * 8 + 8 * (n - 1), 0);
            bulk_send(own, box, U_N8, bars + B_UF * 8 + 8 * n, rank ^ 1);
          }
          __syncwarp();
        }
      }
      float zu[32], su[32];
      uint32_t fu[16], uh[16];
#pragma unroll
      for (int n = 0; n < 4; n++) mbar_wait(bars + (B_UF + n) * 8, 0);
      T1u(zu, make_desc(sb + OFF_U, 128, U_N8, 0));
      wg_wait<0>(); fence_regs<32>(zu);
      pack32(fu, zu); twiddle<0>(fu, tp, ts); fence_u32<16>(fu);
      T2(su, fu);
      wg_wait<0>(); fence_regs<32>(su); fence_u32<16>(fu);
      pack32(uh, su);
      product(pr, kh0, uh);
    }
    {
#define CF(i) do { if ((CFM >> (i)) & 1) PMFENCE(); } while (0)
      const uint32_t vs = w < 2 ? 512 : U_N8, vi = (w >> 1) * U_CH;
      uint32_t va = (w < 2 ? sb + OFF_VP : sb + OFF_U) + ((lane >> 4) & 1) * vs + (w & 1) * 256 + (lane & 15) * 16;
      const uint32_t ya = sb + OFF_U + (2 * w + ((lane >> 3) & 1)) * U_N8 + (lane >> 4) * 128 + (lane & 7) * 16;
      uint64_t du = make_desc(sb + OFF_U, 128, U_N8, 0), dk = make_desc(sb + OFF_K, 2048, 512, 2);
      const uint64_t dv = make_desc(sb + OFF_VP, 128, 512, 0), dks = 2 * dk + 256;
      uint32_t yp[8] = {};
      uint32_t yq = sb + OFF_Q + lane * 16, yi = ya - yq;
      auto store_y = [&]() { stsm4(yq, yp[0], yp[1], yp[2], yp[3]); stsm4(yq + 256, yp[4], yp[5], yp[6], yp[7]); };
      auto step = [&](uint32_t c8, auto fwd) {
        constexpr bool FWD = decltype(fwd)::value;
        float zu[32], sk[32], su[32], v[32], y[16];
        uint32_t kh[16], uh[16], fk[16], fu[16], fv[16];
        wg_fence();
        rs_n32<0, 0>(v, pr, dF2i); rs_n32<0, 0>(v + 16, pr + 8, dF2i); rs_n32<1, 0>(v, pr + 4, dF2i + 16); rs_n32<1, 0>(v + 16, pr + 12, dF2i + 16);
        wg_commit();
        CF(0);
        const float dd = FWD ? __uint_as_float(lds32(sb + OFF_D + 8 + c8)) : 0.f;
        store_y();
        if (FWD) {
          zk[0] = fmaf(d0r, dd, zk[0]); zk[2] = fmaf(d0i, dd, zk[2]);
          pack32(fk, zk); twiddle<0>(fk, tp, ts); fence_u32<16>(fk);
          T2(sk, fk);
          CF(2);
          mbar_wait(bars + (B_KF + 2) * 8 + c8, 0);
          wg_wait<1>();
        } else {
#pragma unroll
          for (int r = 3; r < 6; r++) mbar_wait(bars + (B_IN + r) * 8, 0);
          wg_wait<0>();
        }
        fence_regs<32>(v); fence_u32<16>(pr);
        pack32(fv, v); fence_u32<16>(fv);
        CF(4);
        if (FWD) T1u(zu, du + U_CH / 16);
        CF(5);
        if (FWD) { wg_wait<1>(); fence_regs<32>(sk); fence_u32<16>(fk); pack32(kh, sk); }
        twiddle<1>(fv, tp, ts);
        fence_u32<16>(fv);
        if (FWD) fence_u32<16>(kh);
        CF(7);
        if (FWD) T1k(zk, dk);
#pragma unroll
        for (int i = 0; i < 4; i++) stsm4(va + 2 * i * vs, fv[4 * i], fv[4 * i + 1], fv[4 * i + 2], fv[4 * i + 3]);
        if (FWD) {
          CF(8);
          wg_wait<1>(); fence_regs<32>(zu);
          pack32(fu, zu); twiddle<0>(fu, tp, ts); fence_u32<16>(fu);
          T2(su, fu);
          CF(10);
        }
        fence_proxy_async_smem();
        bar_sync(7, 128);
        wg_fence();
        ss_n32_tt<0>(y, dv, dF1b); ss_n32_tt<1>(y, dv + 16, dF1b + 64); ss_n32_tt<1>(y, du, dF1b + 128); ss_n32_tt<1>(y, du + 16, dF1b + 192);
        wg_commit();
        CF(12);
        if (FWD) {
          wg_wait<1>(); fence_regs<32>(su); fence_u32<16>(fu); fence_regs<32>(zk);
          if (t == 0) mbar_arrive(bars + B_ST * 8 + c8);
          pack32(uh, su);
          bimac<0>(pr, kh, uh, pr); bimac<2>(pr + 8, kh + 8, uh, pr); fence_u32<16>(pr);
          CF(14);
          wg_wait<0>(); fence_regs<16>(y);
          bimac<1>(pr + 8, kh, uh + 8, pr + 8); fence_u32<8>(pr + 8);
          du += U_CH / 16; dk = dks - dk;
          va += vi;
        }
        if (!FWD) {
          PMFENCE();
          fin_setup(); get_q(0, OFF_K, B_KF + 8, 0);
#pragma unroll
          for (int r = 0; r < 8; r++) q[2 + (r >> 2)][r & 3] = make_uint2(0, 0);
          wg_wait<0>(); fence_regs<16>(y);
        }
#pragma unroll
        for (int i = 0; i < 8; i++) yp[i] = pack_bf16(y[2 * i], y[2 * i + 1]);
        fence_u32<8>(yp);
        yq += yi; yi = U_CH;
      };
#pragma unroll 1
      for (uint32_t c8 = 0; c8 < 56; c8 += 8) step(c8, std::true_type());
      step(56, std::false_type());
      store_y();
    }
    fence_proxy_async_smem();
    bar_sync(7, 128);
    if (elect_one()) bulk_send(sb + OFF_U + (4 * rank + w) * U_N8 + 4 * U_CH, sb + OFF_U + (4 * (rank ^ 1) + w) * U_N8 + 6 * U_CH, U_CH + 512, bars + (B_IN + 6) * 8, rank ^ 1);
    __syncwarp();
    asm volatile("bar.arrive 9, 256;" ::: "memory");
  } else {
    asm volatile("setmaxnreg.inc.sync.aligned.u32 %0;" ::"n"(GREG));
    const int t = tid & 127, w = warp & 3, lane = t & 31, g = lane >> 2, c = lane & 3;
    if (wg == 1) {
      wait_until(c_start, COEF_T0);
      const int p = 64 * j + (t & 63) + 8 * (t & 64);
      const float Lr = bf2f(P.lam_re[p]), Li = bf2f(P.lam_im[p]);
      const uint32_t ds = __bfloat16_as_ushort(P.Dskip[128 * j + t]);
      const unsigned epoch = (ld_relaxed(&g_flagH[tc * 32]) >> 3) + 1;
      const float dt = bf2f(__float2bfloat16_rn(expf(bf2f(P.log_dt[p]))));
      const float e = expf(dt * Lr);
      float sn, cs;
      {
        const double z = (double)(dt * Li) * 0.15915494309189535;
        sincospif(2.f * (float)(z - rint(z)), &sn, &cs);
      }
      const float lr = e * cs, li = e * sn;
      const float nr = lr - 1.0f, ni = li;
      const bool big = fabsf(Lr) >= fabsf(Li);
      const float la = big ? Lr : Li, lb = big ? Li : Lr, r = __fdiv_rn(lb, la), inv = __frcp_rn(fmaf(lb, r, la));
      const float br = (big ? fmaf(ni, r, nr) : fmaf(nr, r, ni)) * inv, bi = (big ? fmaf(-nr, r, ni) : fmaf(ni, r, -nr)) * inv;
      sts128(sb + OFF_COEF + t * 16, make_uint4(__float_as_uint(lr), __float_as_uint(li), pack_bf16(2.f * br, 2.f * br), pack_bf16(-2.f * bi, -2.f * bi)));
      sts32(sb + OFF_DS + 4 * t, ds << 16);
      if (t == 0) sts32(bars + B_EPOCH * 8, epoch);
    }
    CLUSTER_WAIT();
    if (wg == 1) mbar_arrive(bars + B_COEF * 8);
    float d[128];
    uint32_t so = 0, ph = 0, po = 0;
    uint32_t ra;
    auto set_ra = [&]() { asm volatile("mapa.shared::cluster.u32 %0, %1, %2;" : "=r"(ra) : "r"(bars + B_EMPTY * 8), "r"((t & 1) ? rank ^ 1 : rank)); };
    set_ra();
    auto release = [&](uint32_t off) { if (t < 2) asm volatile("mbarrier.arrive.shared::cluster.b64 _, [%0];" ::"r"(ra + off) : "memory"); };
    constexpr uint32_t NOBAR = 8 * (B_NONE - B_EMPTY);
    auto block = [&](auto ta, uint64_t da0, uint64_t db0, bool zero, int nn) {
      constexpr int PH = decltype(ta)::value, TA = PH > 0, KS = TA ? 128 : 2, QD = PH == 0 ? QD1 : PH == 1 ? QD2 : QD3;
      mbar_wait(bars + B_FULL * 8 + so, ph);
      const uint64_t da = da0 + (so << 8), db = db0 + (so << 8);
      wg_fence();
      wgmma_n128<TA>(d, da, db, !zero);
      wgmma_n128<TA>(d + 64, da + 512, db, !zero);
      wg_commit();
      wg_wait<1>();
      release(po);
#pragma unroll
      for (int k = 1; k < 4; k++) {
        if (QD == 2 || (QD == 4 && k == 2)) wg_fence();
        wgmma_n128<TA>(d, da + KS * k, db + 2 * k, 1);
        wgmma_n128<TA>(d + 64, da + 512 + KS * k, db + 2 * k, 1);
        if (QD == 2 || (QD == 4 && k == 1)) wg_commit();
        if ((QD == 2 && k < 3) || (QD == 4 && k == 1)) wg_wait<1>();
      }
      if (QD != 2) wg_commit();
      po = so;
      so += 8;
      if (so == 8 * STAGES) { so = 0; ph ^= 1; }
    };
    {
      so = wg ? 8 * (16 % STAGES) : 0; ph = wg ? (16 / STAGES) & 1 : 0; po = NOBAR;
      const uint64_t da0 = make_desc(sb + OFF_RING, 16, 1024, 1), db0 = make_desc(sb + OFF_RING + 16384, 16, 1024, 1);
      if (wg == 1) bar_sync(1, 256);
#pragma unroll 1
      for (int kb = 0; kb < 16; kb++) {
        block(std::integral_constant<int, 0>(), da0, db0, kb == 0, 16 * wg + kb);
      }
      asm volatile("bar.arrive %0, 256;" ::"r"(1 + wg) : "memory");
    }
    mbar_wait(bars + B_COEF * 8, 0);
    const uint32_t ca = sb + OFF_COEF + (64 * wg + 8 * w + g) * 16;
    const uint32_t tag = __shfl_sync(0xffffffffu, lds32(bars + B_EPOCH * 8) & 3, 0);
    constexpr int RE = SWAPB ? 2 : 0, IM = 2 - RE;
    const int ct = lane >> 3;
    const uint2* cp = g_carry + __shfl_sync(0xffffffffu, ((16 * wg + 2 * j) * 16 + tc - 1 - ct) * 32 + 8 * w + (lane & 7), lane);
    unsigned long long cv[4];
    const int nv = tc - ct;
    auto load_carry = [&](int i) {
#pragma unroll
      for (int m = 0; m < 4; m++)
        asm volatile("{\n.reg .pred p;\nsetp.gt.s32 p, %2, %3;\n@p ld.relaxed.gpu.global.b64 %0, [%1];\n}\n" : "+l"(cv[m]) : "l"(cp + 512 * i - 128 * m), "r"(nv), "r"(4 * m) : "memory");
    };
    float lr[2], li[2], pr[2], pi[2], wr[2], wi[2], vr[2], vi[2], qr[2], qi[2], gr[2], gi[2];
#pragma unroll
    for (int i = 0; i < 2; i++) {
      const uint2 cf = lds64(ca + 512 * i);
      pr[i] = lr[i] = __uint_as_float(cf.x); pi[i] = li[i] = __uint_as_float(cf.y);
#pragma unroll
      for (int s = 0; s < 4; s++) csq(pr[i], pi[i]);
      gr[i] = pr[i]; gi[i] = pi[i];
      csq(pr[i], pi[i]);
      qr[i] = pr[i]; qi[i] = pi[i];
      csq(qr[i], qi[i]);
      asm volatile("" : "+f"(pr[i]), "+f"(pi[i]), "+f"(qr[i]), "+f"(qi[i]));
    }
    PMFENCE();
    wg_wait<0>();
    fence_regs<128>(d);
    release(po);
#pragma unroll
    for (int i = 0; i < 2; i++) {
      float* e = d + 64 * i;
      auto chain = [&](int s0, int s1, float& sr, float& si) {
        sr = e[2 * s0 + RE]; si = e[2 * s0 + IM];
#pragma unroll
        for (int s = s0 + 1; s < s1; s++) {
          const int ia = 4 * (s >> 1) + (s & 1);
          const float nr = fmaf(-li[i], si, fmaf(lr[i], sr, e[ia + RE])), ni = fmaf(li[i], sr, fmaf(lr[i], si, e[ia + IM]));
          sr = nr; si = ni;
        }
      };
      float sr, si;
      if ((GREEDY >> i) & 1) {
        float ar, ai;
        chain(0, 16, ar, ai); chain(16, 32, sr, si);
        sr = fmaf(gr[i], ar, fmaf(-gi[i], ai, sr)); si = fmaf(gr[i], ai, fmaf(gi[i], ar, si));
      } else chain(0, 32, sr, si);
      if (i == 1) { asm volatile("pmevent 0;" : "+f"(sr), "+f"(si)::"memory"); cv[0] = cv[1] = cv[2] = cv[3] = tag; load_carry(0); }
      float ur = __shfl_up_sync(0xffffffffu, sr, 1, 4), ui = __shfl_up_sync(0xffffffffu, si, 1, 4);
      if (c >= 1) { sr = fmaf(pr[i], ur, fmaf(-pi[i], ui, sr)); si = fmaf(pr[i], ui, fmaf(pi[i], ur, si)); }
      ur = __shfl_up_sync(0xffffffffu, sr, 2, 4); ui = __shfl_up_sync(0xffffffffu, si, 2, 4);
      if (c >= 2) { sr = fmaf(qr[i], ur, fmaf(-qi[i], ui, sr)); si = fmaf(qr[i], ui, fmaf(qi[i], ur, si)); }
      ur = __shfl_sync(0xffffffffu, sr, 4 * lane + 3); ui = __shfl_sync(0xffffffffu, si, 4 * lane + 3);
      asm volatile("{\n.reg .pred p;\n.reg .b64 v;\nsetp.lt.u32 p, %3, 8;\nmov.b64 v, {%1,%2};\n@p st.relaxed.gpu.global.b64 [%0], v;\n}\n"
                   ::"l"(cp + 512 * i + 32), "r"((__float_as_uint(ur) & ~3u) | tag), "r"(__float_as_uint(ui)), "r"(lane) : "memory");
      PMFENCE();
      ur = __shfl_up_sync(0xffffffffu, sr, 1, 4); ui = __shfl_up_sync(0xffffffffu, si, 1, 4);
      if (c >= 1) { e[RE] = fmaf(lr[i], ur, fmaf(-li[i], ui, e[RE])); e[IM] = fmaf(lr[i], ui, fmaf(li[i], ur, e[IM])); }
      asm volatile("" : "+f"(e[RE]), "+f"(e[IM]));
    }
#pragma unroll
    for (int i = 0; i < 2; i++) {
      wr[i] = (c & 1) ? pr[i] : 1.f; wi[i] = (c & 1) ? pi[i] : 0.f;
      if (c & 2) { float x, y; cmul(wr[i], wi[i], qr[i], qi[i], x, y); wr[i] = x; wi[i] = y; }
      vr[i] = wr[i]; vi[i] = wi[i];
      csq(vr[i], vi[i]); csq(vr[i], vi[i]);
      csq(qr[i], qi[i]); csq(qr[i], qi[i]); csq(qr[i], qi[i]);
      const int src = 4 * (lane & 7) + ct;
      vr[i] = __shfl_sync(0xffffffffu, vr[i], src); vi[i] = __shfl_sync(0xffffffffu, vi[i], src);
      qr[i] = __shfl_sync(0xffffffffu, qr[i], src); qi[i] = __shfl_sync(0xffffffffu, qi[i], src);
    }
    uint4* hp = g_h + (32 * tc + 16 * wg + 2 * j) * 1024 + 64 * w + 4 * g + (c ^ (g >> 1));
    float sr[2], si[2];
    uint32_t gp[2], gm[2];
    auto carry_in = [&](int i) {
      auto ready = [&]() { return __all_sync(0xffffffffu, ((((uint32_t)cv[0] ^ tag) | ((uint32_t)cv[1] ^ tag) | ((uint32_t)cv[2] ^ tag) | ((uint32_t)cv[3] ^ tag)) & 3) == 0); };
      if (!ready()) {
        int n = 0;
#pragma unroll 1
        do load_carry(i); while (!ready() && ++n <= (SPIN_LIMIT << 4));
      }
      float hr = __uint_as_float((uint32_t)cv[3]), hi = __uint_as_float((uint32_t)(cv[3] >> 32));
#pragma unroll
      for (int m = 2; m >= 0; m--) {
        const float nr = fmaf(qr[i], hr, fmaf(-qi[i], hi, __uint_as_float((uint32_t)cv[m]))), ni = fmaf(qr[i], hi, fmaf(qi[i], hr, __uint_as_float((uint32_t)(cv[m] >> 32))));
        hr = nr; hi = ni;
      }
      { float x, y; cmul(hr, hi, vr[i], vi[i], x, y); hr = x; hi = y; }
      const uint4 cf = lds128(ca + 512 * i);
      lr[i] = __uint_as_float(cf.x); li[i] = __uint_as_float(cf.y); gp[i] = cf.z; gm[i] = cf.w;
      hr += __shfl_xor_sync(0xffffffffu, hr, 8); hi += __shfl_xor_sync(0xffffffffu, hi, 8);
      hr = __shfl_sync(0xffffffffu, hr, g) + __shfl_sync(0xffffffffu, hr, g + 16); hi = __shfl_sync(0xffffffffu, hi, g) + __shfl_sync(0xffffffffu, hi, g + 16);
      cmul(wr[i], wi[i], hr, hi, sr[i], si[i]);
    };
    PMFENCE();
    carry_in(0);
#pragma unroll
    for (int u = 0; u < 8; u++) {
      const int i = u >> 2, i8 = u & 3;
      float* e = d + 64 * i;
      asm volatile("pmevent 0;" : "+f"(sr[i]), "+f"(si[i])::"memory");
      if (u == 1) load_carry(1);
      if (u == 3) carry_in(1);
#pragma unroll
      for (int s = 8 * i8; s < 8 * i8 + 8; s++) {
        const int ia = 4 * (s >> 1) + (s & 1);
        const float nr = fmaf(-li[i], si[i], fmaf(lr[i], sr[i], e[ia + RE])), ni = fmaf(li[i], sr[i], fmaf(lr[i], si[i], e[ia + IM]));
        sr[i] = nr; si[i] = ni;
        e[ia + RE] = nr; e[ia + IM] = ni;
      }
      uint32_t hq[8];
#pragma unroll
      for (int m = 0; m < 4; m++) {
        const float* f = e + 16 * i8 + 4 * m;
        const uint32_t x = pack_bf16(f[RE], f[RE + 1]), y = pack_bf16(f[IM], f[IM + 1]);
        hq[m] = bfma2(gp[i], x, bmul2(gm[i], y)); hq[4 + m] = bfnma2(gp[i], y, bmul2(gm[i], x));
      }
      uint4* o = hp + 512 * (i8 >> 1) + 256 * i + 32 * (i8 & 1);
      stg128(o, make_uint4(hq[0], hq[1], hq[2], hq[3]));
      stg128(o + 1024, make_uint4(hq[4], hq[5], hq[6], hq[7]));
#pragma unroll
      for (int m = 0; m < 8; m++) d[16 * u + m] = __uint_as_float(hq[m]);
      fence_regs<8>(d + 16 * u);
    }
    const int trow = 128 * tc + 64 * (w & 1) + 8 * (w >> 1) + g;
    const int dcol = 128 * j + 4 * c;
    asm volatile("bar.arrive %0, 160;" ::"r"(4 + wg) : "memory");
    if (wg == 0) {
      set_ra();
      {
        const uint32_t dt = sb + OFF_Q + 4096;
        mbar_wait(bars + (B_UF + 3) * 8, 0);
        const int n = t & 15, k = 2 * (n & 6) + 2 * (n >> 3) + (n & 1);
        const uint32_t dv = lds32(sb + OFF_DS + (t & ~15) * 4 + 4 * k) >> (16 - 16 * (k & 1));
#pragma unroll
        for (int u = 0; u < 2; u++) {
          const int m = (k >> 1) - 4 * u;
          sts128(dt + (t >> 4) * 512 + u * 256 + n * 16, make_uint4(m == 0 ? dv : 0, m == 1 ? dv : 0, m == 2 ? dv : 0, m == 3 ? dv : 0));
        }
        fence_proxy_async_smem();
        bar_sync(2, 256);
        mbar_wait(bars + (B_FULL + XPOS % STAGES) * 8, (XPOS / STAGES) & 1);
        const uint64_t dx = make_desc(sb + OFF_RING + (XPOS % STAGES) * STAGE_BYTES, 16, 1024, 1), dd = make_desc(dt, 256, 128, 0);
        wg_fence();
#pragma unroll
        for (int u = 0; u < 16; u++) {
          const uint64_t da = dx + ((u >> 2) & 1) * 1024 + (u >> 3) * 512 + (u & 3) * 2, db = dd + (u & 7) * 32;
          if (u & 1) ss_n16(d + 8 * u, da, db); else ss_n16_in(d + 8 * u, da, db, P.zero);
        }
        wg_commit();
        wg_wait<0>();
        rename_regs<128>(d);
        release(8 * (XPOS % STAGES));
        if (t == 0) mbar_arrive(bars + B_XI * 8);
      }
      so = 8 * (33 % STAGES); ph = (33 / STAGES) & 1; po = NOBAR;
      const uint64_t da0 = make_desc(sb + OFF_RING + 16384, 512, 1024, 2), db0 = make_desc(sb + OFF_RING, 16, 1024, 1);
#pragma unroll 1
      for (int kb = 0; kb < QSW; kb++) block(std::integral_constant<int, 1>(), da0, db0, false, 32 + kb);
#pragma unroll 1
      for (int kb = QSW; kb < 32 - TAILB; kb++) block(std::integral_constant<int, 2>(), da0, db0, false, 32 + kb);
      float* op = P.out + (size_t)trow * 2048 + 1024 + dcol;
      auto mma = [&](int i, int kb, int k0, int k1) {
        const int s = (33 + kb) % STAGES;
        wg_fence();
#pragma unroll
        for (int k = k0; k < k1; k++) wgmma_n128<1>(d + 64 * i, da0 + s * 2048 + 512 * i + 128 * k, db0 + (i ? 0 : P.zero) + s * 2048 + 2 * k, 1);
        wg_commit();
      };
      auto store = [&](int i, int J0, int J1) {
#pragma unroll
        for (int J = J0; J < J1; J++) {
#pragma unroll
          for (int h = 0; h < 2; h++) {
            const float* e = d + 64 * i + 8 * J + 2 * h;
            stg128(op + (size_t)(16 * i + 32 * h) * 2048 + 16 * J, make_uint4(__float_as_uint(e[0]), __float_as_uint(e[1]), __float_as_uint(e[4]), __float_as_uint(e[5])));
          }
        }
        PMFENCE();
      };
      constexpr int K0 = 32 - TAILB;
#pragma unroll
      for (int kb = K0; kb < 32; kb++) {
        mbar_wait(bars + (B_FULL + (33 + kb) % STAGES) * 8, ((33 + kb) / STAGES) & 1);
        if (TAILB == 5 && kb == K0) { mma(0, kb, 0, 2); wg_wait<1>(); release(po); mma(0, kb, 2, 4); }
        else mma(0, kb, 0, 4);
      }
      mma(1, K0, 0, 4);
      wg_wait<1>();
      fence_regs<64>(d);
#pragma unroll
      for (int kb = K0 + 1; kb < 32; kb++) {
        mma(1, kb, 0, 4);
        store(0, T_ST * (kb - K0 - 1), kb == 31 ? 8 : T_ST * (kb - K0));
      }
      wg_wait<0>();
      fence_regs<64>(d + 64);
      store(1, 0, 8);
      return;
    }
    asm volatile("setmaxnreg.dec.sync.aligned.u32 %0;" ::"n"(488 - 2 * GREG));
    fin_setup();
#pragma unroll
    for (int n = 0; n < 4; n += 2) {
      get_q(n, OFF_Q, B_QF, n >> 1);
      uint32_t dep = P.zero;
#pragma unroll
      for (int r = 0; r < 8; r++) dep &= q[n + (r >> 2)][r & 3].x;
      bar_sync(6 + dep, 128);
      if (w < 2 && elect_one()) load_q(5 + 2 * w - (n >> 1), OFF_Q, B_QF + n);
      __syncwarp();
    }
#pragma unroll 1
    for (int r = 0; r < 6; r++) mbar_wait(bars + (B_IN + r) * 8, 0);
    bar_sync(9, 256);
  }
  {
    const int w = warp & 3, h = wg & 1, lane = fl;
    const uint32_t ob0 = sb + (h ? OFF_F1 : OFF_K) + 1024 * w, ob1 = sb + (h ? OFF_VP : OFF_K + 4096) + 1024 * w;
    uint32_t y[2][8];
    auto get_y = [&](int n) { ldsm4t(y[n & 1], fa + n * fs); ldsm4t(y[n & 1] + 4, fa + n * fs + 32); };
    mbar_wait(bars + B_HR * 8, 1);
    mbar_wait(bars + (B_IN + 6) * 8, 0);
    get_y(0);
#pragma unroll
    for (int n = 0; n < 4; n++) {
      uint32_t* o = y[n & 1];
#pragma unroll
      for (int r = 0; r < 4; r++) { o[2 * r] = bmul2(o[2 * r], q[n][r].x); o[2 * r + 1] = bmul2(o[2 * r + 1], q[n][r].y); }
      if (n > 0 && lane == 0) asm volatile("cp.async.bulk.wait_group.read 0;" ::: "memory");
      __syncwarp();
#pragma unroll
      for (int r = 0; r < 4; r++)
        sts128((r & 2 ? ob1 : ob0) + (r & 1) * 512 + lane * 16, make_uint4(o[2 * r] << 16, o[2 * r] & 0xffff0000u, o[2 * r + 1] << 16, o[2 * r + 1] & 0xffff0000u));
      fence_proxy_async_smem();
      __syncwarp();
      if (lane == 0) {
#pragma unroll
        for (int u = 0; u < 2; u++)
          asm volatile("cp.async.bulk.tensor.3d.global.shared::cta.bulk_group [%0, {%2, %3, %4}], [%1];"
                       ::"l"(&mO), "r"(u ? ob1 : ob0), "r"(32 * slot), "r"(32 * rank + 8 * w), "r"(8 * n + 4 * h + 2 * u) : "memory");
        asm volatile("cp.async.bulk.commit_group;" ::: "memory");
      }
      __syncwarp();
      if (n < 3) get_y(n + 1);
      if (n == 1 && !h) get_q(2, OFF_Q, B_QF + 2, 0);
    }
    if (warp == 8 && lane == 0) mbar_arrive_cta(bars + B_ACK * 8, rank ^ 1);
    if (lane == 0) asm volatile("cp.async.bulk.wait_group 0;" ::: "memory");
    mbar_wait(bars + B_ACK * 8, 0);
  }
}

typedef CUresult (*EncodeFn)(CUtensorMap*, CUtensorMapDataType, cuuint32_t, void*, const cuuint64_t*, const cuuint64_t*, const cuuint32_t*,
                             const cuuint32_t*, CUtensorMapInterleave, CUtensorMapSwizzle, CUtensorMapL2promotion, CUtensorMapFloatOOBfill);

bool encode(EncodeFn fn, CUtensorMap* m, int rank, const void* base, const cuuint64_t* dims, const cuuint64_t* strides, const cuuint32_t* box, CUtensorMapSwizzle swz,
            CUtensorMapL2promotion promo = CU_TENSOR_MAP_L2_PROMOTION_L2_128B) {
  const cuuint32_t es[5] = {1, 1, 1, 1, 1};
  return fn(m, CU_TENSOR_MAP_DATA_TYPE_BFLOAT16, rank, const_cast<void*>(base), dims, strides, box, es, CU_TENSOR_MAP_INTERLEAVE_NONE, swz,
            promo, CU_TENSOR_MAP_FLOAT_OOB_FILL_NONE) == CUDA_SUCCESS;
}

}

extern "C" void kernel_launch(void* const* d_in, const int* in_sizes, int n_in, void* d_out, int out_size) {
  (void)in_sizes; (void)n_in; (void)out_size;
  typedef const __nv_bfloat16* In;
  const In q = (In)d_in[0], k = (In)d_in[1], v = (In)d_in[2], ssm_k = (In)d_in[4], x = (In)d_in[6], B_re = (In)d_in[9], B_im = (In)d_in[10], C_re = (In)d_in[11], C_im = (In)d_in[12];
  Params P = {};
  P.shift_k = (In)d_in[3]; P.ssm_D = (In)d_in[5]; P.lam_re = (In)d_in[7]; P.lam_im = (In)d_in[8]; P.log_dt = (In)d_in[13]; P.Dskip = (In)d_in[14];
  P.out = (float*)d_out;
  for (int cl = 0; cl < 64; cl++) P.slot[cl >> 2] |= (cl < 4 ? 4 + cl : cl < 36 ? 8 * ((cl - 4) & 7) + ((cl - 4) >> 3) : 8 * (1 + (cl - 36) % 7) + 4 + (cl - 36) / 7) << (8 * (cl & 3));
  const bool swapB = (uintptr_t)B_im < (uintptr_t)B_re;

  EncodeFn fn = nullptr;
  cudaDriverEntryPointQueryResult qr;
  cudaGetDriverEntryPoint("cuTensorMapEncodeTiled", (void**)&fn, cudaEnableDefault, &qr);
  if (!fn) return;

  CUtensorMap mX, mB, mCre, mCim, mXs, mK, mV, mQ, mS, mO;
  bool ok = true;
  {
    const cuuint64_t dims[4] = {1024, 2, 64, 16}, str[3] = {2048, 32 * 2048, 2 * 2048};
    const cuuint32_t box[4] = {64, 2, 4, 16};
    ok &= encode(fn, &mX, 4, x, dims, str, box, CU_TENSOR_MAP_SWIZZLE_128B);
  }
  {
    const uintptr_t lo = swapB ? (uintptr_t)B_im : (uintptr_t)B_re, hi = swapB ? (uintptr_t)B_re : (uintptr_t)B_im;
    const cuuint64_t dims[4] = {1024, 8, 2, 128}, str[3] = {2048, (cuuint64_t)(hi - lo), 8 * 2048};
    const cuuint32_t box[4] = {64, 8, 2, 4};
    ok &= encode(fn, &mB, 4, (const void*)lo, dims, str, box, CU_TENSOR_MAP_SWIZZLE_128B);
  }
  {
    const cuuint64_t dims[5] = {1024, 2, 4, 2, 64}, str[4] = {2048, 4 * 2048, 2 * 2048, 16 * 2048};
    const cuuint32_t box[5] = {64, 2, 4, 2, 4};
    ok &= encode(fn, &mCre, 5, C_re, dims, str, box, CU_TENSOR_MAP_SWIZZLE_128B);
    ok &= encode(fn, &mCim, 5, C_im, dims, str, box, CU_TENSOR_MAP_SWIZZLE_128B);
  }
  {
    const cuuint64_t dims[4] = {1024, 8, 64, 4}, str[3] = {2048, 32 * 2048, 8 * 2048};
    const cuuint32_t box[4] = {64, 8, 4, 4};
    ok &= encode(fn, &mXs, 4, x, dims, str, box, CU_TENSOR_MAP_SWIZZLE_128B);
  }
  {
    const cuuint64_t dims[3] = {1024, 64, 32}, str[2] = {32 * 2048, 2048};
    const cuuint32_t box[3] = {16, 32, 4};
    const cuuint64_t dimq[4] = {1024, 8, 32, 8}, strq[3] = {32 * 2048, 2048, 256 * 2048};
    const cuuint32_t boxq[4] = {16, 8, 4, 4};
    ok &= encode(fn, &mQ, 4, q, dimq, strq, boxq, CU_TENSOR_MAP_SWIZZLE_NONE);
    ok &= encode(fn, &mK, 3, k, dims, str, box, CU_TENSOR_MAP_SWIZZLE_32B);
    ok &= encode(fn, &mV, 3, v, dims, str, box, CU_TENSOR_MAP_SWIZZLE_32B);
  }
  {
    const cuuint64_t dims[2] = {32, 65536}, str[1] = {64};
    const cuuint32_t box[2] = {32, 64};
    ok &= encode(fn, &mS, 2, ssm_k, dims, str, box, CU_TENSOR_MAP_SWIZZLE_64B);
  }
  {
    const cuuint64_t dims[3] = {2048, 64, 32}, str[2] = {32 * 8192, 8192};
    const cuuint32_t box[3] = {32, 8, 2};
    ok &= encode(fn, &mO, 3, d_out, dims, str, box, CU_TENSOR_MAP_SWIZZLE_NONE);
  }
  if (!ok) return;
  auto kern = swapB ? fused_kernel<1> : fused_kernel<0>;
  cudaFuncSetAttribute(kern, cudaFuncAttributeMaxDynamicSharedMemorySize, SMEM_BYTES);
  kern<<<NCTA, 512, SMEM_BYTES, cudaStreamPerThread>>>(P, mX, mB, mCre, mCim, mXs, mK, mV, mQ, mS, mO);
}
```

```cpp
#include <cuda_runtime.h>
#include <cuda_bf16.h>
#include <cuda.h>
#include <stdint.h>
#include <type_traits>

namespace {

constexpr int D_DIM = 1024;
constexpr int NCTA = 128;

constexpr int STAGES = 5, STAGE_BYTES = 32768;
constexpr int OFF_RING = 0;
constexpr int OFF_F1 = STAGES * STAGE_BYTES, OFF_F2 = OFF_F1 + 4096, OFF_K = OFF_F2 + 2048, OFF_VP = OFF_K + 8192, OFF_Q = OFF_VP + 4096, OFF_IN = OFF_Q + 8192;
constexpr int OFF_KV = OFF_K;
constexpr int U_CH = 528, U_N8 = 8 * U_CH, OFF_U = OFF_IN + U_N8;
constexpr int OFF_COEF = OFF_U + 8 * U_N8;
constexpr int OFF_DS = OFF_COEF + 2048, OFF_D = OFF_DS + 512;
constexpr int OFF_BAR = OFF_D + 64;
constexpr int SMEM_BYTES = OFF_BAR + 512;
static_assert(SMEM_BYTES <= 232448 && OFF_K % 1024 == 0 && (OFF_U + 3 * U_N8) % 512 == 0 && (4 * U_N8) % 512 == 0, "smem map");
constexpr int B_FULL = 0, B_XI = 5, B_HR = 6, B_HP = 7, B_KVF = 8, B_QF = 11, B_IN = 15, B_UF = 23, B_ACK = 27, B_KF = 28, B_ST = 38,
              B_EMPTY = 45, B_COEF = 50, B_KVE = 51, B_NONE = 54, B_EPOCH = 55;

constexpr int QD1 = 8;
constexpr int QD2 = 2;
constexpr int QD3 = 8;
constexpr int QSW = 16;
constexpr int HEAD = 3;
constexpr int ST_T0 = 200;
constexpr int ST_DELAY = 300;
constexpr int XPOS = 32;
constexpr int K_T0 = 800;
constexpr int KV_T0 = 1500;
constexpr int KV_DT = 620;
constexpr int KV_DV = 450;
constexpr int POLL_NS = 30;
constexpr int GREEDY = 1;
constexpr int TAILB = 5;
constexpr int GREG = 168;
constexpr int COEF_T0 = 2500;
constexpr int T_ST = 2;
constexpr int PFC_T0 = 12500;
constexpr int PFC_T1 = 1500;
constexpr int PFC_DT = 250;
constexpr int KV_E = 6;
constexpr int KV_D2 = 300;
constexpr int CFM = 0x40f1;
constexpr int SPIN_LIMIT = 1 << 14;

struct Params {
  unsigned slot[16];
  unsigned zero;
  const __nv_bfloat16 *shift_k, *ssm_D, *lam_re, *lam_im, *log_dt, *Dskip;
  float* out;
};

__device__ __align__(1024) uint4 g_h[16 * 32 * 1024];
__device__ __align__(128) uint2 g_carry[32 * 16 * 32];
__device__ __align__(128) unsigned g_flagH[16 * 32];

__device__ __forceinline__ uint64_t make_desc(uint32_t addr, uint32_t lbo, uint32_t sbo, uint32_t swz) {
  return (uint64_t)((addr & 0x3FFFF) >> 4) | ((uint64_t)(lbo >> 4) << 16) | ((uint64_t)(sbo >> 4) << 32) | ((uint64_t)swz << 62);
}
__device__ __forceinline__ void wg_fence() { asm volatile("wgmma.fence.sync.aligned;" ::: "memory"); }
__device__ __forceinline__ void wg_commit() { asm volatile("wgmma.commit_group.sync.aligned;" ::: "memory"); }
template <int N> __device__ __forceinline__ void wg_wait() { asm volatile("wgmma.wait_group.sync.aligned %0;" ::"n"(N) : "memory"); }
__device__ __forceinline__ void mbar_init(uint32_t bar, int cnt) { asm volatile("mbarrier.init.shared::cta.b64 [%0], %1;" ::"r"(bar), "r"(cnt) : "memory"); }
__device__ __forceinline__ void mbar_expect(uint32_t bar, uint32_t bytes) { asm volatile("mbarrier.arrive.expect_tx.shared::cta.b64 _, [%0], %1;" ::"r"(bar), "r"(bytes) : "memory"); }
__device__ __forceinline__ bool mbar_try(uint32_t bar, uint32_t parity) {
  uint32_t ok;
  asm volatile("{\n.reg .pred p;\nmbarrier.try_wait.parity.shared::cta.b64 p, [%1], %2;\nselp.u32 %0, 1, 0, p;\n}\n" : "=r"(ok) : "r"(bar), "r"(parity) : "memory");
  return ok;
}
__device__ __forceinline__ void mbar_wait(uint32_t bar, uint32_t parity) {
  if (__builtin_expect(!mbar_try(bar, parity), 0)) {
#pragma unroll 1
    for (int n = 0; n < SPIN_LIMIT && !mbar_try(bar, parity); n++) {}
  }
}
__device__ __forceinline__ void mbar_arrive(uint32_t bar) { asm volatile("mbarrier.arrive.shared::cta.b64 _, [%0];" ::"r"(bar) : "memory"); }
__device__ __forceinline__ void mbar_arrive_cta(uint32_t bar, uint32_t cta) {
  asm volatile("{\n.reg .b32 ra;\nmapa.shared::cluster.u32 ra, %0, %1;\nmbarrier.arrive.shared::cluster.b64 _, [ra];\n}\n" ::"r"(bar), "r"(cta) : "memory");
}
__device__ __forceinline__ bool elect_one() {
  uint32_t p;
  asm volatile("{\n.reg .pred P;\nelect.sync _|P, 0xffffffff;\nselp.u32 %0, 1, 0, P;\n}\n" : "=r"(p));
  return p != 0;
}
__device__ __forceinline__ void bar_sync(int id, int n) { asm volatile("bar.sync %0, %1;" ::"r"(id), "r"(n) : "memory"); }
#define TMA_LD(dim) "cp.async.bulk.tensor." dim ".shared::cluster.global.mbarrier::complete_tx::bytes"
__device__ __forceinline__ void tma2d(uint32_t dst, const CUtensorMap* m, int c0, int c1, uint32_t bar) {
  asm volatile(TMA_LD("2d") " [%0], [%1, {%3, %4}], [%2];" ::"r"(dst), "l"(m), "r"(bar), "r"(c0), "r"(c1) : "memory");
}
__device__ __forceinline__ void tma3d(uint32_t dst, const CUtensorMap* m, int c0, int c1, int c2, uint32_t bar) {
  asm volatile(TMA_LD("3d") " [%0], [%1, {%3, %4, %5}], [%2];" ::"r"(dst), "l"(m), "r"(bar), "r"(c0), "r"(c1), "r"(c2) : "memory");
}
__device__ __forceinline__ void tma4d(uint32_t dst, const CUtensorMap* m, int c0, int c1, int c2, int c3, uint32_t bar) {
  asm volatile(TMA_LD("4d") " [%0], [%1, {%3, %4, %5, %6}], [%2];" ::"r"(dst), "l"(m), "r"(bar), "r"(c0), "r"(c1), "r"(c2), "r"(c3) : "memory");
}
__device__ __forceinline__ void tma4d_mc(uint32_t dst, const CUtensorMap* m, int c0, int c1, int c2, int c3, uint32_t bar) {
  asm volatile(TMA_LD("4d") ".multicast::cluster [%0], [%1, {%3, %4, %5, %6}], [%2], %7;" ::"r"(dst), "l"(m), "r"(bar), "r"(c0), "r"(c1), "r"(c2), "r"(c3), "h"((uint16_t)3) : "memory");
}
__device__ __forceinline__ void tma5d_mc(uint32_t dst, const CUtensorMap* m, int c0, int c1, int c2, int c3, int c4, uint32_t bar) {
  asm volatile(TMA_LD("5d") ".multicast::cluster [%0], [%1, {%3, %4, %5, %6, %7}], [%2], %8;" ::"r"(dst), "l"(m), "r"(bar), "r"(c0), "r"(c1), "r"(c2), "r"(c3), "r"(c4), "h"((uint16_t)3) : "memory");
}
__device__ __forceinline__ void bulk_load(uint32_t dst, const void* src, uint32_t bytes, uint32_t bar) {
  asm volatile("cp.async.bulk.shared::cluster.global.mbarrier::complete_tx::bytes [%0], [%1], %2, [%3];" ::"r"(dst), "l"(src), "r"(bytes), "r"(bar) : "memory");
}
__device__ __forceinline__ void bulk_send(uint32_t dst, uint32_t src, uint32_t bytes, uint32_t bar, uint32_t cta) {
  asm volatile("{\n.reg .b32 rd, rb;\nmapa.shared::cluster.u32 rd, %0, %3;\nmapa.shared::cluster.u32 rb, %2, %3;\n"
               "cp.async.bulk.shared::cluster.shared::cta.mbarrier::complete_tx::bytes [rd], [%1], %4, [rb];\n}\n"
               ::"r"(dst), "r"(src), "r"(bar), "r"(cta), "r"(bytes) : "memory");
}
__device__ __forceinline__ void fence_proxy_async_smem() { asm volatile("fence.proxy.async.shared::cta;" ::: "memory"); }
__device__ __forceinline__ void fence_proxy_async_global() { asm volatile("fence.proxy.async.global;" ::: "memory"); }
__device__ __forceinline__ uint32_t clk32() { uint32_t c; asm volatile("mov.u32 %0, %%clock;" : "=r"(c)::"memory"); return c; }
__device__ __forceinline__ void wait_until(uint32_t t0, uint32_t dt) { while (clk32() - t0 < dt) __nanosleep(32); }
__device__ __forceinline__ void spin_until(uint32_t t0, uint32_t dt) { while (clk32() - t0 < dt) {} }
__device__ __forceinline__ void prefetch_map(const CUtensorMap* m) { asm volatile("prefetch.tensormap [%0];" ::"l"(m) : "memory"); }
__device__ __forceinline__ void prefetch_line(const void* p) { asm volatile("prefetch.global.L2 [%0];" ::"l"(p) : "memory"); }
__device__ __forceinline__ unsigned ld_acquire(const unsigned* p) { unsigned v; asm volatile("ld.acquire.gpu.global.u32 %0, [%1];" : "=r"(v) : "l"(p) : "memory"); return v; }
__device__ __forceinline__ unsigned ld_relaxed(const unsigned* p) { unsigned v; asm volatile("ld.relaxed.gpu.global.u32 %0, [%1];" : "=r"(v) : "l"(p) : "memory"); return v; }
__device__ __forceinline__ uint32_t lds32(uint32_t a) { uint32_t v; asm volatile("ld.shared.u32 %0, [%1];" : "=r"(v) : "r"(a)); return v; }
__device__ __forceinline__ uint2 lds64(uint32_t a) { uint2 v; asm volatile("ld.shared.v2.u32 {%0,%1}, [%2];" : "=r"(v.x), "=r"(v.y) : "r"(a) : "memory"); return v; }
__device__ __forceinline__ uint4 lds128(uint32_t a) { uint4 v; asm volatile("ld.shared.v4.u32 {%0,%1,%2,%3}, [%4];" : "=r"(v.x), "=r"(v.y), "=r"(v.z), "=r"(v.w) : "r"(a) : "memory"); return v; }
__device__ __forceinline__ void sts32(uint32_t a, uint32_t v) { asm volatile("st.shared.u32 [%0], %1;" ::"r"(a), "r"(v) : "memory"); }
__device__ __forceinline__ void sts128(uint32_t a, uint4 v) { asm volatile("st.shared.v4.u32 [%0], {%1,%2,%3,%4};" ::"r"(a), "r"(v.x), "r"(v.y), "r"(v.z), "r"(v.w) : "memory"); }
__device__ __forceinline__ void ldsm4(uint32_t* r, uint32_t a) { asm volatile("ldmatrix.sync.aligned.m8n8.x4.shared.b16 {%0,%1,%2,%3}, [%4];" : "=r"(r[0]), "=r"(r[1]), "=r"(r[2]), "=r"(r[3]) : "r"(a) : "memory"); }
__device__ __forceinline__ void ldsm4t(uint32_t* r, uint32_t a) { asm volatile("ldmatrix.sync.aligned.m8n8.x4.trans.shared.b16 {%0,%1,%2,%3}, [%4];" : "=r"(r[0]), "=r"(r[1]), "=r"(r[2]), "=r"(r[3]) : "r"(a) : "memory"); }
__device__ __forceinline__ void stsm4t(uint32_t a, uint32_t r0, uint32_t r1, uint32_t r2, uint32_t r3) {
  asm volatile("stmatrix.sync.aligned.m8n8.x4.trans.shared.b16 [%0], {%1,%2,%3,%4};" ::"r"(a), "r"(r0), "r"(r1), "r"(r2), "r"(r3) : "memory");
}
__device__ __forceinline__ uint4 ldg128_nc(const void* p) { uint4 v; asm volatile("ld.global.nc.L1::no_allocate.v4.u32 {%0,%1,%2,%3}, [%4];" : "=r"(v.x), "=r"(v.y), "=r"(v.z), "=r"(v.w) : "l"(p)); return v; }
__device__ __forceinline__ void stg128(void* p, uint4 v) { asm volatile("st.global.L1::no_allocate.v4.u32 [%0], {%1,%2,%3,%4};" ::"l"(p), "r"(v.x), "r"(v.y), "r"(v.z), "r"(v.w) : "memory"); }
__device__ __forceinline__ uint32_t pack_bf16(float lo, float hi) { uint32_t r; asm("cvt.rn.bf16x2.f32 %0, %1, %2;" : "=r"(r) : "f"(hi), "f"(lo)); return r; }
__device__ __forceinline__ uint32_t bmul2(uint32_t a, uint32_t b) { uint32_t r; asm("mul.rn.bf16x2 %0, %1, %2;" : "=r"(r) : "r"(a), "r"(b)); return r; }
__device__ __forceinline__ uint32_t bfma2(uint32_t a, uint32_t b, uint32_t c) { uint32_t r; asm("fma.rn.bf16x2 %0, %1, %2, %3;" : "=r"(r) : "r"(a), "r"(b), "r"(c)); return r; }
__device__ __forceinline__ uint32_t blo2(uint32_t a) { uint32_t r; asm("{\n.reg .b16 l, h;\nmov.b32 {l, h}, %1;\nmov.b32 %0, {l, l};\n}" : "=r"(r) : "r"(a)); return r; }
__device__ __forceinline__ float bf2f(__nv_bfloat16 v) { return __bfloat162float(v); }

#define R8(d, o) "+f"(d[o]), "+f"(d[o + 1]), "+f"(d[o + 2]), "+f"(d[o + 3]), "+f"(d[o + 4]), "+f"(d[o + 5]), "+f"(d[o + 6]), "+f"(d[o + 7])
#define R16(d, o) R8(d, o), R8(d, o + 8)
#define R64(d, o) R16(d, o), R16(d, o + 16), R16(d, o + 32), R16(d, o + 48)
template <int TA> __device__ __forceinline__ void wgmma_n128(float* d, uint64_t da, uint64_t db, int scale_d) {
  asm volatile("{\n.reg .pred p;\nsetp.ne.b32 p, %66, 0;\n"
    "wgmma.mma_async.sync.aligned.m64n128k16.f32.bf16.bf16 {"
    "%0,%1,%2,%3,%4,%5,%6,%7,%8,%9,%10,%11,%12,%13,%14,%15,%16,%17,%18,%19,%20,%21,%22,%23,%24,%25,%26,%27,%28,%29,%30,%31,"
    "%32,%33,%34,%35,%36,%37,%38,%39,%40,%41,%42,%43,%44,%45,%46,%47,%48,%49,%50,%51,%52,%53,%54,%55,%56,%57,%58,%59,%60,%61,%62,%63"
    "}, %64, %65, p, 1, 1, %67, 0;\n}\n"
    : R64(d, 0)
    : "l"(da), "l"(db), "r"(scale_d), "n"(TA));
}
template <int N> __device__ __forceinline__ void fence_regs(float* d) {
#pragma unroll
  for (int i = 0; i < N; i++) asm volatile("" : "+f"(d[i])::"memory");
}
#define PMFENCE() asm volatile("pmevent 0;" ::: "memory")
__device__ __forceinline__ void cmul(float ar, float ai, float br, float bi, float& cr, float& ci) {
  cr = ar * br - ai * bi; ci = ar * bi + ai * br;
}
__device__ __forceinline__ void csq(float& r, float& i) { const float x = fmaf(r, r, -i * i), y = r * i; r = x; i = y + y; }

#define W8(d, o) "=f"(d[o]), "=f"(d[o + 1]), "=f"(d[o + 2]), "=f"(d[o + 3]), "=f"(d[o + 4]), "=f"(d[o + 5]), "=f"(d[o + 6]), "=f"(d[o + 7])
#define L16 "{%0,%1,%2,%3,%4,%5,%6,%7,%8,%9,%10,%11,%12,%13,%14,%15}"
#define L32 "{%0,%1,%2,%3,%4,%5,%6,%7,%8,%9,%10,%11,%12,%13,%14,%15,%16,%17,%18,%19,%20,%21,%22,%23,%24,%25,%26,%27,%28,%29,%30,%31}"
template <int ACC, int TB> __device__ __forceinline__ void rs_n32(float* d, const uint32_t* a, uint64_t db) {
  if constexpr (ACC) asm volatile("wgmma.mma_async.sync.aligned.m64n32k16.f32.bf16.bf16 " L16 ", {%16,%17,%18,%19}, %20, 1, 1, 1, %21;" : R16(d, 0) : "r"(a[0]), "r"(a[1]), "r"(a[2]), "r"(a[3]), "l"(db), "n"(TB));
  else asm volatile("wgmma.mma_async.sync.aligned.m64n32k16.f32.bf16.bf16 " L16 ", {%16,%17,%18,%19}, %20, 0, 1, 1, %21;" : W8(d, 0), W8(d, 8) : "r"(a[0]), "r"(a[1]), "r"(a[2]), "r"(a[3]), "l"(db), "n"(TB));
}
template <int ACC, int TB> __device__ __forceinline__ void rs_n64(float* d, const uint32_t* a, uint64_t db) {
  if constexpr (ACC) asm volatile("wgmma.mma_async.sync.aligned.m64n64k16.f32.bf16.bf16 " L32 ", {%32,%33,%34,%35}, %36, 1, 1, 1, %37;" : R16(d, 0), R16(d, 16) : "r"(a[0]), "r"(a[1]), "r"(a[2]), "r"(a[3]), "l"(db), "n"(TB));
  else asm volatile("wgmma.mma_async.sync.aligned.m64n64k16.f32.bf16.bf16 " L32 ", {%32,%33,%34,%35}, %36, 0, 1, 1, %37;" : W8(d, 0), W8(d, 8), W8(d, 16), W8(d, 24) : "r"(a[0]), "r"(a[1]), "r"(a[2]), "r"(a[3]), "l"(db), "n"(TB));
}
template <int ACC> __device__ __forceinline__ void ss_n32_tt(float* d, uint64_t da, uint64_t db) {
  if constexpr (ACC) asm volatile("wgmma.mma_async.sync.aligned.m64n32k16.f32.bf16.bf16 " L16 ", %16, %17, 1, 1, 1, 1, 1;" : R16(d, 0) : "l"(da), "l"(db));
  else asm volatile("wgmma.mma_async.sync.aligned.m64n32k16.f32.bf16.bf16 " L16 ", %16, %17, 0, 1, 1, 1, 1;" : W8(d, 0), W8(d, 8) : "l"(da), "l"(db));
}
__device__ __forceinline__ void stsm4(uint32_t a, uint32_t r0, uint32_t r1, uint32_t r2, uint32_t r3) {
  asm volatile("stmatrix.sync.aligned.m8n8.x4.shared.b16 [%0], {%1,%2,%3,%4};" ::"r"(a), "r"(r0), "r"(r1), "r"(r2), "r"(r3) : "memory");
}
template <int N> __device__ __forceinline__ void fence_u32(uint32_t* d) {
#pragma unroll
  for (int i = 0; i < N; i++) asm volatile("" : "+r"(d[i])::"memory");
}
__device__ __forceinline__ void pack32(uint32_t* f, const float* z) {
#pragma unroll
  for (int i = 0; i < 16; i++) f[i] = pack_bf16(z[2 * i], z[2 * i + 1]);
}
template <int INV> __device__ __forceinline__ void twiddle(uint32_t* f, const uint32_t* tp, const uint32_t* ts) {
#pragma unroll
  for (int i = 0; i < 8; i++) {
    uint32_t x = f[2 * i + INV], y = f[2 * i + 1 - INV];
    x = bfma2(tp[i & 3], y, x); y = bfma2(ts[i & 3], x, y); x = bfma2(tp[i & 3], y, x);
    f[2 * i + INV] = x; f[2 * i + 1 - INV] = y;
  }
}
__device__ __forceinline__ uint32_t bfnma2(uint32_t a, uint32_t b, uint32_t c) { uint32_t r; asm("{\n.reg .b32 t;\nmul.bf16x2 t, %1, %2;\nsub.bf16x2 %0, %3, t;\n}" : "=r"(r) : "r"(a), "r"(b), "r"(c)); return r; }
__device__ __forceinline__ uint32_t bfms2(uint32_t a, uint32_t b, uint32_t c) { uint32_t r; asm("{\n.reg .b32 t;\nmul.bf16x2 t, %1, %2;\nsub.bf16x2 %0, t, %3;\n}" : "=r"(r) : "r"(a), "r"(b), "r"(c)); return r; }
template <int ADD> __device__ __forceinline__ void bimac(uint32_t* o, const uint32_t* a, const uint32_t* b, const uint32_t* c) {
#pragma unroll
  for (int J = 0; J < 2; J++) {
    const uint32_t Pr = a[2 * J], Pi = a[2 * J + 1], Qr = a[2 * J + 4], Qi = a[2 * J + 5], pr = b[2 * J], pi = b[2 * J + 1], qr = b[2 * J + 4], qi = b[2 * J + 5];
    uint32_t x0, x1, x2, x3;
    if (ADD == 0) { x0 = bmul2(Pr, pr); x1 = bmul2(Pr, pi); x2 = bmul2(Pr, qr); x3 = bmul2(Pr, qi); }
    if (ADD == 1) { x0 = bfma2(Pr, pr, c[2 * J]); x1 = bfma2(Pr, pi, c[2 * J + 1]); x2 = bfma2(Pr, qr, c[2 * J + 4]); x3 = bfma2(Pr, qi, c[2 * J + 5]); }
    if (ADD == 2) { x0 = bfma2(Pr, pr, c[2 * J + 1]); x1 = bfms2(Pr, pi, c[2 * J]); x2 = bfma2(Pr, qr, c[2 * J + 5]); x3 = bfms2(Pr, qi, c[2 * J + 4]); }
    x0 = bfnma2(Pi, pi, x0); x1 = bfma2(Pi, pr, x1); x2 = bfnma2(Pi, qi, x2); x3 = bfma2(Pi, qr, x3);
    x0 = bfnma2(Qr, qr, x0); x1 = bfnma2(Qr, qi, x1); x2 = bfma2(Qr, pr, x2); x3 = bfma2(Qr, pi, x3);
    x0 = bfma2(Qi, qi, x0); x1 = bfnma2(Qi, qr, x1); x2 = bfnma2(Qi, pi, x2); x3 = bfma2(Qi, pr, x3);
    o[2 * J] = x0; o[2 * J + 1] = x1; o[2 * J + 4] = x2; o[2 * J + 5] = x3;
  }
}
__device__ __forceinline__ void sincos8k(int n, float& s, float& c) {
  const float x = (float)((n << 19) >> 19) * (6.283185307179586f / 8192.f);
  s = __sinf(x); c = __cosf(x);
}
__device__ __forceinline__ void fft_tables(uint32_t f1a, uint32_t f2a, int w, int lane, uint32_t* tp, uint32_t* ts, float& d0r, float& d0i) {
  const int c = lane & 3, f1 = 8 * w + (lane >> 2);
#pragma unroll 1
  for (int J = 3; J >= 0; J--) {
    const int a = 8 * J + 2 * c;
    float s0, c0, s1, c1;
    sincos8k(64 * (4 * f1 + 1) * a + 31 * (4 * f1 - 63), d0i, d0r); sincos8k(64 * (4 * f1 + 1) * (a + 1) + 31 * (4 * f1 - 63), s1, c1);
    d0r *= 0.125f; d0i *= 0.125f;
    sts32(f1a + w * 1024 + J * 128 + lane * 4, pack_bf16(d0r, 0.125f * c1)); sts32(f1a + w * 1024 + 512 + J * 128 + lane * 4, pack_bf16(d0i, 0.125f * s1));
    sincos8k(128 * (2 * (a & 15) + 1) * f1 - 128 * (a & 16), s0, c0); sincos8k(128 * (2 * (a & 15) + 3) * f1 - 128 * (a & 16), s1, c1);
    sts32(f2a + w * 512 + J * 128 + lane * 4, pack_bf16(c0, c1));
    sincos8k((4 * f1 - 63) * (2 * a - 31), s0, c0); sincos8k((4 * f1 - 63) * (2 * a - 29), s1, c1);
#pragma unroll
    for (int i = 3; i > 0; i--) { ts[i] = ts[i - 1]; tp[i] = tp[i - 1]; }
    ts[0] = pack_bf16(s0, s1); tp[0] = pack_bf16(-__fdividef(s0, 1.f + c0), -__fdividef(s1, 1.f + c1));
  }
  if (c != 0) d0r = d0i = 0.f;
}

__device__ __forceinline__ void ss_n16_in(float* d, uint64_t da, uint64_t db, uint32_t zero) {
  asm volatile("{\n.reg .pred p;\nsetp.ne.b32 p, %10, 0;\nwgmma.mma_async.sync.aligned.m64n16k16.f32.bf16.bf16 {%0,%1,%2,%3,%4,%5,%6,%7}, %8, %9, p, 1, 1, 0, 0;\n}\n" : R8(d, 0) : "l"(da), "l"(db), "r"(zero));
}
__device__ __forceinline__ void ss_n16(float* d, uint64_t da, uint64_t db) {
  asm volatile("wgmma.mma_async.sync.aligned.m64n16k16.f32.bf16.bf16 {%0,%1,%2,%3,%4,%5,%6,%7}, %8, %9, 0, 1, 1, 0, 0;" : W8(d, 0) : "l"(da), "l"(db));
}
template <int N> __device__ __forceinline__ void rename_regs(float* d) {
#pragma unroll
  for (int i = 0; i < N; i++) { float t; asm volatile("mov.b32 %0, %1;" : "=f"(t) : "f"(d[i]) : "memory"); d[i] = t; }
}

template <int SWAPB>
__global__ void __cluster_dims__(2, 1, 1) __launch_bounds__(512, 1)
fused_kernel(const __grid_constant__ Params P, const __grid_constant__ CUtensorMap mX, const __grid_constant__ CUtensorMap mB,
             const __grid_constant__ CUtensorMap mCre, const __grid_constant__ CUtensorMap mCim, const __grid_constant__ CUtensorMap mXs,
             const __grid_constant__ CUtensorMap mK, const __grid_constant__ CUtensorMap mV, const __grid_constant__ CUtensorMap mQ, const __grid_constant__ CUtensorMap mS,
             const __grid_constant__ CUtensorMap mO) {
  extern __shared__ __align__(1024) uint8_t smem_raw[];
  if (threadIdx.x == 0) { prefetch_map(&mX); prefetch_map(&mB); }
  const uint32_t sb = (uint32_t)__cvta_generic_to_shared(smem_raw);
  const uint32_t bars = sb + OFF_BAR;
  const int slot = (P.slot[blockIdx.x >> 3] >> (4 * (blockIdx.x & 6))) & 63, rank = blockIdx.x & 1;
  const int j = slot & 7, tc = 2 * (slot >> 3) + rank, b = 2 * slot + rank;
  const int tid = threadIdx.x;
  const int warp = __shfl_sync(0xffffffffu, tid >> 5, 0);
  const int wg = warp >> 2;
  const uint32_t c_start = clk32();
  auto kblock = [&](int n) { return ((n & 14) == 0 || (n & 14) == 2 * j ? n ^ (2 * j) : n) & 31; };
  auto send_y = [&](int r) {
    const uint32_t src = sb + OFF_U + 4 * (rank ^ 1) * U_N8 + r * U_CH, dst = r >= 2 ? sb + OFF_U + 4 * rank * U_N8 + (r - 2) * U_CH : sb + OFF_IN + 96 + r * 2064;
#pragma unroll 1
    for (int n = 0; n < 4; n++) bulk_send(dst + n * (r >= 2 ? U_N8 : 512), src + n * U_N8, 512, bars + (B_IN + r) * 8, rank ^ 1);
  };
  auto load_q = [&](int i, int off, int bar) {
    const uint32_t fb = bars + bar * 8 + 4 * (i & 2);
    mbar_expect(fb, 4096); tma4d(sb + off + 2048 * (i & 2), &mQ, 16 * slot, 0, 4 * i, 4 * rank, fb);
  };
  auto head = [&](int n) {
    const uint32_t fb = bars + (B_FULL + n) * 8, dst = sb + OFF_RING + n * STAGE_BYTES;
    mbar_expect(fb, STAGE_BYTES);
    tma4d(dst + 16384, &mX, 64 * n, 0, 4 * tc, 0, fb);
    tma4d(dst, &mB, 64 * n, 0, 0, 8 * j, fb);
    tma4d(dst + 8192, &mB, 64 * n, 0, 0, 8 * j + 4, fb);
  };
  if (warp == 0 && elect_one()) {
#pragma unroll
    for (int s = 0; s < STAGES; s++) mbar_init(bars + (B_FULL + s) * 8, 1);
    head(0);
    asm volatile("fence.mbarrier_init.release.cluster;" ::: "memory");
  }
  if (wg == 3 && elect_one()) {
    if (warp < 15) {
#pragma unroll
      for (int s = 0; s < 13; s++) mbar_init(bars + 8 * B_XI + (warp & 3) * 104 + 8 * s, 1);
    } else {
#pragma unroll
      for (int s = B_XI + 39; s <= B_NONE; s++) mbar_init(bars + 8 * s, s < B_EMPTY ? 1 : s < B_COEF ? 2 : s == B_COEF ? 128 : 4);
    }
    asm volatile("fence.mbarrier_init.release.cluster;" ::: "memory");
  }
  __syncwarp();
  asm volatile("barrier.cluster.arrive.relaxed.aligned;" ::: "memory");
  if (warp == 0 && elect_one()) {
#pragma unroll 1
    for (int n = 1; n < HEAD; n++) { spin_until(c_start, ST_T0 + n * ST_DELAY); head(n); }
  }
  __syncwarp();
  int fl;
  uint32_t fa, fs;
  uint2 q[4][4];
  auto fin_setup = [&]() {
    asm volatile("mov.u32 %0, %%laneid;" : "=r"(fl));
    const int lc = 2 * (fl & 2) + (fl & 1) + ((fl >> 2) & 2);
    const bool own = ((fl >> 2) & 1) == rank, spare = !own && lc < 2;
    fa = (spare ? sb + OFF_IN + 96 + lc * 2064 : sb + OFF_U + (own ? 4 * rank * U_N8 : 4 * (rank ^ 1) * U_N8 - 2 * U_CH) + lc * U_CH) + (warp & 3) * 128 + (fl >> 4) * 16 + (wg & 1) * 64;
    fs = spare ? 512 : U_N8;
  };
  auto get_q = [&](int n, int off, int bar, int ph) {
#pragma unroll
    for (int u = 0; u < 2; u++) {
      mbar_wait(bars + (bar + u) * 8, ph);
#pragma unroll
      for (int r = 0; r < 4; r++) q[n + u][r] = lds64(sb + off + 4096 * u + 1024 * (warp & 3) + 256 * r + 8 * fl);
    }
  };
#define CLUSTER_WAIT() asm volatile("barrier.cluster.wait.aligned;" ::: "memory")

  if (wg == 3) {
    asm volatile("setmaxnreg.dec.sync.aligned.u32 24;");
    CLUSTER_WAIT();
    if (warp < 14) {
      if (elect_one()) {
        uint32_t so = 8 * (HEAD % STAGES), ph = HEAD < STAGES;
        auto step = [&](auto issue) {
          mbar_wait(bars + B_EMPTY * 8 + so, ph);
          issue(sb + OFF_RING + (so << 12), bars + B_FULL * 8 + so);
          so += 8;
          if (so == 8 * STAGES) { so = 0; ph ^= 1; }
        };
        if (warp == 12) {
          auto g1 = [&](int n0, int n1, int grp) {
#pragma unroll 1
            for (int n = n0; n < n1; n++) step([&](uint32_t dst, uint32_t fb) { mbar_expect(fb, STAGE_BYTES); tma4d_mc(dst + rank * 8192, &mB, n * 64, 0, 0, grp + 4 * rank, fb); });
          };
#pragma unroll 1
          for (int n = HEAD; n < STAGES; n++) { spin_until(c_start, ST_T0 + n * ST_DELAY); g1(n, n + 1, 8 * j); }
          g1(STAGES, 16, 8 * j);
          g1(0, XPOS - 16, 8 * j + 64);
          step([&](uint32_t dst, uint32_t fb) { mbar_expect(fb, STAGE_BYTES); tma4d(dst, &mXs, 128 * j, 0, 4 * tc, 0, fb); });
#pragma unroll 1
          for (int n = 0; n < 32; n += 2) {
            const int col = kblock(n) * 32;
#pragma unroll
            for (int part = 0; part < 2; part++)
              step([&](uint32_t dst, uint32_t fb) { mbar_expect(fb, STAGE_BYTES); tma5d_mc(dst + rank * 8192, part ? &mCim : &mCre, col, 0, 0, 0, 8 * j + 4 * rank, fb); });
          }
        } else {
          auto g1 = [&](int n0, int n1, int nb) {
#pragma unroll 1
            for (int n = n0; n < n1; n++) step([&](uint32_t dst, uint32_t fb) { tma4d(dst + 16384, &mX, n * 64, 0, 4 * tc, 0, fb); });
          };
          auto g2 = [&](int n0, int n1) {
#pragma unroll 1
            for (int n = n0; n < n1; n++) step([&](uint32_t dst, uint32_t fb) { bulk_load(dst + 16384, g_h + (32 * tc + kblock(n)) * 1024, 16384, fb); });
          };
#pragma unroll 1
          for (int n = HEAD; n < STAGES; n++) { spin_until(c_start, ST_T0 + n * ST_DELAY); g1(n, n + 1, 0); }
          g1(STAGES, 16, 0);
          g1(0, XPOS - 16, 16);
          step([&](uint32_t dst, uint32_t fb) { tma4d(dst + 16384, &mXs, 128 * j + 64, 0, 4 * tc, 0, fb); });
#pragma unroll 1
          for (int v = 0; v < 2; v++) {
            mbar_wait(bars + B_HP * 8, v);
            fence_proxy_async_global();
            g2(16 * v, 16 * v + 2);
            mbar_wait(bars + B_HR * 8, v);
            fence_proxy_async_global();
            g2(16 * v + 2, 16 * v + 16);
          }
        }
      }
    } else if (warp == 15) {
      mbar_wait(bars + B_COEF * 8, 0);
      const unsigned epoch = lds32(bars + B_EPOCH * 8);
#pragma unroll 1
      for (int v = 0; v < 2; v++) {
        unsigned* fp = &g_flagH[tc * 32 + v];
        if (elect_one()) {
          wait_until(v ? clk32() : c_start, (v ? PFC_T1 : PFC_T0) + (slot >> 3) * PFC_DT);
#pragma unroll
          for (int part = 0; part < 2; part++)
            asm volatile("cp.async.bulk.prefetch.tensor.5d.L2.global [%0, {%1, %2, %2, %2, %3}];" ::"l"(part ? &mCim : &mCre), "r"(512 * v + 8 * (slot & 56)), "r"(0), "r"(8 * j + 4 * rank) : "memory");
        }
        __syncwarp();
        bar_sync(4 + v, 160);
        if (elect_one()) {
          asm volatile("red.release.gpu.global.add.u32 [%0], 1;" ::"l"(fp) : "memory");
          mbar_arrive(bars + B_HP * 8);
          int it = 0;
          while (ld_acquire(fp) != 8 * epoch && ++it < (SPIN_LIMIT << 4)) __nanosleep(POLL_NS);
          mbar_arrive(bars + B_HR * 8);
        }
        __syncwarp();
      }
    } else if (elect_one()) {
      const int ch0 = 16 * slot;
      auto load_k = [&](int s, uint32_t dst) { const uint32_t fb = bars + (B_KF + s) * 8; mbar_expect(fb, 4096); tma2d(dst, &mS, 0, 64 * (8 * b + s), fb); };
      prefetch_map(&mS); prefetch_map(&mK); prefetch_map(&mV);
      wait_until(c_start, K_T0);
      load_k(0, sb + OFF_U + (4 * rank + 3) * U_N8); load_k(1, sb + OFF_U + (4 * rank + 3) * U_N8 - 4096);
      {
        uint32_t so = 16, ph = 1;
#pragma unroll 1
        for (int e = 0; e < 9; e++) {
          const uint32_t fb = bars + B_KVF * 8 + so, dst = sb + OFF_KV + (so << 10);
          wait_until(c_start, KV_T0 + (e ? 2 * e - 1 : 0) * KV_DT - (e > KV_E ? e - KV_E : 0) * 2 * (KV_DT - KV_D2));
          mbar_wait(bars + B_KVE * 8 + so, ph);
          const uint32_t c1 = clk32();
          mbar_expect(fb, e ? 8192 : 4096);
          tma3d(dst, &mK, ch0, 32 * rank - (e == 0), (4 * e - 4) & 31, fb);
          if (e > 0) { wait_until(c1, KV_DV); tma3d(dst + 4096, &mV, ch0, 32 * rank, 4 * e - 4, fb); }
          so += 8;
          if (so == 24) so = 0;
          if (so == 16) ph ^= 1;
        }
      }
      prefetch_map(&mCre); prefetch_map(&mCim); prefetch_map(&mXs); prefetch_map(&mQ); prefetch_map(&mO);
      mbar_wait(bars + B_KVE * 8, 0);
      load_k(2, sb + OFF_K); load_k(3, sb + OFF_K + 4096);
      mbar_wait(bars + (B_UF + 3) * 8, 0);
#pragma unroll 1
      for (int ch = 0; ch < 7; ch++) {
        mbar_wait(bars + (B_ST + ch) * 8, 0);
        if (ch > 2) mbar_wait(bars + (B_IN + ch - 3) * 8, 0);
        if (ch < 4) load_k(ch + 4, sb + OFF_K + (ch & 1) * 4096);
        else if (ch < 6) load_q(2 * (ch & 1), OFF_K, B_KF + 8);
        if (ch > 0) send_y(ch - 1);
        if (ch == 2) load_q(1, OFF_Q, B_QF);
        if (ch == 3) asm volatile("cp.async.bulk.prefetch.tensor.4d.L2.global [%0, {%1, %2, %3, %4}];" ::"l"(&mQ), "r"(16 * (slot & ~3)), "r"(0), "r"(16 + 4 * (slot & 3)), "r"(4 * rank) : "memory");
        if (ch == 4) { mbar_wait(bars + B_XI * 8, 0); load_q(3, OFF_Q, B_QF); }
      }
    }
    return;
  } else if (wg == 2) {
    asm volatile("setmaxnreg.inc.sync.aligned.u32 %0;" ::"n"(488 - 2 * GREG));
    const int t = tid & 127, w = warp & 3, lane = t & 31, g = lane >> 2, c = lane & 3;
    const uint4 s2[2] = {ldg128_nc(P.shift_k + (8 * b + 2 * c) * 4), ldg128_nc(P.shift_k + (8 * (b ^ 1) + 2 * c) * 4)};
    const uint32_t dskip = __bfloat16_as_ushort(P.ssm_D[8 * b + (t & 7)]);
    uint32_t tp[4] = {}, ts[4] = {};
    float d0r, d0i;
    fft_tables(sb + OFF_F1, sb + OFF_F2, w, lane, tp, ts, d0r, d0i);
    CLUSTER_WAIT();
    if (t < 12) mbar_expect(bars + (B_IN + t) * 8, t < 6 ? 2048 : t < 8 ? 4 * (U_CH + 512) : U_N8);
    if (t < 8) sts32(sb + OFF_D + 8 * t, dskip << 16);
    const uint64_t dF1b = make_desc(sb + OFF_F1, 512, 128, 0);
    const uint64_t dF2f = make_desc(sb + OFF_F2, 512, 128, 0), dF2i = make_desc(sb + OFF_F2, 128, 512, 0);
    uint32_t f1[8];
#pragma unroll
    for (int i = 0; i < 8; i++) f1[i] = lds32(sb + OFF_F1 + w * 1024 + (i & 1) * 512 + (i >> 1) * 128 + lane * 4);
    auto T1k = [&](float* z, uint64_t dk) { wg_fence(); rs_n64<0, 1>(z, f1, dk); rs_n64<1, 1>(z, f1 + 4, dk + 64); wg_commit(); };
    auto T1u = [&](float* z, uint64_t du) { wg_fence(); rs_n64<0, 0>(z, f1, du); rs_n64<1, 0>(z, f1 + 4, du + 16); wg_commit(); };
    auto T2 = [&](float* s, const uint32_t* f) {
      wg_fence();
      rs_n32<0, 1>(s, f, dF2f); rs_n32<0, 1>(s + 16, f + 8, dF2f); rs_n32<1, 1>(s, f + 4, dF2f + 64); rs_n32<1, 1>(s + 16, f + 12, dF2f + 64);
      wg_commit();
    };
    auto product = [&](uint32_t* pr, const uint32_t* kh, const uint32_t* uh) {
      bimac<0>(pr, kh, uh, pr); bimac<2>(pr + 8, kh + 8, uh, pr); bimac<1>(pr + 8, kh, uh + 8, pr + 8);
      fence_u32<16>(pr);
    };
    float zk[32] = {};
    uint32_t pr[16];
    {
      uint32_t kh0[16];
      {
        float z0[32], sk[32];
        uint32_t fk[16];
        const uint64_t dk = make_desc(sb + OFF_U + (4 * rank + 3) * U_N8, 2048, 512, 2);
        fence_proxy_async_smem();
        bar_sync(7, 128);
        mbar_wait(bars + B_KF * 8, 0);
        T1k(z0, dk);
        mbar_wait(bars + (B_KF + 1) * 8, 0);
        T1k(zk, dk - 256);
        wg_wait<0>(); fence_regs<32>(z0); fence_regs<32>(zk);
        const float dd = __uint_as_float(lds32(sb + OFF_D));
        z0[0] = fmaf(d0r, dd, z0[0]); z0[2] = fmaf(d0i, dd, z0[2]);
        pack32(fk, z0); twiddle<0>(fk, tp, ts); fence_u32<16>(fk);
        T2(sk, fk);
        wg_wait<0>(); fence_regs<32>(sk); fence_u32<16>(fk);
        pack32(kh0, sk); fence_u32<16>(kh0);
      }
      {
        uint32_t sk[2][4], kx[2][8];
#pragma unroll
        for (int o = 0; o < 2; o++) {
          sk[o][0] = __byte_perm(s2[o].x, s2[o].z, 0x5410); sk[o][1] = __byte_perm(s2[o].x, s2[o].z, 0x7632);
          sk[o][2] = __byte_perm(s2[o].y, s2[o].w, 0x5410); sk[o][3] = __byte_perm(s2[o].y, s2[o].w, 0x7632);
        }
        const uint32_t la = sb + OFF_KV + (lane >> 3) * 1024 + (8 * w + (lane & 7)) * 32 + ((rank ^ ((lane >> 2) & 1)) << 4);
        const uint32_t uo = (lane & 7) * U_CH + w * 128 + (lane >> 3) * 16;
        mbar_wait(bars + (B_KVF + 2) * 8, 0);
        ldsm4(kx[0], la + 16384); ldsm4(kx[1], (la ^ 16) + 16384);
        if (lane == 0) mbar_arrive(bars + (B_KVE + 2) * 8 + (kx[0][1] & kx[1][1] & P.zero));
        uint32_t so = 0, ph = 0;
#pragma unroll 1
        for (int n = 0; n < 4; n++) {
          const uint32_t own = sb + OFF_U + (4 * rank + n) * U_N8, box = n < 3 ? sb + OFF_U + (4 * (rank ^ 1) + n + 1) * U_N8 : sb + OFF_IN;
#pragma unroll
          for (int e = 0; e < 2; e++) {
            uint32_t vx[2][4];
            mbar_wait(bars + B_KVF * 8 + so, ph);
#pragma unroll
            for (int o = 0; o < 2; o++) { ldsm4(kx[o] + 4, (la ^ (16 * o)) + (so << 10)); ldsm4(vx[o], (la ^ (16 * o)) + (so << 10) + 4096); }
            if (lane == 0) mbar_arrive(bars + B_KVE * 8 + so + (kx[0][4] & kx[1][4] & vx[0][0] & vx[1][0] & P.zero));
#pragma unroll
            for (int o = 0; o < 2; o++) {
#pragma unroll
              for (int i = 0; i < 4; i++) vx[o][i] = bmul2(bfma2(kx[o][i + 4], sk[o][0], bfma2(kx[o][i + 3], sk[o][1], bfma2(kx[o][i + 2], sk[o][2], bmul2(kx[o][i + 1], sk[o][3])))), vx[o][i]);
              stsm4t((o ? box : own) + uo + e * 64, vx[o][0], vx[o][1], vx[o][2], vx[o][3]);
              kx[o][1] = kx[o][5]; kx[o][2] = kx[o][6]; kx[o][3] = kx[o][7];
            }
            so += 8;
            if (so == 24) so = 0;
            if (so == 16) ph ^= 1;
          }
          fence_proxy_async_smem();
          bar_sync(7, 128);
          if (w == 0 && elect_one()) {
            if (n > 0) mbar_wait(bars + B_UF * 8 + 8 * (n - 1), 0);
            bulk_send(own, box, U_N8, bars + B_UF * 8 + 8 * n, rank ^ 1);
          }
          __syncwarp();
        }
      }
      float zu[32], su[32];
      uint32_t fu[16], uh[16];
#pragma unroll
      for (int n = 0; n < 4; n++) mbar_wait(bars + (B_UF + n) * 8, 0);
      T1u(zu, make_desc(sb + OFF_U, 128, U_N8, 0));
      wg_wait<0>(); fence_regs<32>(zu);
      pack32(fu, zu); twiddle<0>(fu, tp, ts); fence_u32<16>(fu);
      T2(su, fu);
      wg_wait<0>(); fence_regs<32>(su); fence_u32<16>(fu);
      pack32(uh, su);
      product(pr, kh0, uh);
    }
    {
#define CF(i) do { if ((CFM >> (i)) & 1) PMFENCE(); } while (0)
      const uint32_t vs = w < 2 ? 512 : U_N8, vi = (w >> 1) * U_CH;
      uint32_t va = (w < 2 ? sb + OFF_VP : sb + OFF_U) + ((lane >> 4) & 1) * vs + (w & 1) * 256 + (lane & 15) * 16;
      const uint32_t ya = sb + OFF_U + (2 * w + ((lane >> 3) & 1)) * U_N8 + (lane >> 4) * 128 + (lane & 7) * 16;
      uint64_t du = make_desc(sb + OFF_U, 128, U_N8, 0), dk = make_desc(sb + OFF_K, 2048, 512, 2);
      const uint64_t dv = make_desc(sb + OFF_VP, 128, 512, 0), dks = 2 * dk + 256;
      uint32_t yp[8] = {};
      uint32_t yq = sb + OFF_Q + lane * 16, yi = ya - yq;
      auto store_y = [&]() { stsm4(yq, yp[0], yp[1], yp[2], yp[3]); stsm4(yq + 256, yp[4], yp[5], yp[6], yp[7]); };
      auto step = [&](uint32_t c8, auto fwd) {
        constexpr bool FWD = decltype(fwd)::value;
        float zu[32], sk[32], su[32], v[32], y[16];
        uint32_t kh[16], uh[16], fk[16], fu[16], fv[16];
        wg_fence();
        rs_n32<0, 0>(v, pr, dF2i); rs_n32<0, 0>(v + 16, pr + 8, dF2i); rs_n32<1, 0>(v, pr + 4, dF2i + 16); rs_n32<1, 0>(v + 16, pr + 12, dF2i + 16);
        wg_commit();
        CF(0);
        const float dd = FWD ? __uint_as_float(lds32(sb + OFF_D + 8 + c8)) : 0.f;
        store_y();
        if (FWD) {
          zk[0] = fmaf(d0r, dd, zk[0]); zk[2] = fmaf(d0i, dd, zk[2]);
          pack32(fk, zk); twiddle<0>(fk, tp, ts); fence_u32<16>(fk);
          T2(sk, fk);
          CF(2);
          mbar_wait(bars + (B_KF + 2) * 8 + c8, 0);
          wg_wait<1>();
        } else {
#pragma unroll
          for (int r = 3; r < 6; r++) mbar_wait(bars + (B_IN + r) * 8, 0);
          wg_wait<0>();
        }
        fence_regs<32>(v); fence_u32<16>(pr);
        pack32(fv, v); fence_u32<16>(fv);
        CF(4);
        if (FWD) T1u(zu, du + U_CH / 16);
        CF(5);
        if (FWD) { wg_wait<1>(); fence_regs<32>(sk); fence_u32<16>(fk); pack32(kh, sk); }
        twiddle<1>(fv, tp, ts);
        fence_u32<16>(fv);
        if (FWD) fence_u32<16>(kh);
        CF(7);
        if (FWD) T1k(zk, dk);
#pragma unroll
        for (int i = 0; i < 4; i++) stsm4(va + 2 * i * vs, fv[4 * i], fv[4 * i + 1], fv[4 * i + 2], fv[4 * i + 3]);
        if (FWD) {
          CF(8);
          wg_wait<1>(); fence_regs<32>(zu);
          pack32(fu, zu); twiddle<0>(fu, tp, ts); fence_u32<16>(fu);
          T2(su, fu);
          CF(10);
        }
        fence_proxy_async_smem();
        bar_sync(7, 128);
        wg_fence();
        ss_n32_tt<0>(y, dv, dF1b); ss_n32_tt<1>(y, dv + 16, dF1b + 64); ss_n32_tt<1>(y, du, dF1b + 128); ss_n32_tt<1>(y, du + 16, dF1b + 192);
        wg_commit();
        CF(12);
        if (FWD) {
          wg_wait<1>(); fence_regs<32>(su); fence_u32<16>(fu); fence_regs<32>(zk);
          if (t == 0) mbar_arrive(bars + B_ST * 8 + c8);
          pack32(uh, su);
          bimac<0>(pr, kh, uh, pr); bimac<2>(pr + 8, kh + 8, uh, pr); fence_u32<16>(pr);
          CF(14);
          wg_wait<0>(); fence_regs<16>(y);
          bimac<1>(pr + 8, kh, uh + 8, pr + 8); fence_u32<8>(pr + 8);
          du += U_CH / 16; dk = dks - dk;
          va += vi;
        }
        if (!FWD) {
          PMFENCE();
          fin_setup(); get_q(0, OFF_K, B_KF + 8, 0);
#pragma unroll
          for (int r = 0; r < 8; r++) q[2 + (r >> 2)][r & 3] = make_uint2(0, 0);
          wg_wait<0>(); fence_regs<16>(y);
        }
#pragma unroll
        for (int i = 0; i < 8; i++) yp[i] = pack_bf16(y[2 * i], y[2 * i + 1]);
        fence_u32<8>(yp);
        yq += yi; yi = U_CH;
      };
#pragma unroll 1
      for (uint32_t c8 = 0; c8 < 56; c8 += 8) step(c8, std::true_type());
      step(56, std::false_type());
      store_y();
    }
    fence_proxy_async_smem();
    bar_sync(7, 128);
    if (elect_one()) bulk_send(sb + OFF_U + (4 * rank + w) * U_N8 + 4 * U_CH, sb + OFF_U + (4 * (rank ^ 1) + w) * U_N8 + 6 * U_CH, U_CH + 512, bars + (B_IN + 6) * 8, rank ^ 1);
    __syncwarp();
    asm volatile("bar.arrive 9, 256;" ::: "memory");
  } else {
    asm volatile("setmaxnreg.inc.sync.aligned.u32 %0;" ::"n"(GREG));
    const int t = tid & 127, w = warp & 3, lane = t & 31, g = lane >> 2, c = lane & 3;
    if (wg == 1) {
      wait_until(c_start, COEF_T0);
      const int p = 64 * j + (t & 63) + 8 * (t & 64);
      const float Lr = bf2f(P.lam_re[p]), Li = bf2f(P.lam_im[p]);
      const uint32_t ds = __bfloat16_as_ushort(P.Dskip[128 * j + t]);
      const unsigned epoch = (ld_relaxed(&g_flagH[tc * 32]) >> 3) + 1;
      const float dt = bf2f(__float2bfloat16_rn(expf(bf2f(P.log_dt[p]))));
      const float e = expf(dt * Lr);
      float sn, cs;
      {
        const double z = (double)(dt * Li) * 0.15915494309189535;
        sincospif(2.f * (float)(z - rint(z)), &sn, &cs);
      }
      const float lr = e * cs, li = e * sn;
      const float nr = lr - 1.0f, ni = li;
      const bool big = fabsf(Lr) >= fabsf(Li);
      const float la = big ? Lr : Li, lb = big ? Li : Lr, r = __fdiv_rn(lb, la), inv = __frcp_rn(fmaf(lb, r, la));
      const float br = (big ? fmaf(ni, r, nr) : fmaf(nr, r, ni)) * inv, bi = (big ? fmaf(-nr, r, ni) : fmaf(ni, r, -nr)) * inv;
      sts128(sb + OFF_COEF + t * 16, make_uint4(__float_as_uint(lr), __float_as_uint(li), pack_bf16(2.f * br, 2.f * br), pack_bf16(-2.f * bi, -2.f * bi)));
      sts32(sb + OFF_DS + 4 * t, ds << 16);
      if (t == 0) sts32(bars + B_EPOCH * 8, epoch);
    }
    CLUSTER_WAIT();
    if (wg == 1) mbar_arrive(bars + B_COEF * 8);
    float d[128];
    uint32_t so = 0, ph = 0, po = 0;
    uint32_t ra;
    auto set_ra = [&]() { asm volatile("mapa.shared::cluster.u32 %0, %1, %2;" : "=r"(ra) : "r"(bars + B_EMPTY * 8), "r"((t & 1) ? rank ^ 1 : rank)); };
    set_ra();
    auto release = [&](uint32_t off) { if (t < 2) asm volatile("mbarrier.arrive.shared::cluster.b64 _, [%0];" ::"r"(ra + off) : "memory"); };
    constexpr uint32_t NOBAR = 8 * (B_NONE - B_EMPTY);
    auto block = [&](auto ta, uint64_t da0, uint64_t db0, bool zero, int nn) {
      constexpr int PH = decltype(ta)::value, TA = PH > 0, KS = TA ? 128 : 2, QD = PH == 0 ? QD1 : PH == 1 ? QD2 : QD3;
      mbar_wait(bars + B_FULL * 8 + so, ph);
      const uint64_t da = da0 + (so << 8), db = db0 + (so << 8);
      wg_fence();
      wgmma_n128<TA>(d, da, db, !zero);
      wgmma_n128<TA>(d + 64, da + 512, db, !zero);
      wg_commit();
      wg_wait<1>();
      release(po);
#pragma unroll
      for (int k = 1; k < 4; k++) {
        if (QD == 2 || (QD == 4 && k == 2)) wg_fence();
        wgmma_n128<TA>(d, da + KS * k, db + 2 * k, 1);
        wgmma_n128<TA>(d + 64, da + 512 + KS * k, db + 2 * k, 1);
        if (QD == 2 || (QD == 4 && k == 1)) wg_commit();
        if ((QD == 2 && k < 3) || (QD == 4 && k == 1)) wg_wait<1>();
      }
      if (QD != 2) wg_commit();
      po = so;
      so += 8;
      if (so == 8 * STAGES) { so = 0; ph ^= 1; }
    };
    {
      so = wg ? 8 * (16 % STAGES) : 0; ph = wg ? (16 / STAGES) & 1 : 0; po = NOBAR;
      const uint64_t da0 = make_desc(sb + OFF_RING, 16, 1024, 1), db0 = make_desc(sb + OFF_RING + 16384, 16, 1024, 1);
      if (wg == 1) bar_sync(1, 256);
#pragma unroll 1
      for (int kb = 0; kb < 16; kb++) {
        block(std::integral_constant<int, 0>(), da0, db0, kb == 0, 16 * wg + kb);
      }
      asm volatile("bar.arrive %0, 256;" ::"r"(1 + wg) : "memory");
    }
    mbar_wait(bars + B_COEF * 8, 0);
    const uint32_t ca = sb + OFF_COEF + (64 * wg + 8 * w + g) * 16;
    const uint32_t tag = __shfl_sync(0xffffffffu, lds32(bars + B_EPOCH * 8) & 3, 0);
    constexpr int RE = SWAPB ? 2 : 0, IM = 2 - RE;
    const int ct = lane >> 3;
    const uint2* cp = g_carry + __shfl_sync(0xffffffffu, ((16 * wg + 2 * j) * 16 + tc - 1 - ct) * 32 + 8 * w + (lane & 7), lane);
    const uint2* sp = g_carry + __shfl_sync(0xffffffffu, ((16 * wg + 2 * j) * 16 + tc) * 32 + 8 * w + g, lane);
    unsigned long long cv[4];
    const int nv = tc - ct;
    auto load_carry = [&](int i) {
#pragma unroll
      for (int m = 0; m < 4; m++)
        asm volatile("{\n.reg .pred p;\nsetp.gt.s32 p, %2, %3;\n@p ld.relaxed.gpu.global.b64 %0, [%1];\n}\n" : "+l"(cv[m]) : "l"(cp + 512 * i - 128 * m), "r"(nv), "r"(4 * m) : "memory");
    };
    float lr[2], li[2], pr[2], pi[2], wr[2], wi[2], vr[2], vi[2], qr[2], qi[2], gr[2], gi[2];
#pragma unroll
    for (int i = 0; i < 2; i++) {
      const uint2 cf = lds64(ca + 512 * i);
      pr[i] = lr[i] = __uint_as_float(cf.x); pi[i] = li[i] = __uint_as_float(cf.y);
#pragma unroll
      for (int s = 0; s < 4; s++) csq(pr[i], pi[i]);
      gr[i] = pr[i]; gi[i] = pi[i];
      csq(pr[i], pi[i]);
      asm volatile("" : "+f"(pr[i]), "+f"(pi[i]));
    }
    PMFENCE();
    wg_wait<0>();
    fence_regs<128>(d);
    release(po);
#pragma unroll
    for (int i = 0; i < 2; i++) {
      float* e = d + 64 * i;
      auto chain = [&](int s0, int s1, float& sr, float& si) {
        sr = e[2 * s0 + RE]; si = e[2 * s0 + IM];
#pragma unroll
        for (int s = s0 + 1; s < s1; s++) {
          const int ia = 4 * (s >> 1) + (s & 1);
          const float nr = fmaf(-li[i], si, fmaf(lr[i], sr, e[ia + RE])), ni = fmaf(li[i], sr, fmaf(lr[i], si, e[ia + IM]));
          sr = nr; si = ni;
        }
      };
      float sr, si;
      if (i == 1) { cv[0] = cv[1] = cv[2] = cv[3] = tag; asm volatile("" : "+l"(cv[0]), "+l"(cv[1]), "+l"(cv[2]), "+l"(cv[3])); }
      if ((GREEDY >> i) & 1) {
        float ar, ai;
        chain(0, 16, ar, ai); chain(16, 32, sr, si);
        sr = fmaf(gr[i], ar, fmaf(-gi[i], ai, sr)); si = fmaf(gr[i], ai, fmaf(gi[i], ar, si));
      } else chain(0, 32, sr, si);
      if (i == 1) { asm volatile("pmevent 0;" : "+f"(sr), "+f"(si)::"memory"); load_carry(0); PMFENCE(); }
      float ur[3], ui[3], er = 0.f, ei = 0.f;
#pragma unroll
      for (int m = 0; m < 3; m++) { ur[m] = __shfl_up_sync(0xffffffffu, sr, m + 1, 4); ui[m] = __shfl_up_sync(0xffffffffu, si, m + 1, 4); }
      if (c == 3) { er = ur[2]; ei = ui[2]; }
#pragma unroll
      for (int m = 1; m >= 0; m--) {
        const float nr = fmaf(pr[i], er, fmaf(-pi[i], ei, ur[m])), ni = fmaf(pr[i], ei, fmaf(pi[i], er, ui[m]));
        if (c > m) { er = nr; ei = ni; }
      }
      sr = fmaf(pr[i], er, fmaf(-pi[i], ei, sr)); si = fmaf(pr[i], ei, fmaf(pi[i], er, si));
      asm volatile("{\n.reg .pred p;\n.reg .b64 v;\nsetp.eq.u32 p, %3, 3;\nmov.b64 v, {%1,%2};\n@p st.relaxed.gpu.global.b64 [%0], v;\n}\n"
                   ::"l"(sp + 512 * i), "r"((__float_as_uint(sr) & ~3u) | tag), "r"(__float_as_uint(si)), "r"(c) : "memory");
      e[RE] = fmaf(lr[i], er, fmaf(-li[i], ei, e[RE])); e[IM] = fmaf(lr[i], ei, fmaf(li[i], er, e[IM]));
      PMFENCE();
      asm volatile("" : "+f"(e[RE]), "+f"(e[IM]));
    }
#pragma unroll
    for (int i = 0; i < 2; i++) {
      qr[i] = pr[i]; qi[i] = pi[i];
      csq(qr[i], qi[i]);
      wr[i] = (c & 1) ? pr[i] : 1.f; wi[i] = (c & 1) ? pi[i] : 0.f;
      if (c & 2) { float x, y; cmul(wr[i], wi[i], qr[i], qi[i], x, y); wr[i] = x; wi[i] = y; }
      vr[i] = wr[i]; vi[i] = wi[i];
      csq(vr[i], vi[i]); csq(vr[i], vi[i]);
      csq(qr[i], qi[i]); csq(qr[i], qi[i]); csq(qr[i], qi[i]);
      const int src = 4 * (lane & 7) + ct;
      vr[i] = __shfl_sync(0xffffffffu, vr[i], src); vi[i] = __shfl_sync(0xffffffffu, vi[i], src);
      qr[i] = __shfl_sync(0xffffffffu, qr[i], src); qi[i] = __shfl_sync(0xffffffffu, qi[i], src);
    }
    uint4* hp = g_h + (32 * tc + 16 * wg + 2 * j) * 1024 + 64 * w + 4 * g + (c ^ (g >> 1));
    float sr[2], si[2];
    uint32_t gp[2], gm[2];
    auto carry_in = [&](int i) {
      auto ready = [&]() { return __all_sync(0xffffffffu, ((((uint32_t)cv[0] ^ tag) | ((uint32_t)cv[1] ^ tag) | ((uint32_t)cv[2] ^ tag) | ((uint32_t)cv[3] ^ tag)) & 3) == 0); };
      if (!ready()) {
        int n = 0;
#pragma unroll 1
        do load_carry(i); while (!ready() && ++n <= (SPIN_LIMIT << 4));
      }
      float hr = __uint_as_float((uint32_t)cv[3]), hi = __uint_as_float((uint32_t)(cv[3] >> 32));
#pragma unroll
      for (int m = 2; m >= 0; m--) {
        const float nr = fmaf(qr[i], hr, fmaf(-qi[i], hi, __uint_as_float((uint32_t)cv[m]))), ni = fmaf(qr[i], hi, fmaf(qi[i], hr, __uint_as_float((uint32_t)(cv[m] >> 32))));
        hr = nr; hi = ni;
      }
      { float x, y; cmul(hr, hi, vr[i], vi[i], x, y); hr = x; hi = y; }
      const uint4 cf = lds128(ca + 512 * i);
      lr[i] = __uint_as_float(cf.x); li[i] = __uint_as_float(cf.y); gp[i] = cf.z; gm[i] = cf.w;
      hr += __shfl_xor_sync(0xffffffffu, hr, 8); hi += __shfl_xor_sync(0xffffffffu, hi, 8);
      hr = __shfl_sync(0xffffffffu, hr, g) + __shfl_sync(0xffffffffu, hr, g + 16); hi = __shfl_sync(0xffffffffu, hi, g) + __shfl_sync(0xffffffffu, hi, g + 16);
      cmul(wr[i], wi[i], hr, hi, sr[i], si[i]);
    };
    PMFENCE();
    carry_in(0);
#pragma unroll
    for (int u = 0; u < 8; u++) {
      const int i = u >> 2, i8 = u & 3;
      float* e = d + 64 * i;
      asm volatile("pmevent 0;" : "+f"(sr[i]), "+f"(si[i])::"memory");
      if (u == 1) load_carry(1);
      if (u == 3) carry_in(1);
#pragma unroll
      for (int s = 8 * i8; s < 8 * i8 + 8; s++) {
        const int ia = 4 * (s >> 1) + (s & 1);
        const float nr = fmaf(-li[i], si[i], fmaf(lr[i], sr[i], e[ia + RE])), ni = fmaf(li[i], sr[i], fmaf(lr[i], si[i], e[ia + IM]));
        sr[i] = nr; si[i] = ni;
        e[ia + RE] = nr; e[ia + IM] = ni;
      }
      uint32_t hq[8];
#pragma unroll
      for (int m = 0; m < 4; m++) {
        const float* f = e + 16 * i8 + 4 * m;
        const uint32_t x = pack_bf16(f[RE], f[RE + 1]), y = pack_bf16(f[IM], f[IM + 1]);
        hq[m] = bfma2(gp[i], x, bmul2(gm[i], y)); hq[4 + m] = bfnma2(gp[i], y, bmul2(gm[i], x));
      }
      uint4* o = hp + 512 * (i8 >> 1) + 256 * i + 32 * (i8 & 1);
      stg128(o, make_uint4(hq[0], hq[1], hq[2], hq[3]));
      stg128(o + 1024, make_uint4(hq[4], hq[5], hq[6], hq[7]));
#pragma unroll
      for (int m = 0; m < 8; m++) d[16 * u + m] = __uint_as_float(hq[m]);
      fence_regs<8>(d + 16 * u);
    }
    const int trow = 128 * tc + 64 * (w & 1) + 8 * (w >> 1) + g;
    const int dcol = 128 * j + 4 * c;
    asm volatile("bar.arrive %0, 160;" ::"r"(4 + wg) : "memory");
    if (wg == 0) {
      set_ra();
      {
        const uint32_t dt = sb + OFF_Q + 4096;
        mbar_wait(bars + (B_UF + 3) * 8, 0);
        const int n = t & 15, k = 2 * (n & 6) + 2 * (n >> 3) + (n & 1);
        const uint32_t dv = lds32(sb + OFF_DS + (t & ~15) * 4 + 4 * k) >> (16 - 16 * (k & 1));
#pragma unroll
        for (int u = 0; u < 2; u++) {
          const int m = (k >> 1) - 4 * u;
          sts128(dt + (t >> 4) * 512 + u * 256 + n * 16, make_uint4(m == 0 ? dv : 0, m == 1 ? dv : 0, m == 2 ? dv : 0, m == 3 ? dv : 0));
        }
        fence_proxy_async_smem();
        bar_sync(2, 256);
        mbar_wait(bars + (B_FULL + XPOS % STAGES) * 8, (XPOS / STAGES) & 1);
        const uint64_t dx = make_desc(sb + OFF_RING + (XPOS % STAGES) * STAGE_BYTES, 16, 1024, 1), dd = make_desc(dt, 256, 128, 0);
        wg_fence();
#pragma unroll
        for (int u = 0; u < 16; u++) {
          const uint64_t da = dx + ((u >> 2) & 1) * 1024 + (u >> 3) * 512 + (u & 3) * 2, db = dd + (u & 7) * 32;
          if (u & 1) ss_n16(d + 8 * u, da, db); else ss_n16_in(d + 8 * u, da, db, P.zero);
        }
        wg_commit();
        wg_wait<0>();
        rename_regs<128>(d);
        release(8 * (XPOS % STAGES));
        if (t == 0) mbar_arrive(bars + B_XI * 8);
      }
      so = 8 * (33 % STAGES); ph = (33 / STAGES) & 1; po = NOBAR;
      const uint64_t da0 = make_desc(sb + OFF_RING + 16384, 512, 1024, 2), db0 = make_desc(sb + OFF_RING, 16, 1024, 1);
#pragma unroll 1
      for (int kb = 0; kb < QSW; kb++) block(std::integral_constant<int, 1>(), da0, db0, false, 32 + kb);
#pragma unroll 1
      for (int kb = QSW; kb < 32 - TAILB; kb++) block(std::integral_constant<int, 2>(), da0, db0, false, 32 + kb);
      float* op = P.out + (size_t)trow * 2048 + 1024 + dcol;
      auto mma = [&](int i, int kb, int k0, int k1) {
        const int s = (33 + kb) % STAGES;
        wg_fence();
#pragma unroll
        for (int k = k0; k < k1; k++) wgmma_n128<1>(d + 64 * i, da0 + s * 2048 + 512 * i + 128 * k, db0 + (i ? 0 : P.zero) + s * 2048 + 2 * k, 1);
        wg_commit();
      };
      auto store = [&](int i, int J0, int J1) {
#pragma unroll
        for (int J = J0; J < J1; J++) {
#pragma unroll
          for (int h = 0; h < 2; h++) {
            const float* e = d + 64 * i + 8 * J + 2 * h;
            stg128(op + (size_t)(16 * i + 32 * h) * 2048 + 16 * J, make_uint4(__float_as_uint(e[0]), __float_as_uint(e[1]), __float_as_uint(e[4]), __float_as_uint(e[5])));
          }
        }
        PMFENCE();
      };
      constexpr int K0 = 32 - TAILB;
#pragma unroll
      for (int kb = K0; kb < 32; kb++) {
        mbar_wait(bars + (B_FULL + (33 + kb) % STAGES) * 8, ((33 + kb) / STAGES) & 1);
        if (TAILB == 5 && kb == K0) { mma(0, kb, 0, 2); wg_wait<1>(); release(po); mma(0, kb, 2, 4); }
        else mma(0, kb, 0, 4);
      }
      mma(1, K0, 0, 4);
      wg_wait<1>();
      fence_regs<64>(d);
#pragma unroll
      for (int kb = K0 + 1; kb < 32; kb++) {
        mma(1, kb, 0, 4);
        store(0, T_ST * (kb - K0 - 1), kb == 31 ? 8 : T_ST * (kb - K0));
      }
      wg_wait<0>();
      fence_regs<64>(d + 64);
      store(1, 0, 8);
      return;
    }
    asm volatile("setmaxnreg.dec.sync.aligned.u32 %0;" ::"n"(488 - 2 * GREG));
    fin_setup();
#pragma unroll
    for (int n = 0; n < 4; n += 2) {
      get_q(n, OFF_Q, B_QF, n >> 1);
      uint32_t dep = P.zero;
#pragma unroll
      for (int r = 0; r < 8; r++) dep &= q[n + (r >> 2)][r & 3].x;
      bar_sync(6 + dep, 128);
      if (w < 2 && elect_one()) load_q(5 + 2 * w - (n >> 1), OFF_Q, B_QF + n);
      __syncwarp();
    }
#pragma unroll 1
    for (int r = 0; r < 6; r++) mbar_wait(bars + (B_IN + r) * 8, 0);
    bar_sync(9, 256);
  }
  {
    const int w = warp & 3, h = wg & 1, lane = fl;
    const uint32_t ob0 = sb + (h ? OFF_F1 : OFF_K) + 1024 * w, ob1 = sb + (h ? OFF_VP : OFF_K + 4096) + 1024 * w;
    uint32_t y[2][8];
    auto get_y = [&](int n) { ldsm4t(y[n & 1], fa + n * fs); ldsm4t(y[n & 1] + 4, fa + n * fs + 32); };
    mbar_wait(bars + B_HR * 8, 1);
    mbar_wait(bars + (B_IN + 6) * 8, 0);
    get_y(0);
#pragma unroll
    for (int n = 0; n < 4; n++) {
      uint32_t* o = y[n & 1];
#pragma unroll
      for (int r = 0; r < 4; r++) { o[2 * r] = bmul2(o[2 * r], q[n][r].x); o[2 * r + 1] = bmul2(o[2 * r + 1], q[n][r].y); }
      if (n > 0 && lane == 0) asm volatile("cp.async.bulk.wait_group.read 0;" ::: "memory");
      __syncwarp();
#pragma unroll
      for (int r = 0; r < 4; r++)
        sts128((r & 2 ? ob1 : ob0) + (r & 1) * 512 + lane * 16, make_uint4(o[2 * r] << 16, o[2 * r] & 0xffff0000u, o[2 * r + 1] << 16, o[2 * r + 1] & 0xffff0000u));
      fence_proxy_async_smem();
      __syncwarp();
      if (lane == 0) {
#pragma unroll
        for (int u = 0; u < 2; u++)
          asm volatile("cp.async.bulk.tensor.3d.global.shared::cta.bulk_group [%0, {%2, %3, %4}], [%1];"
                       ::"l"(&mO), "r"(u ? ob1 : ob0), "r"(32 * slot), "r"(32 * rank + 8 * w), "r"(8 * n + 4 * h + 2 * u) : "memory");
        asm volatile("cp.async.bulk.commit_group;" ::: "memory");
      }
      __syncwarp();
      if (n < 3) get_y(n + 1);
      if (n == 1 && !h) get_q(2, OFF_Q, B_QF + 2, 0);
    }
    if (warp == 8 && lane == 0) mbar_arrive_cta(bars + B_ACK * 8, rank ^ 1);
    if (lane == 0) asm volatile("cp.async.bulk.wait_group 0;" ::: "memory");
    mbar_wait(bars + B_ACK * 8, 0);
  }
}

typedef CUresult (*EncodeFn)(CUtensorMap*, CUtensorMapDataType, cuuint32_t, void*, const cuuint64_t*, const cuuint64_t*, const cuuint32_t*,
                             const cuuint32_t*, CUtensorMapInterleave, CUtensorMapSwizzle, CUtensorMapL2promotion, CUtensorMapFloatOOBfill);

bool encode(EncodeFn fn, CUtensorMap* m, int rank, const void* base, const cuuint64_t* dims, const cuuint64_t* strides, const cuuint32_t* box, CUtensorMapSwizzle swz,
            CUtensorMapL2promotion promo = CU_TENSOR_MAP_L2_PROMOTION_L2_128B) {
  const cuuint32_t es[5] = {1, 1, 1, 1, 1};
  return fn(m, CU_TENSOR_MAP_DATA_TYPE_BFLOAT16, rank, const_cast<void*>(base), dims, strides, box, es, CU_TENSOR_MAP_INTERLEAVE_NONE, swz,
            promo, CU_TENSOR_MAP_FLOAT_OOB_FILL_NONE) == CUDA_SUCCESS;
}

}

extern "C" void kernel_launch(void* const* d_in, const int* in_sizes, int n_in, void* d_out, int out_size) {
  (void)in_sizes; (void)n_in; (void)out_size;
  typedef const __nv_bfloat16* In;
  const In q = (In)d_in[0], k = (In)d_in[1], v = (In)d_in[2], ssm_k = (In)d_in[4], x = (In)d_in[6], B_re = (In)d_in[9], B_im = (In)d_in[10], C_re = (In)d_in[11], C_im = (In)d_in[12];
  Params P = {};
  P.shift_k = (In)d_in[3]; P.ssm_D = (In)d_in[5]; P.lam_re = (In)d_in[7]; P.lam_im = (In)d_in[8]; P.log_dt = (In)d_in[13]; P.Dskip = (In)d_in[14];
  P.out = (float*)d_out;
  for (int cl = 0; cl < 64; cl++) P.slot[cl >> 2] |= (cl < 4 ? 4 + cl : cl < 36 ? 8 * ((cl - 4) & 7) + ((cl - 4) >> 3) : 8 * (1 + (cl - 36) % 7) + 4 + (cl - 36) / 7) << (8 * (cl & 3));
  const bool swapB = (uintptr_t)B_im < (uintptr_t)B_re;

  EncodeFn fn = nullptr;
  cudaDriverEntryPointQueryResult qr;
  cudaGetDriverEntryPoint("cuTensorMapEncodeTiled", (void**)&fn, cudaEnableDefault, &qr);
  if (!fn) return;

  CUtensorMap mX, mB, mCre, mCim, mXs, mK, mV, mQ, mS, mO;
  bool ok = true;
  {
    const cuuint64_t dims[4] = {1024, 2, 64, 16}, str[3] = {2048, 32 * 2048, 2 * 2048};
    const cuuint32_t box[4] = {64, 2, 4, 16};
    ok &= encode(fn, &mX, 4, x, dims, str, box, CU_TENSOR_MAP_SWIZZLE_128B);
  }
  {
    const uintptr_t lo = swapB ? (uintptr_t)B_im : (uintptr_t)B_re, hi = swapB ? (uintptr_t)B_re : (uintptr_t)B_im;
    const cuuint64_t dims[4] = {1024, 8, 2, 128}, str[3] = {2048, (cuuint64_t)(hi - lo), 8 * 2048};
    const cuuint32_t box[4] = {64, 8, 2, 4};
    ok &= encode(fn, &mB, 4, (const void*)lo, dims, str, box, CU_TENSOR_MAP_SWIZZLE_128B);
  }
  {
    const cuuint64_t dims[5] = {1024, 2, 4, 2, 64}, str[4] = {2048, 4 * 2048, 2 * 2048, 16 * 2048};
    const cuuint32_t box[5] = {64, 2, 4, 2, 4};
    ok &= encode(fn, &mCre, 5, C_re, dims, str, box, CU_TENSOR_MAP_SWIZZLE_128B);
    ok &= encode(fn, &mCim, 5, C_im, dims, str, box, CU_TENSOR_MAP_SWIZZLE_128B);
  }
  {
    const cuuint64_t dims[4] = {1024, 8, 64, 4}, str[3] = {2048, 32 * 2048, 8 * 2048};
    const cuuint32_t box[4] = {64, 8, 4, 4};
    ok &= encode(fn, &mXs, 4, x, dims, str, box, CU_TENSOR_MAP_SWIZZLE_128B);
  }
  {
    const cuuint64_t dims[3] = {1024, 64, 32}, str[2] = {32 * 2048, 2048};
    const cuuint32_t box[3] = {16, 32, 4};
    const cuuint64_t dimq[4] = {1024, 8, 32, 8}, strq[3] = {32 * 2048, 2048, 256 * 2048};
    const cuuint32_t boxq[4] = {16, 8, 4, 4};
    ok &= encode(fn, &mQ, 4, q, dimq, strq, boxq, CU_TENSOR_MAP_SWIZZLE_NONE);
    ok &= encode(fn, &mK, 3, k, dims, str, box, CU_TENSOR_MAP_SWIZZLE_32B);
    ok &= encode(fn, &mV, 3, v, dims, str, box, CU_TENSOR_MAP_SWIZZLE_32B);
  }
  {
    const cuuint64_t dims[2] = {32, 65536}, str[1] = {64};
    const cuuint32_t box[2] = {32, 64};
    ok &= encode(fn, &mS, 2, ssm_k, dims, str, box, CU_TENSOR_MAP_SWIZZLE_64B);
  }
  {
    const cuuint64_t dims[3] = {2048, 64, 32}, str[2] = {32 * 8192, 8192};
    const cuuint32_t box[3] = {32, 8, 2};
    ok &= encode(fn, &mO, 3, d_out, dims, str, box, CU_TENSOR_MAP_SWIZZLE_NONE);
  }
  if (!ok) return;
  auto kern = swapB ? fused_kernel<1> : fused_kernel<0>;
  cudaFuncSetAttribute(kern, cudaFuncAttributeMaxDynamicSharedMemorySize, SMEM_BYTES);
  kern<<<NCTA, 512, SMEM_BYTES, cudaStreamPerThread>>>(P, mX, mB, mCre, mCim, mXs, mK, mV, mQ, mS, mO);
}
```

```cpp
#include <cuda_runtime.h>
#include <cuda_bf16.h>
#include <cuda.h>
#include <stdint.h>
#include <type_traits>

namespace {

constexpr int D_DIM = 1024;
constexpr int NCTA = 128;

constexpr int STAGES = 5, STAGE_BYTES = 32768;
constexpr int OFF_RING = 0;
constexpr int OFF_F1 = STAGES * STAGE_BYTES, OFF_F2 = OFF_F1 + 4096, OFF_K = OFF_F2 + 2048, OFF_VP = OFF_K + 8192, OFF_Q = OFF_VP + 4096, OFF_IN = OFF_Q + 8192;
constexpr int OFF_KV = OFF_K;
constexpr int U_CH = 528, U_N8 = 8 * U_CH, OFF_U = OFF_IN + U_N8;
constexpr int OFF_COEF = OFF_U + 8 * U_N8;
constexpr int OFF_DS = OFF_COEF + 2048, OFF_D = OFF_DS + 512;
constexpr int OFF_BAR = OFF_D + 64;
constexpr int SMEM_BYTES = OFF_BAR + 512;
static_assert(SMEM_BYTES <= 232448 && OFF_K % 1024 == 0 && (OFF_U + 3 * U_N8) % 512 == 0 && (4 * U_N8) % 512 == 0, "smem map");
constexpr int B_FULL = 0, B_XI = 5, B_HR = 6, B_HP = 8, B_KVF = 10, B_QF = 13, B_IN = 17, B_UF = 25, B_ACK = 29, B_KF = 30, B_ST = 40,
              B_EMPTY = 47, B_COEF = 52, B_KVE = 53, B_NONE = 56, B_EPOCH = 57;

constexpr int QD1 = 8;
constexpr int QD2 = 2;
constexpr int QD3 = 8;
constexpr int QSW = 16;
constexpr int HEAD = 3;
constexpr int ST_T0 = 200;
constexpr int ST_DELAY = 300;
constexpr int XPOS = 32;
constexpr int K_T0 = 800;
constexpr int KV_T0 = 1500;
constexpr int KV_DT = 620;
constexpr int KV_DV = 450;
constexpr int POLL_NS = 30;
constexpr int GREEDY = 1;
constexpr int TAILB = 5;
constexpr int GREG = 168;
constexpr int COEF_T0 = 2500;
constexpr int T_ST = 2;
constexpr int PFC_T0 = 12500;
constexpr int PFC_T1 = 1500;
constexpr int PFC_DT = 250;
constexpr int KV_E = 6;
constexpr int KV_D2 = 300;
constexpr int CFM = 0x40f1;
constexpr int SPIN_LIMIT = 1 << 14;

struct Params {
  unsigned slot[16];
  unsigned zero;
  const __nv_bfloat16 *shift_k, *ssm_D, *lam_re, *lam_im, *log_dt, *Dskip;
  float* out;
};

__device__ __align__(1024) uint4 g_h[16 * 32 * 1024];
__device__ __align__(128) uint2 g_carry[32 * 16 * 32];
__device__ __align__(128) unsigned g_flagH[16 * 32];

__device__ __forceinline__ uint64_t make_desc(uint32_t addr, uint32_t lbo, uint32_t sbo, uint32_t swz) {
  return (uint64_t)((addr & 0x3FFFF) >> 4) | ((uint64_t)(lbo >> 4) << 16) | ((uint64_t)(sbo >> 4) << 32) | ((uint64_t)swz << 62);
}
__device__ __forceinline__ void wg_fence() { asm volatile("wgmma.fence.sync.aligned;" ::: "memory"); }
__device__ __forceinline__ void wg_commit() { asm volatile("wgmma.commit_group.sync.aligned;" ::: "memory"); }
template <int N> __device__ __forceinline__ void wg_wait() { asm volatile("wgmma.wait_group.sync.aligned %0;" ::"n"(N) : "memory"); }
__device__ __forceinline__ void mbar_init(uint32_t bar, int cnt) { asm volatile("mbarrier.init.shared::cta.b64 [%0], %1;" ::"r"(bar), "r"(cnt) : "memory"); }
__device__ __forceinline__ void mbar_expect(uint32_t bar, uint32_t bytes) { asm volatile("mbarrier.arrive.expect_tx.shared::cta.b64 _, [%0], %1;" ::"r"(bar), "r"(bytes) : "memory"); }
__device__ __forceinline__ bool mbar_try(uint32_t bar, uint32_t parity) {
  uint32_t ok;
  asm volatile("{\n.reg .pred p;\nmbarrier.try_wait.parity.shared::cta.b64 p, [%1], %2;\nselp.u32 %0, 1, 0, p;\n}\n" : "=r"(ok) : "r"(bar), "r"(parity) : "memory");
  return ok;
}
__device__ __forceinline__ void mbar_wait(uint32_t bar, uint32_t parity) {
  if (__builtin_expect(!mbar_try(bar, parity), 0)) {
#pragma unroll 1
    for (int n = 0; n < SPIN_LIMIT && !mbar_try(bar, parity); n++) {}
  }
}
__device__ __forceinline__ void mbar_arrive(uint32_t bar) { asm volatile("mbarrier.arrive.shared::cta.b64 _, [%0];" ::"r"(bar) : "memory"); }
__device__ __forceinline__ void mbar_arrive_cta(uint32_t bar, uint32_t cta) {
  asm volatile("{\n.reg .b32 ra;\nmapa.shared::cluster.u32 ra, %0, %1;\nmbarrier.arrive.shared::cluster.b64 _, [ra];\n}\n" ::"r"(bar), "r"(cta) : "memory");
}
__device__ __forceinline__ bool elect_one() {
  uint32_t p;
  asm volatile("{\n.reg .pred P;\nelect.sync _|P, 0xffffffff;\nselp.u32 %0, 1, 0, P;\n}\n" : "=r"(p));
  return p != 0;
}
__device__ __forceinline__ void bar_sync(int id, int n) { asm volatile("bar.sync %0, %1;" ::"r"(id), "r"(n) : "memory"); }
#define TMA_LD(dim) "cp.async.bulk.tensor." dim ".shared::cluster.global.mbarrier::complete_tx::bytes"
__device__ __forceinline__ void tma2d(uint32_t dst, const CUtensorMap* m, int c0, int c1, uint32_t bar) {
  asm volatile(TMA_LD("2d") " [%0], [%1, {%3, %4}], [%2];" ::"r"(dst), "l"(m), "r"(bar), "r"(c0), "r"(c1) : "memory");
}
__device__ __forceinline__ void tma3d(uint32_t dst, const CUtensorMap* m, int c0, int c1, int c2, uint32_t bar) {
  asm volatile(TMA_LD("3d") " [%0], [%1, {%3, %4, %5}], [%2];" ::"r"(dst), "l"(m), "r"(bar), "r"(c0), "r"(c1), "r"(c2) : "memory");
}
__device__ __forceinline__ void tma4d(uint32_t dst, const CUtensorMap* m, int c0, int c1, int c2, int c3, uint32_t bar) {
  asm volatile(TMA_LD("4d") " [%0], [%1, {%3, %4, %5, %6}], [%2];" ::"r"(dst), "l"(m), "r"(bar), "r"(c0), "r"(c1), "r"(c2), "r"(c3) : "memory");
}
__device__ __forceinline__ void tma4d_mc(uint32_t dst, const CUtensorMap* m, int c0, int c1, int c2, int c3, uint32_t bar) {
  asm volatile(TMA_LD("4d") ".multicast::cluster [%0], [%1, {%3, %4, %5, %6}], [%2], %7;" ::"r"(dst), "l"(m), "r"(bar), "r"(c0), "r"(c1), "r"(c2), "r"(c3), "h"((uint16_t)3) : "memory");
}
__device__ __forceinline__ void tma5d_mc(uint32_t dst, const CUtensorMap* m, int c0, int c1, int c2, int c3, int c4, uint32_t bar) {
  asm volatile(TMA_LD("5d") ".multicast::cluster [%0], [%1, {%3, %4, %5, %6, %7}], [%2], %8;" ::"r"(dst), "l"(m), "r"(bar), "r"(c0), "r"(c1), "r"(c2), "r"(c3), "r"(c4), "h"((uint16_t)3) : "memory");
}
__device__ __forceinline__ void bulk_load(uint32_t dst, const void* src, uint32_t bytes, uint32_t bar) {
  asm volatile("cp.async.bulk.shared::cluster.global.mbarrier::complete_tx::bytes [%0], [%1], %2, [%3];" ::"r"(dst), "l"(src), "r"(bytes), "r"(bar) : "memory");
}
__device__ __forceinline__ void bulk_send(uint32_t dst, uint32_t src, uint32_t bytes, uint32_t bar, uint32_t cta) {
  asm volatile("{\n.reg .b32 rd, rb;\nmapa.shared::cluster.u32 rd, %0, %3;\nmapa.shared::cluster.u32 rb, %2, %3;\n"
               "cp.async.bulk.shared::cluster.shared::cta.mbarrier::complete_tx::bytes [rd], [%1], %4, [rb];\n}\n"
               ::"r"(dst), "r"(src), "r"(bar), "r"(cta), "r"(bytes) : "memory");
}
__device__ __forceinline__ void fence_proxy_async_smem() { asm volatile("fence.proxy.async.shared::cta;" ::: "memory"); }
__device__ __forceinline__ void fence_proxy_async_global() { asm volatile("fence.proxy.async.global;" ::: "memory"); }
__device__ __forceinline__ uint32_t clk32() { uint32_t c; asm volatile("mov.u32 %0, %%clock;" : "=r"(c)::"memory"); return c; }
__device__ __forceinline__ void wait_until(uint32_t t0, uint32_t dt) { while (clk32() - t0 < dt) __nanosleep(32); }
__device__ __forceinline__ void spin_until(uint32_t t0, uint32_t dt) { while (clk32() - t0 < dt) {} }
__device__ __forceinline__ void prefetch_map(const CUtensorMap* m) { asm volatile("prefetch.tensormap [%0];" ::"l"(m) : "memory"); }
__device__ __forceinline__ void prefetch_line(const void* p) { asm volatile("prefetch.global.L2 [%0];" ::"l"(p) : "memory"); }
__device__ __forceinline__ unsigned ld_acquire(const unsigned* p) { unsigned v; asm volatile("ld.acquire.gpu.global.u32 %0, [%1];" : "=r"(v) : "l"(p) : "memory"); return v; }
__device__ __forceinline__ unsigned ld_relaxed(const unsigned* p) { unsigned v; asm volatile("ld.relaxed.gpu.global.u32 %0, [%1];" : "=r"(v) : "l"(p) : "memory"); return v; }
__device__ __forceinline__ uint32_t lds32(uint32_t a) { uint32_t v; asm volatile("ld.shared.u32 %0, [%1];" : "=r"(v) : "r"(a)); return v; }
__device__ __forceinline__ uint2 lds64(uint32_t a) { uint2 v; asm volatile("ld.shared.v2.u32 {%0,%1}, [%2];" : "=r"(v.x), "=r"(v.y) : "r"(a) : "memory"); return v; }
__device__ __forceinline__ uint4 lds128(uint32_t a) { uint4 v; asm volatile("ld.shared.v4.u32 {%0,%1,%2,%3}, [%4];" : "=r"(v.x), "=r"(v.y), "=r"(v.z), "=r"(v.w) : "r"(a) : "memory"); return v; }
__device__ __forceinline__ void sts32(uint32_t a, uint32_t v) { asm volatile("st.shared.u32 [%0], %1;" ::"r"(a), "r"(v) : "memory"); }
__device__ __forceinline__ void sts128(uint32_t a, uint4 v) { asm volatile("st.shared.v4.u32 [%0], {%1,%2,%3,%4};" ::"r"(a), "r"(v.x), "r"(v.y), "r"(v.z), "r"(v.w) : "memory"); }
__device__ __forceinline__ void ldsm4(uint32_t* r, uint32_t a) { asm volatile("ldmatrix.sync.aligned.m8n8.x4.shared.b16 {%0,%1,%2,%3}, [%4];" : "=r"(r[0]), "=r"(r[1]), "=r"(r[2]), "=r"(r[3]) : "r"(a) : "memory"); }
__device__ __forceinline__ void ldsm4t(uint32_t* r, uint32_t a) { asm volatile("ldmatrix.sync.aligned.m8n8.x4.trans.shared.b16 {%0,%1,%2,%3}, [%4];" : "=r"(r[0]), "=r"(r[1]), "=r"(r[2]), "=r"(r[3]) : "r"(a) : "memory"); }
__device__ __forceinline__ void stsm4t(uint32_t a, uint32_t r0, uint32_t r1, uint32_t r2, uint32_t r3) {
  asm volatile("stmatrix.sync.aligned.m8n8.x4.trans.shared.b16 [%0], {%1,%2,%3,%4};" ::"r"(a), "r"(r0), "r"(r1), "r"(r2), "r"(r3) : "memory");
}
__device__ __forceinline__ uint4 ldg128_nc(const void* p) { uint4 v; asm volatile("ld.global.nc.L1::no_allocate.v4.u32 {%0,%1,%2,%3}, [%4];" : "=r"(v.x), "=r"(v.y), "=r"(v.z), "=r"(v.w) : "l"(p)); return v; }
__device__ __forceinline__ void stg128(void* p, uint4 v) { asm volatile("st.global.L1::no_allocate.v4.u32 [%0], {%1,%2,%3,%4};" ::"l"(p), "r"(v.x), "r"(v.y), "r"(v.z), "r"(v.w) : "memory"); }
__device__ __forceinline__ uint32_t pack_bf16(float lo, float hi) { uint32_t r; asm("cvt.rn.bf16x2.f32 %0, %1, %2;" : "=r"(r) : "f"(hi), "f"(lo)); return r; }
__device__ __forceinline__ uint32_t bmul2(uint32_t a, uint32_t b) { uint32_t r; asm("mul.rn.bf16x2 %0, %1, %2;" : "=r"(r) : "r"(a), "r"(b)); return r; }
__device__ __forceinline__ uint32_t bfma2(uint32_t a, uint32_t b, uint32_t c) { uint32_t r; asm("fma.rn.bf16x2 %0, %1, %2, %3;" : "=r"(r) : "r"(a), "r"(b), "r"(c)); return r; }
__device__ __forceinline__ uint32_t blo2(uint32_t a) { uint32_t r; asm("{\n.reg .b16 l, h;\nmov.b32 {l, h}, %1;\nmov.b32 %0, {l, l};\n}" : "=r"(r) : "r"(a)); return r; }
__device__ __forceinline__ float bf2f(__nv_bfloat16 v) { return __bfloat162float(v); }

#define R8(d, o) "+f"(d[o]), "+f"(d[o + 1]), "+f"(d[o + 2]), "+f"(d[o + 3]), "+f"(d[o + 4]), "+f"(d[o + 5]), "+f"(d[o + 6]), "+f"(d[o + 7])
#define R16(d, o) R8(d, o), R8(d, o + 8)
#define R64(d, o) R16(d, o), R16(d, o + 16), R16(d, o + 32), R16(d, o + 48)
template <int TA> __device__ __forceinline__ void wgmma_n128(float* d, uint64_t da, uint64_t db, int scale_d) {
  asm volatile("{\n.reg .pred p;\nsetp.ne.b32 p, %66, 0;\n"
    "wgmma.mma_async.sync.aligned.m64n128k16.f32.bf16.bf16 {"
    "%0,%1,%2,%3,%4,%5,%6,%7,%8,%9,%10,%11,%12,%13,%14,%15,%16,%17,%18,%19,%20,%21,%22,%23,%24,%25,%26,%27,%28,%29,%30,%31,"
    "%32,%33,%34,%35,%36,%37,%38,%39,%40,%41,%42,%43,%44,%45,%46,%47,%48,%49,%50,%51,%52,%53,%54,%55,%56,%57,%58,%59,%60,%61,%62,%63"
    "}, %64, %65, p, 1, 1, %67, 0;\n}\n"
    : R64(d, 0)
    : "l"(da), "l"(db), "r"(scale_d), "n"(TA));
}
template <int N> __device__ __forceinline__ void fence_regs(float* d) {
#pragma unroll
  for (int i = 0; i < N; i++) asm volatile("" : "+f"(d[i])::"memory");
}
#define PMFENCE() asm volatile("pmevent 0;" ::: "memory")
__device__ __forceinline__ void cmul(float ar, float ai, float br, float bi, float& cr, float& ci) {
  cr = ar * br - ai * bi; ci = ar * bi + ai * br;
}
__device__ __forceinline__ void csq(float& r, float& i) { const float x = fmaf(r, r, -i * i), y = r * i; r = x; i = y + y; }

#define W8(d, o) "=f"(d[o]), "=f"(d[o + 1]), "=f"(d[o + 2]), "=f"(d[o + 3]), "=f"(d[o + 4]), "=f"(d[o + 5]), "=f"(d[o + 6]), "=f"(d[o + 7])
#define L16 "{%0,%1,%2,%3,%4,%5,%6,%7,%8,%9,%10,%11,%12,%13,%14,%15}"
#define L32 "{%0,%1,%2,%3,%4,%5,%6,%7,%8,%9,%10,%11,%12,%13,%14,%15,%16,%17,%18,%19,%20,%21,%22,%23,%24,%25,%26,%27,%28,%29,%30,%31}"
template <int ACC, int TB> __device__ __forceinline__ void rs_n32(float* d, const uint32_t* a, uint64_t db) {
  if constexpr (ACC) asm volatile("wgmma.mma_async.sync.aligned.m64n32k16.f32.bf16.bf16 " L16 ", {%16,%17,%18,%19}, %20, 1, 1, 1, %21;" : R16(d, 0) : "r"(a[0]), "r"(a[1]), "r"(a[2]), "r"(a[3]), "l"(db), "n"(TB));
  else asm volatile("wgmma.mma_async.sync.aligned.m64n32k16.f32.bf16.bf16 " L16 ", {%16,%17,%18,%19}, %20, 0, 1, 1, %21;" : W8(d, 0), W8(d, 8) : "r"(a[0]), "r"(a[1]), "r"(a[2]), "r"(a[3]), "l"(db), "n"(TB));
}
template <int ACC, int TB> __device__ __forceinline__ void rs_n64(float* d, const uint32_t* a, uint64_t db) {
  if constexpr (ACC) asm volatile("wgmma.mma_async.sync.aligned.m64n64k16.f32.bf16.bf16 " L32 ", {%32,%33,%34,%35}, %36, 1, 1, 1, %37;" : R16(d, 0), R16(d, 16) : "r"(a[0]), "r"(a[1]), "r"(a[2]), "r"(a[3]), "l"(db), "n"(TB));
  else asm volatile("wgmma.mma_async.sync.aligned.m64n64k16.f32.bf16.bf16 " L32 ", {%32,%33,%34,%35}, %36, 0, 1, 1, %37;" : W8(d, 0), W8(d, 8), W8(d, 16), W8(d, 24) : "r"(a[0]), "r"(a[1]), "r"(a[2]), "r"(a[3]), "l"(db), "n"(TB));
}
template <int ACC> __device__ __forceinline__ void ss_n32_tt(float* d, uint64_t da, uint64_t db) {
  if constexpr (ACC) asm volatile("wgmma.mma_async.sync.aligned.m64n32k16.f32.bf16.bf16 " L16 ", %16, %17, 1, 1, 1, 1, 1;" : R16(d, 0) : "l"(da), "l"(db));
  else asm volatile("wgmma.mma_async.sync.aligned.m64n32k16.f32.bf16.bf16 " L16 ", %16, %17, 0, 1, 1, 1, 1;" : W8(d, 0), W8(d, 8) : "l"(da), "l"(db));
}
__device__ __forceinline__ void stsm4(uint32_t a, uint32_t r0, uint32_t r1, uint32_t r2, uint32_t r3) {
  asm volatile("stmatrix.sync.aligned.m8n8.x4.shared.b16 [%0], {%1,%2,%3,%4};" ::"r"(a), "r"(r0), "r"(r1), "r"(r2), "r"(r3) : "memory");
}
template <int N> __device__ __forceinline__ void fence_u32(uint32_t* d) {
#pragma unroll
  for (int i = 0; i < N; i++) asm volatile("" : "+r"(d[i])::"memory");
}
__device__ __forceinline__ void pack32(uint32_t* f, const float* z) {
#pragma unroll
  for (int i = 0; i < 16; i++) f[i] = pack_bf16(z[2 * i], z[2 * i + 1]);
}
template <int INV> __device__ __forceinline__ void twiddle(uint32_t* f, const uint32_t* tp, const uint32_t* ts) {
#pragma unroll
  for (int i = 0; i < 8; i++) {
    uint32_t x = f[2 * i + INV], y = f[2 * i + 1 - INV];
    x = bfma2(tp[i & 3], y, x); y = bfma2(ts[i & 3], x, y); x = bfma2(tp[i & 3], y, x);
    f[2 * i + INV] = x; f[2 * i + 1 - INV] = y;
  }
}
__device__ __forceinline__ uint32_t bfnma2(uint32_t a, uint32_t b, uint32_t c) { uint32_t r; asm("{\n.reg .b32 t;\nmul.bf16x2 t, %1, %2;\nsub.bf16x2 %0, %3, t;\n}" : "=r"(r) : "r"(a), "r"(b), "r"(c)); return r; }
__device__ __forceinline__ uint32_t bfms2(uint32_t a, uint32_t b, uint32_t c) { uint32_t r; asm("{\n.reg .b32 t;\nmul.bf16x2 t, %1, %2;\nsub.bf16x2 %0, t, %3;\n}" : "=r"(r) : "r"(a), "r"(b), "r"(c)); return r; }
template <int ADD> __device__ __forceinline__ void bimac(uint32_t* o, const uint32_t* a, const uint32_t* b, const uint32_t* c) {
#pragma unroll
  for (int J = 0; J < 2; J++) {
    const uint32_t Pr = a[2 * J], Pi = a[2 * J + 1], Qr = a[2 * J + 4], Qi = a[2 * J + 5], pr = b[2 * J], pi = b[2 * J + 1], qr = b[2 * J + 4], qi = b[2 * J + 5];
    uint32_t x0, x1, x2, x3;
    if (ADD == 0) { x0 = bmul2(Pr, pr); x1 = bmul2(Pr, pi); x2 = bmul2(Pr, qr); x3 = bmul2(Pr, qi); }
    if (ADD == 1) { x0 = bfma2(Pr, pr, c[2 * J]); x1 = bfma2(Pr, pi, c[2 * J + 1]); x2 = bfma2(Pr, qr, c[2 * J + 4]); x3 = bfma2(Pr, qi, c[2 * J + 5]); }
    if (ADD == 2) { x0 = bfma2(Pr, pr, c[2 * J + 1]); x1 = bfms2(Pr, pi, c[2 * J]); x2 = bfma2(Pr, qr, c[2 * J + 5]); x3 = bfms2(Pr, qi, c[2 * J + 4]); }
    x0 = bfnma2(Pi, pi, x0); x1 = bfma2(Pi, pr, x1); x2 = bfnma2(Pi, qi, x2); x3 = bfma2(Pi, qr, x3);
    x0 = bfnma2(Qr, qr, x0); x1 = bfnma2(Qr, qi, x1); x2 = bfma2(Qr, pr, x2); x3 = bfma2(Qr, pi, x3);
    x0 = bfma2(Qi, qi, x0); x1 = bfnma2(Qi, qr, x1); x2 = bfnma2(Qi, pi, x2); x3 = bfma2(Qi, pr, x3);
    o[2 * J] = x0; o[2 * J + 1] = x1; o[2 * J + 4] = x2; o[2 * J + 5] = x3;
  }
}
__device__ __forceinline__ void sincos8k(int n, float& s, float& c) {
  const float x = (float)((n << 19) >> 19) * (6.283185307179586f / 8192.f);
  s = __sinf(x); c = __cosf(x);
}
__device__ __forceinline__ void fft_tables(uint32_t f1a, uint32_t f2a, int w, int lane, uint32_t* tp, uint32_t* ts, float& d0r, float& d0i) {
  const int c = lane & 3, f1 = 8 * w + (lane >> 2);
#pragma unroll 1
  for (int J = 3; J >= 0; J--) {
    const int a = 8 * J + 2 * c;
    float s0, c0, s1, c1;
    sincos8k(64 * (4 * f1 + 1) * a + 31 * (4 * f1 - 63), d0i, d0r); sincos8k(64 * (4 * f1 + 1) * (a + 1) + 31 * (4 * f1 - 63), s1, c1);
    d0r *= 0.125f; d0i *= 0.125f;
    sts32(f1a + w * 1024 + J * 128 + lane * 4, pack_bf16(d0r, 0.125f * c1)); sts32(f1a + w * 1024 + 512 + J * 128 + lane * 4, pack_bf16(d0i, 0.125f * s1));
    sincos8k(128 * (2 * (a & 15) + 1) * f1 - 128 * (a & 16), s0, c0); sincos8k(128 * (2 * (a & 15) + 3) * f1 - 128 * (a & 16), s1, c1);
    sts32(f2a + w * 512 + J * 128 + lane * 4, pack_bf16(c0, c1));
    sincos8k((4 * f1 - 63) * (2 * a - 31), s0, c0); sincos8k((4 * f1 - 63) * (2 * a - 29), s1, c1);
#pragma unroll
    for (int i = 3; i > 0; i--) { ts[i] = ts[i - 1]; tp[i] = tp[i - 1]; }
    ts[0] = pack_bf16(s0, s1); tp[0] = pack_bf16(-__fdividef(s0, 1.f + c0), -__fdividef(s1, 1.f + c1));
  }
  if (c != 0) d0r = d0i = 0.f;
}

__device__ __forceinline__ void ss_n16_in(float* d, uint64_t da, uint64_t db, uint32_t zero) {
  asm volatile("{\n.reg .pred p;\nsetp.ne.b32 p, %10, 0;\nwgmma.mma_async.sync.aligned.m64n16k16.f32.bf16.bf16 {%0,%1,%2,%3,%4,%5,%6,%7}, %8, %9, p, 1, 1, 0, 0;\n}\n" : R8(d, 0) : "l"(da), "l"(db), "r"(zero));
}
__device__ __forceinline__ void ss_n16(float* d, uint64_t da, uint64_t db) {
  asm volatile("wgmma.mma_async.sync.aligned.m64n16k16.f32.bf16.bf16 {%0,%1,%2,%3,%4,%5,%6,%7}, %8, %9, 0, 1, 1, 0, 0;" : W8(d, 0) : "l"(da), "l"(db));
}
template <int N> __device__ __forceinline__ void rename_regs(float* d) {
#pragma unroll
  for (int i = 0; i < N; i++) { float t; asm volatile("mov.b32 %0, %1;" : "=f"(t) : "f"(d[i]) : "memory"); d[i] = t; }
}

template <int SWAPB>
__global__ void __cluster_dims__(2, 1, 1) __launch_bounds__(512, 1)
fused_kernel(const __grid_constant__ Params P, const __grid_constant__ CUtensorMap mX, const __grid_constant__ CUtensorMap mB,
             const __grid_constant__ CUtensorMap mCre, const __grid_constant__ CUtensorMap mCim, const __grid_constant__ CUtensorMap mXs,
             const __grid_constant__ CUtensorMap mK, const __grid_constant__ CUtensorMap mV, const __grid_constant__ CUtensorMap mQ, const __grid_constant__ CUtensorMap mS,
             const __grid_constant__ CUtensorMap mO) {
  extern __shared__ __align__(1024) uint8_t smem_raw[];
  if (threadIdx.x == 0) { prefetch_map(&mX); prefetch_map(&mB); }
  const uint32_t sb = (uint32_t)__cvta_generic_to_shared(smem_raw);
  const uint32_t bars = sb + OFF_BAR;
  const int slot = (P.slot[blockIdx.x >> 3] >> (4 * (blockIdx.x & 6))) & 63, rank = blockIdx.x & 1;
  const int j = slot & 7, tc = 2 * (slot >> 3) + rank, b = 2 * slot + rank;
  const int tid = threadIdx.x;
  const int warp = __shfl_sync(0xffffffffu, tid >> 5, 0);
  const int wg = warp >> 2;
  const uint32_t c_start = clk32();
  auto kblock = [&](int n) { return ((n & 14) == 0 || (n & 14) == 2 * j ? n ^ (2 * j) : n) & 31; };
  auto send_y = [&](int r) {
    const uint32_t src = sb + OFF_U + 4 * (rank ^ 1) * U_N8 + r * U_CH, dst = r >= 2 ? sb + OFF_U + 4 * rank * U_N8 + (r - 2) * U_CH : sb + OFF_IN + 96 + r * 2064;
#pragma unroll 1
    for (int n = 0; n < 4; n++) bulk_send(dst + n * (r >= 2 ? U_N8 : 512), src + n * U_N8, 512, bars + (B_IN + r) * 8, rank ^ 1);
  };
  auto load_q = [&](int i, int off, int bar) {
    const uint32_t fb = bars + bar * 8 + 4 * (i & 2);
    mbar_expect(fb, 4096); tma4d(sb + off + 2048 * (i & 2), &mQ, 16 * slot, 0, 4 * i, 4 * rank, fb);
  };
  auto head = [&](int n) {
    const uint32_t fb = bars + (B_FULL + n) * 8, dst = sb + OFF_RING + n * STAGE_BYTES;
    mbar_expect(fb, STAGE_BYTES);
    tma4d(dst + 16384, &mX, 64 * n, 0, 4 * tc, 0, fb);
    tma4d(dst, &mB, 64 * n, 0, 0, 8 * j, fb);
    tma4d(dst + 8192, &mB, 64 * n, 0, 0, 8 * j + 4, fb);
  };
  if (warp == 0 && elect_one()) {
#pragma unroll
    for (int s = 0; s < STAGES; s++) mbar_init(bars + (B_FULL + s) * 8, 1);
    asm volatile("fence.mbarrier_init.release.cluster;" ::: "memory");
    head(0);
  }
  if (wg == 3 && elect_one()) {
    if (warp < 15) {
#pragma unroll
      for (int s = 0; s < 13; s++) mbar_init(bars + 8 * B_XI + (warp & 3) * 104 + 8 * s, 1);
    } else {
#pragma unroll
      for (int s = B_XI + 39; s <= B_NONE; s++) mbar_init(bars + 8 * s, s < B_EMPTY ? 1 : s < B_COEF ? 2 : s == B_COEF ? 128 : 4);
    }
    asm volatile("fence.mbarrier_init.release.cluster;" ::: "memory");
  }
  __syncwarp();
  asm volatile("barrier.cluster.arrive.relaxed.aligned;" ::: "memory");
  if (warp == 0 && elect_one()) {
#pragma unroll 1
    for (int n = 1; n < HEAD; n++) { spin_until(c_start, ST_T0 + n * ST_DELAY); head(n); }
  }
  __syncwarp();
  int fl;
  uint32_t fa, fs;
  uint2 q[4][4];
  auto fin_setup = [&]() {
    asm volatile("mov.u32 %0, %%laneid;" : "=r"(fl));
    const int lc = 2 * (fl & 2) + (fl & 1) + ((fl >> 2) & 2);
    const bool own = ((fl >> 2) & 1) == rank, spare = !own && lc < 2;
    fa = (spare ? sb + OFF_IN + 96 + lc * 2064 : sb + OFF_U + (own ? 4 * rank * U_N8 : 4 * (rank ^ 1) * U_N8 - 2 * U_CH) + lc * U_CH) + (warp & 3) * 128 + (fl >> 4) * 16 + (wg & 1) * 64;
    fs = spare ? 512 : U_N8;
  };
  auto get_q = [&](int n, int off, int bar, int ph) {
#pragma unroll
    for (int u = 0; u < 2; u++) {
      mbar_wait(bars + (bar + u) * 8, ph);
#pragma unroll
      for (int r = 0; r < 4; r++) q[n + u][r] = lds64(sb + off + 4096 * u + 1024 * (warp & 3) + 256 * r + 8 * fl);
    }
  };
#define CLUSTER_WAIT() asm volatile("barrier.cluster.wait.aligned;" ::: "memory")

  if (wg == 3) {
    asm volatile("setmaxnreg.dec.sync.aligned.u32 24;");
    CLUSTER_WAIT();
    if (warp < 14) {
      if (elect_one()) {
        uint32_t so = 8 * (HEAD % STAGES), ph = HEAD < STAGES;
        auto step = [&](auto issue) {
          mbar_wait(bars + B_EMPTY * 8 + so, ph);
          issue(sb + OFF_RING + (so << 12), bars + B_FULL * 8 + so);
          so += 8;
          if (so == 8 * STAGES) { so = 0; ph ^= 1; }
        };
        if (warp == 12) {
          auto g1 = [&](int n0, int n1, int grp) {
#pragma unroll 1
            for (int n = n0; n < n1; n++) step([&](uint32_t dst, uint32_t fb) { mbar_expect(fb, STAGE_BYTES); tma4d_mc(dst + rank * 8192, &mB, n * 64, 0, 0, grp + 4 * rank, fb); });
          };
#pragma unroll 1
          for (int n = HEAD; n < STAGES; n++) { spin_until(c_start, ST_T0 + n * ST_DELAY); g1(n, n + 1, 8 * j); }
          g1(STAGES, 16, 8 * j);
          g1(0, XPOS - 16, 8 * j + 64);
          step([&](uint32_t dst, uint32_t fb) { mbar_expect(fb, STAGE_BYTES); tma4d(dst, &mXs, 128 * j, 0, 4 * tc, 0, fb); });
#pragma unroll 1
          for (int n = 0; n < 32; n += 2) {
            const int col = kblock(n) * 32;
#pragma unroll
            for (int part = 0; part < 2; part++)
              step([&](uint32_t dst, uint32_t fb) { mbar_expect(fb, STAGE_BYTES); tma5d_mc(dst + rank * 8192, part ? &mCim : &mCre, col, 0, 0, 0, 8 * j + 4 * rank, fb); });
          }
        } else {
          auto g1 = [&](int n0, int n1, int nb) {
#pragma unroll 1
            for (int n = n0; n < n1; n++) step([&](uint32_t dst, uint32_t fb) { tma4d(dst + 16384, &mX, n * 64, 0, 4 * tc, 0, fb); });
          };
          auto g2 = [&](int n0, int n1) {
#pragma unroll 1
            for (int n = n0; n < n1; n++) step([&](uint32_t dst, uint32_t fb) { bulk_load(dst + 16384, g_h + (32 * tc + kblock(n)) * 1024, 16384, fb); });
          };
#pragma unroll 1
          for (int n = HEAD; n < STAGES; n++) { spin_until(c_start, ST_T0 + n * ST_DELAY); g1(n, n + 1, 0); }
          g1(STAGES, 16, 0);
          g1(0, XPOS - 16, 16);
          step([&](uint32_t dst, uint32_t fb) { tma4d(dst + 16384, &mXs, 128 * j + 64, 0, 4 * tc, 0, fb); });
#pragma unroll 1
          for (int v = 0; v < 2; v++) {
            mbar_wait(bars + (B_HP + v) * 8, 0);
            fence_proxy_async_global();
            g2(16 * v, 16 * v + 2);
            mbar_wait(bars + (B_HR + v) * 8, 0);
            fence_proxy_async_global();
            g2(16 * v + 2, 16 * v + 16);
          }
        }
      }
    } else if (warp == 15) {
      mbar_wait(bars + B_COEF * 8, 0);
      const unsigned epoch = lds32(bars + B_EPOCH * 8);
#pragma unroll 1
      for (int v = 0; v < 2; v++) {
        unsigned* fp = &g_flagH[tc * 32 + v];
        if (elect_one()) {
          wait_until(v ? clk32() : c_start, (v ? PFC_T1 : PFC_T0) + (slot >> 3) * PFC_DT);
#pragma unroll
          for (int part = 0; part < 2; part++)
            asm volatile("cp.async.bulk.prefetch.tensor.5d.L2.global [%0, {%1, %2, %2, %2, %3}];" ::"l"(part ? &mCim : &mCre), "r"(512 * v + 8 * (slot & 56)), "r"(0), "r"(8 * j + 4 * rank) : "memory");
        }
        __syncwarp();
        bar_sync(4 + v, 160);
        if (elect_one()) {
          asm volatile("red.release.gpu.global.add.u32 [%0], 1;" ::"l"(fp) : "memory");
          mbar_arrive(bars + (B_HP + v) * 8);
          int it = 0;
          while (ld_acquire(fp) != 8 * epoch && ++it < (SPIN_LIMIT << 4)) __nanosleep(POLL_NS);
          mbar_arrive(bars + (B_HR + v) * 8);
        }
        __syncwarp();
      }
    } else if (elect_one()) {
      const int ch0 = 16 * slot;
      auto load_k = [&](int s, uint32_t dst) { const uint32_t fb = bars + (B_KF + s) * 8; mbar_expect(fb, 4096); tma2d(dst, &mS, 0, 64 * (8 * b + s), fb); };
      prefetch_map(&mS); prefetch_map(&mK); prefetch_map(&mV);
      wait_until(c_start, K_T0);
      load_k(0, sb + OFF_U + (4 * rank + 3) * U_N8); load_k(1, sb + OFF_U + (4 * rank + 3) * U_N8 - 4096);
      {
        uint32_t so = 16, ph = 1;
#pragma unroll 1
        for (int e = 0; e < 9; e++) {
          const uint32_t fb = bars + B_KVF * 8 + so, dst = sb + OFF_KV + (so << 10);
          wait_until(c_start, KV_T0 + (e ? 2 * e - 1 : 0) * KV_DT - (e > KV_E ? e - KV_E : 0) * 2 * (KV_DT - KV_D2));
          mbar_wait(bars + B_KVE * 8 + so, ph);
          const uint32_t c1 = clk32();
          mbar_expect(fb, e ? 8192 : 4096);
          tma3d(dst, &mK, ch0, 32 * rank - (e == 0), (4 * e - 4) & 31, fb);
          if (e > 0) { wait_until(c1, KV_DV); tma3d(dst + 4096, &mV, ch0, 32 * rank, 4 * e - 4, fb); }
          so += 8;
          if (so == 24) so = 0;
          if (so == 16) ph ^= 1;
        }
      }
      prefetch_map(&mCre); prefetch_map(&mCim); prefetch_map(&mXs); prefetch_map(&mQ); prefetch_map(&mO);
      mbar_wait(bars + B_KVE * 8, 0);
      load_k(2, sb + OFF_K); load_k(3, sb + OFF_K + 4096);
      mbar_wait(bars + (B_UF + 3) * 8, 0);
#pragma unroll 1
      for (int ch = 0; ch < 7; ch++) {
        mbar_wait(bars + (B_ST + ch) * 8, 0);
        if (ch > 2) mbar_wait(bars + (B_IN + ch - 3) * 8, 0);
        if (ch < 4) load_k(ch + 4, sb + OFF_K + (ch & 1) * 4096);
        else if (ch < 6) load_q(2 * (ch & 1), OFF_K, B_KF + 8);
        if (ch > 0) send_y(ch - 1);
        if (ch == 2) load_q(1, OFF_Q, B_QF);
        if (ch == 3) asm volatile("cp.async.bulk.prefetch.tensor.4d.L2.global [%0, {%1, %2, %3, %4}];" ::"l"(&mQ), "r"(16 * (slot & ~3)), "r"(0), "r"(16 + 4 * (slot & 3)), "r"(4 * rank) : "memory");
        if (ch == 4) { mbar_wait(bars + B_XI * 8, 0); load_q(3, OFF_Q, B_QF); }
      }
    }
    return;
  } else if (wg == 2) {
    asm volatile("setmaxnreg.inc.sync.aligned.u32 %0;" ::"n"(488 - 2 * GREG));
    const int t = tid & 127, w = warp & 3, lane = t & 31, g = lane >> 2, c = lane & 3;
    const uint4 s2[2] = {ldg128_nc(P.shift_k + (8 * b + 2 * c) * 4), ldg128_nc(P.shift_k + (8 * (b ^ 1) + 2 * c) * 4)};
    const uint32_t dskip = __bfloat16_as_ushort(P.ssm_D[8 * b + (t & 7)]);
    uint32_t tp[4] = {}, ts[4] = {};
    float d0r, d0i;
    fft_tables(sb + OFF_F1, sb + OFF_F2, w, lane, tp, ts, d0r, d0i);
    CLUSTER_WAIT();
    if (t < 12) mbar_expect(bars + (B_IN + t) * 8, t < 6 ? 2048 : t < 8 ? 4 * (U_CH + 512) : U_N8);
    if (t < 8) sts32(sb + OFF_D + 8 * t, dskip << 16);
    const uint64_t dF1b = make_desc(sb + OFF_F1, 512, 128, 0);
    const uint64_t dF2f = make_desc(sb + OFF_F2, 512, 128, 0), dF2i = make_desc(sb + OFF_F2, 128, 512, 0);
    uint32_t f1[8];
#pragma unroll
    for (int i = 0; i < 8; i++) f1[i] = lds32(sb + OFF_F1 + w * 1024 + (i & 1) * 512 + (i >> 1) * 128 + lane * 4);
    auto T1k = [&](float* z, uint64_t dk) { wg_fence(); rs_n64<0, 1>(z, f1, dk); rs_n64<1, 1>(z, f1 + 4, dk + 64); wg_commit(); };
    auto T1u = [&](float* z, uint64_t du) { wg_fence(); rs_n64<0, 0>(z, f1, du); rs_n64<1, 0>(z, f1 + 4, du + 16); wg_commit(); };
    auto T2 = [&](float* s, const uint32_t* f) {
      wg_fence();
      rs_n32<0, 1>(s, f, dF2f); rs_n32<0, 1>(s + 16, f + 8, dF2f); rs_n32<1, 1>(s, f + 4, dF2f + 64); rs_n32<1, 1>(s + 16, f + 12, dF2f + 64);
      wg_commit();
    };
    auto product = [&](uint32_t* pr, const uint32_t* kh, const uint32_t* uh) {
      bimac<0>(pr, kh, uh, pr); bimac<2>(pr + 8, kh + 8, uh, pr); bimac<1>(pr + 8, kh, uh + 8, pr + 8);
      fence_u32<16>(pr);
    };
    float zk[32] = {};
    uint32_t pr[16];
    {
      uint32_t kh0[16];
      {
        float z0[32], sk[32];
        uint32_t fk[16];
        const uint64_t dk = make_desc(sb + OFF_U + (4 * rank + 3) * U_N8, 2048, 512, 2);
        fence_proxy_async_smem();
        bar_sync(7, 128);
        mbar_wait(bars + B_KF * 8, 0);
        T1k(z0, dk);
        mbar_wait(bars + (B_KF + 1) * 8, 0);
        T1k(zk, dk - 256);
        wg_wait<0>(); fence_regs<32>(z0); fence_regs<32>(zk);
        const float dd = __uint_as_float(lds32(sb + OFF_D));
        z0[0] = fmaf(d0r, dd, z0[0]); z0[2] = fmaf(d0i, dd, z0[2]);
        pack32(fk, z0); twiddle<0>(fk, tp, ts); fence_u32<16>(fk);
        T2(sk, fk);
        wg_wait<0>(); fence_regs<32>(sk); fence_u32<16>(fk);
        pack32(kh0, sk); fence_u32<16>(kh0);
      }
      {
        uint32_t sk[2][4], kx[2][8];
#pragma unroll
        for (int o = 0; o < 2; o++) {
          sk[o][0] = __byte_perm(s2[o].x, s2[o].z, 0x5410); sk[o][1] = __byte_perm(s2[o].x, s2[o].z, 0x7632);
          sk[o][2] = __byte_perm(s2[o].y, s2[o].w, 0x5410); sk[o][3] = __byte_perm(s2[o].y, s2[o].w, 0x7632);
        }
        const uint32_t la = sb + OFF_KV + (lane >> 3) * 1024 + (8 * w + (lane & 7)) * 32 + ((rank ^ ((lane >> 2) & 1)) << 4);
        const uint32_t uo = (lane & 7) * U_CH + w * 128 + (lane >> 3) * 16;
        mbar_wait(bars + (B_KVF + 2) * 8, 0);
        ldsm4(kx[0], la + 16384); ldsm4(kx[1], (la ^ 16) + 16384);
        if (lane == 0) mbar_arrive(bars + (B_KVE + 2) * 8 + (kx[0][1] & kx[1][1] & P.zero));
        uint32_t so = 0, ph = 0;
#pragma unroll 1
        for (int n = 0; n < 4; n++) {
          const uint32_t own = sb + OFF_U + (4 * rank + n) * U_N8, box = n < 3 ? sb + OFF_U + (4 * (rank ^ 1) + n + 1) * U_N8 : sb + OFF_IN;
#pragma unroll
          for (int e = 0; e < 2; e++) {
            uint32_t vx[2][4];
            mbar_wait(bars + B_KVF * 8 + so, ph);
#pragma unroll
            for (int o = 0; o < 2; o++) { ldsm4(kx[o] + 4, (la ^ (16 * o)) + (so << 10)); ldsm4(vx[o], (la ^ (16 * o)) + (so << 10) + 4096); }
            if (lane == 0) mbar_arrive(bars + B_KVE * 8 + so + (kx[0][4] & kx[1][4] & vx[0][0] & vx[1][0] & P.zero));
#pragma unroll
            for (int o = 0; o < 2; o++) {
#pragma unroll
              for (int i = 0; i < 4; i++) vx[o][i] = bmul2(bfma2(kx[o][i + 4], sk[o][0], bfma2(kx[o][i + 3], sk[o][1], bfma2(kx[o][i + 2], sk[o][2], bmul2(kx[o][i + 1], sk[o][3])))), vx[o][i]);
              stsm4t((o ? box : own) + uo + e * 64, vx[o][0], vx[o][1], vx[o][2], vx[o][3]);
              kx[o][1] = kx[o][5]; kx[o][2] = kx[o][6]; kx[o][3] = kx[o][7];
            }
            so += 8;
            if (so == 24) so = 0;
            if (so == 16) ph ^= 1;
          }
          fence_proxy_async_smem();
          bar_sync(7, 128);
          if (w == 0 && elect_one()) {
            if (n > 0) mbar_wait(bars + B_UF * 8 + 8 * (n - 1), 0);
            bulk_send(own, box, U_N8, bars + B_UF * 8 + 8 * n, rank ^ 1);
          }
          __syncwarp();
        }
      }
      float zu[32], su[32];
      uint32_t fu[16], uh[16];
#pragma unroll
      for (int n = 0; n < 4; n++) mbar_wait(bars + (B_UF + n) * 8, 0);
      T1u(zu, make_desc(sb + OFF_U, 128, U_N8, 0));
      wg_wait<0>(); fence_regs<32>(zu);
      pack32(fu, zu); twiddle<0>(fu, tp, ts); fence_u32<16>(fu);
      T2(su, fu);
      wg_wait<0>(); fence_regs<32>(su); fence_u32<16>(fu);
      pack32(uh, su);
      product(pr, kh0, uh);
    }
    {
#define CF(i) do { if ((CFM >> (i)) & 1) PMFENCE(); } while (0)
      const uint32_t vs = w < 2 ? 512 : U_N8, vi = (w >> 1) * U_CH;
      uint32_t va = (w < 2 ? sb + OFF_VP : sb + OFF_U) + ((lane >> 4) & 1) * vs + (w & 1) * 256 + (lane & 15) * 16;
      const uint32_t ya = sb + OFF_U + (2 * w + ((lane >> 3) & 1)) * U_N8 + (lane >> 4) * 128 + (lane & 7) * 16;
      uint64_t du = make_desc(sb + OFF_U, 128, U_N8, 0), dk = make_desc(sb + OFF_K, 2048, 512, 2);
      const uint64_t dv = make_desc(sb + OFF_VP, 128, 512, 0), dks = 2 * dk + 256;
      uint32_t yp[8] = {};
      uint32_t yq = sb + OFF_Q + lane * 16, yi = ya - yq;
      auto store_y = [&]() { stsm4(yq, yp[0], yp[1], yp[2], yp[3]); stsm4(yq + 256, yp[4], yp[5], yp[6], yp[7]); };
      auto step = [&](uint32_t c8, auto fwd) {
        constexpr bool FWD = decltype(fwd)::value;
        float zu[32], sk[32], su[32], v[32], y[16];
        uint32_t kh[16], uh[16], fk[16], fu[16], fv[16];
        wg_fence();
        rs_n32<0, 0>(v, pr, dF2i); rs_n32<0, 0>(v + 16, pr + 8, dF2i); rs_n32<1, 0>(v, pr + 4, dF2i + 16); rs_n32<1, 0>(v + 16, pr + 12, dF2i + 16);
        wg_commit();
        CF(0);
        const float dd = FWD ? __uint_as_float(lds32(sb + OFF_D + 8 + c8)) : 0.f;
        store_y();
        if (FWD) {
          zk[0] = fmaf(d0r, dd, zk[0]); zk[2] = fmaf(d0i, dd, zk[2]);
          pack32(fk, zk); twiddle<0>(fk, tp, ts); fence_u32<16>(fk);
          T2(sk, fk);
          CF(2);
          mbar_wait(bars + (B_KF + 2) * 8 + c8, 0);
          wg_wait<1>();
        } else {
#pragma unroll
          for (int r = 3; r < 6; r++) mbar_wait(bars + (B_IN + r) * 8, 0);
          wg_wait<0>();
        }
        fence_regs<32>(v); fence_u32<16>(pr);
        pack32(fv, v); fence_u32<16>(fv);
        CF(4);
        if (FWD) T1u(zu, du + U_CH / 16);
        CF(5);
        if (FWD) { wg_wait<1>(); fence_regs<32>(sk); fence_u32<16>(fk); pack32(kh, sk); }
        twiddle<1>(fv, tp, ts);
        fence_u32<16>(fv);
        if (FWD) fence_u32<16>(kh);
        CF(7);
        if (FWD) T1k(zk, dk);
#pragma unroll
        for (int i = 0; i < 4; i++) stsm4(va + 2 * i * vs, fv[4 * i], fv[4 * i + 1], fv[4 * i + 2], fv[4 * i + 3]);
        if (FWD) {
          CF(8);
          wg_wait<1>(); fence_regs<32>(zu);
          pack32(fu, zu); twiddle<0>(fu, tp, ts); fence_u32<16>(fu);
          T2(su, fu);
          CF(10);
        }
        fence_proxy_async_smem();
        bar_sync(7, 128);
        wg_fence();
        ss_n32_tt<0>(y, dv, dF1b); ss_n32_tt<1>(y, dv + 16, dF1b + 64); ss_n32_tt<1>(y, du, dF1b + 128); ss_n32_tt<1>(y, du + 16, dF1b + 192);
        wg_commit();
        CF(12);
        if (FWD) {
          wg_wait<1>(); fence_regs<32>(su); fence_u32<16>(fu); fence_regs<32>(zk);
          if (t == 0) mbar_arrive(bars + B_ST * 8 + c8);
          pack32(uh, su);
          bimac<0>(pr, kh, uh, pr); bimac<2>(pr + 8, kh + 8, uh, pr); fence_u32<16>(pr);
          CF(14);
          wg_wait<0>(); fence_regs<16>(y);
          bimac<1>(pr + 8, kh, uh + 8, pr + 8); fence_u32<8>(pr + 8);
          du += U_CH / 16; dk = dks - dk;
          va += vi;
        }
        if (!FWD) {
          PMFENCE();
          fin_setup(); get_q(0, OFF_K, B_KF + 8, 0);
#pragma unroll
          for (int r = 0; r < 8; r++) q[2 + (r >> 2)][r & 3] = make_uint2(0, 0);
          wg_wait<0>(); fence_regs<16>(y);
        }
#pragma unroll
        for (int i = 0; i < 8; i++) yp[i] = pack_bf16(y[2 * i], y[2 * i + 1]);
        fence_u32<8>(yp);
        yq += yi; yi = U_CH;
      };
#pragma unroll 1
      for (uint32_t c8 = 0; c8 < 56; c8 += 8) step(c8, std::true_type());
      step(56, std::false_type());
      store_y();
    }
    fence_proxy_async_smem();
    bar_sync(7, 128);
    if (elect_one()) bulk_send(sb + OFF_U + (4 * rank + w) * U_N8 + 4 * U_CH, sb + OFF_U + (4 * (rank ^ 1) + w) * U_N8 + 6 * U_CH, U_CH + 512, bars + (B_IN + 6) * 8, rank ^ 1);
    __syncwarp();
    asm volatile("bar.arrive 9, 256;" ::: "memory");
  } else {
    asm volatile("setmaxnreg.inc.sync.aligned.u32 %0;" ::"n"(GREG));
    const int t = tid & 127, w = warp & 3, lane = t & 31, g = lane >> 2, c = lane & 3;
    if (wg == 1) {
      wait_until(c_start, COEF_T0);
      const int p = 64 * j + (t & 63) + 8 * (t & 64);
      const float Lr = bf2f(P.lam_re[p]), Li = bf2f(P.lam_im[p]);
      const uint32_t ds = __bfloat16_as_ushort(P.Dskip[128 * j + t]);
      const unsigned epoch = (ld_relaxed(&g_flagH[tc * 32]) >> 3) + 1;
      const float dt = bf2f(__float2bfloat16_rn(expf(bf2f(P.log_dt[p]))));
      const float e = expf(dt * Lr);
      float sn, cs;
      {
        const double z = (double)(dt * Li) * 0.15915494309189535;
        sincospif(2.f * (float)(z - rint(z)), &sn, &cs);
      }
      const float lr = e * cs, li = e * sn;
      const float nr = lr - 1.0f, ni = li;
      const bool big = fabsf(Lr) >= fabsf(Li);
      const float la = big ? Lr : Li, lb = big ? Li : Lr, r = __fdiv_rn(lb, la), inv = __frcp_rn(fmaf(lb, r, la));
      const float br = (big ? fmaf(ni, r, nr) : fmaf(nr, r, ni)) * inv, bi = (big ? fmaf(-nr, r, ni) : fmaf(ni, r, -nr)) * inv;
      sts128(sb + OFF_COEF + t * 16, make_uint4(__float_as_uint(lr), __float_as_uint(li), pack_bf16(2.f * br, 2.f * br), pack_bf16(-2.f * bi, -2.f * bi)));
      sts32(sb + OFF_DS + 4 * t, ds << 16);
      if (t == 0) sts32(bars + B_EPOCH * 8, epoch);
    }
    CLUSTER_WAIT();
    if (wg == 1) mbar_arrive(bars + B_COEF * 8);
    float d[128];
    uint32_t so = 0, ph = 0, po = 0;
    uint32_t ra;
    auto set_ra = [&]() { asm volatile("mapa.shared::cluster.u32 %0, %1, %2;" : "=r"(ra) : "r"(bars + B_EMPTY * 8), "r"((t & 1) ? rank ^ 1 : rank)); };
    set_ra();
    auto release = [&](uint32_t off) { if (t < 2) asm volatile("mbarrier.arrive.shared::cluster.b64 _, [%0];" ::"r"(ra + off) : "memory"); };
    constexpr uint32_t NOBAR = 8 * (B_NONE - B_EMPTY);
    auto block = [&](auto ta, uint64_t da0, uint64_t db0, bool zero, int nn) {
      constexpr int PH = decltype(ta)::value, TA = PH > 0, KS = TA ? 128 : 2, QD = PH == 0 ? QD1 : PH == 1 ? QD2 : QD3;
      mbar_wait(bars + B_FULL * 8 + so, ph);
      const uint64_t da = da0 + (so << 8), db = db0 + (so << 8);
      wg_fence();
      wgmma_n128<TA>(d, da, db, !zero);
      wgmma_n128<TA>(d + 64, da + 512, db, !zero);
      wg_commit();
      wg_wait<1>();
      release(po);
#pragma unroll
      for (int k = 1; k < 4; k++) {
        if (QD == 2 || (QD == 4 && k == 2)) wg_fence();
        wgmma_n128<TA>(d, da + KS * k, db + 2 * k, 1);
        wgmma_n128<TA>(d + 64, da + 512 + KS * k, db + 2 * k, 1);
        if (QD == 2 || (QD == 4 && k == 1)) wg_commit();
        if ((QD == 2 && k < 3) || (QD == 4 && k == 1)) wg_wait<1>();
      }
      if (QD != 2) wg_commit();
      po = so;
      so += 8;
      if (so == 8 * STAGES) { so = 0; ph ^= 1; }
    };
    {
      so = wg ? 8 * (16 % STAGES) : 0; ph = wg ? (16 / STAGES) & 1 : 0; po = NOBAR;
      const uint64_t da0 = make_desc(sb + OFF_RING, 16, 1024, 1), db0 = make_desc(sb + OFF_RING + 16384, 16, 1024, 1);
      if (wg == 1) bar_sync(1, 256);
#pragma unroll 1
      for (int kb = 0; kb < 16; kb++) {
        block(std::integral_constant<int, 0>(), da0, db0, kb == 0, 16 * wg + kb);
      }
      asm volatile("bar.arrive %0, 256;" ::"r"(1 + wg) : "memory");
    }
    mbar_wait(bars + B_COEF * 8, 0);
    const uint32_t ca = sb + OFF_COEF + (64 * wg + 8 * w + g) * 16;
    const uint32_t tag = __shfl_sync(0xffffffffu, lds32(bars + B_EPOCH * 8) & 3, 0);
    constexpr int RE = SWAPB ? 2 : 0, IM = 2 - RE;
    const int ct = lane >> 3;
    const uint2* cp = g_carry + __shfl_sync(0xffffffffu, ((16 * wg + 2 * j) * 16 + tc - 1 - ct) * 32 + 8 * w + (lane & 7), lane);
    const uint2* sp = g_carry + __shfl_sync(0xffffffffu, ((16 * wg + 2 * j) * 16 + tc) * 32 + 8 * w + g, lane);
    unsigned long long cv[4];
    const int nv = tc - ct;
    auto load_carry = [&](int i) {
#pragma unroll
      for (int m = 0; m < 4; m++)
        asm volatile("{\n.reg .pred p;\nsetp.gt.s32 p, %2, %3;\n@p ld.relaxed.gpu.global.b64 %0, [%1];\n}\n" : "+l"(cv[m]) : "l"(cp + 512 * i - 128 * m), "r"(nv), "r"(4 * m) : "memory");
    };
    float lr[2], li[2], pr[2], pi[2], wr[2], wi[2], vr[2], vi[2], qr[2], qi[2], gr[2], gi[2];
#pragma unroll
    for (int i = 0; i < 2; i++) {
      const uint2 cf = lds64(ca + 512 * i);
      pr[i] = lr[i] = __uint_as_float(cf.x); pi[i] = li[i] = __uint_as_float(cf.y);
#pragma unroll
      for (int s = 0; s < 4; s++) csq(pr[i], pi[i]);
      gr[i] = pr[i]; gi[i] = pi[i];
      csq(pr[i], pi[i]);
      asm volatile("" : "+f"(pr[i]), "+f"(pi[i]));
    }
    PMFENCE();
    wg_wait<0>();
    fence_regs<128>(d);
    release(po);
#pragma unroll
    for (int i = 0; i < 2; i++) {
      float* e = d + 64 * i;
      auto chain = [&](int s0, int s1, float& sr, float& si) {
        sr = e[2 * s0 + RE]; si = e[2 * s0 + IM];
#pragma unroll
        for (int s = s0 + 1; s < s1; s++) {
          const int ia = 4 * (s >> 1) + (s & 1);
          const float nr = fmaf(-li[i], si, fmaf(lr[i], sr, e[ia + RE])), ni = fmaf(li[i], sr, fmaf(lr[i], si, e[ia + IM]));
          sr = nr; si = ni;
        }
      };
      float sr, si;
      if (i == 1) { cv[0] = cv[1] = cv[2] = cv[3] = tag; asm volatile("" : "+l"(cv[0]), "+l"(cv[1]), "+l"(cv[2]), "+l"(cv[3])); }
      if ((GREEDY >> i) & 1) {
        float ar, ai;
        chain(0, 16, ar, ai); chain(16, 32, sr, si);
        sr = fmaf(gr[i], ar, fmaf(-gi[i], ai, sr)); si = fmaf(gr[i], ai, fmaf(gi[i], ar, si));
      } else chain(0, 32, sr, si);
      if (i == 1) { asm volatile("pmevent 0;" : "+f"(sr), "+f"(si)::"memory"); load_carry(0); PMFENCE(); }
      float ur[3], ui[3], er = 0.f, ei = 0.f;
#pragma unroll
      for (int m = 0; m < 3; m++) { ur[m] = __shfl_up_sync(0xffffffffu, sr, m + 1, 4); ui[m] = __shfl_up_sync(0xffffffffu, si, m + 1, 4); }
      if (c == 3) { er = ur[2]; ei = ui[2]; }
#pragma unroll
      for (int m = 1; m >= 0; m--) {
        const float nr = fmaf(pr[i], er, fmaf(-pi[i], ei, ur[m])), ni = fmaf(pr[i], ei, fmaf(pi[i], er, ui[m]));
        if (c > m) { er = nr; ei = ni; }
      }
      sr = fmaf(pr[i], er, fmaf(-pi[i], ei, sr)); si = fmaf(pr[i], ei, fmaf(pi[i], er, si));
      asm volatile("{\n.reg .pred p;\n.reg .b64 v;\nsetp.eq.u32 p, %3, 3;\nmov.b64 v, {%1,%2};\n@p st.relaxed.gpu.global.b64 [%0], v;\n}\n"
                   ::"l"(sp + 512 * i), "r"((__float_as_uint(sr) & ~3u) | tag), "r"(__float_as_uint(si)), "r"(c) : "memory");
      e[RE] = fmaf(lr[i], er, fmaf(-li[i], ei, e[RE])); e[IM] = fmaf(lr[i], ei, fmaf(li[i], er, e[IM]));
      PMFENCE();
      asm volatile("" : "+f"(e[RE]), "+f"(e[IM]));
    }
#pragma unroll
    for (int i = 0; i < 2; i++) {
      qr[i] = pr[i]; qi[i] = pi[i];
      csq(qr[i], qi[i]);
      wr[i] = (c & 1) ? pr[i] : 1.f; wi[i] = (c & 1) ? pi[i] : 0.f;
      if (c & 2) { float x, y; cmul(wr[i], wi[i], qr[i], qi[i], x, y); wr[i] = x; wi[i] = y; }
      vr[i] = wr[i]; vi[i] = wi[i];
      csq(vr[i], vi[i]); csq(vr[i], vi[i]);
      csq(qr[i], qi[i]); csq(qr[i], qi[i]); csq(qr[i], qi[i]);
      const int src = 4 * (lane & 7) + ct;
      vr[i] = __shfl_sync(0xffffffffu, vr[i], src); vi[i] = __shfl_sync(0xffffffffu, vi[i], src);
      qr[i] = __shfl_sync(0xffffffffu, qr[i], src); qi[i] = __shfl_sync(0xffffffffu, qi[i], src);
    }
    uint4* hp = g_h + (32 * tc + 16 * wg + 2 * j) * 1024 + 64 * w + 4 * g + (c ^ (g >> 1));
    float sr[2], si[2];
    uint32_t gp[2], gm[2];
    auto carry_in = [&](int i) {
      auto ready = [&]() { return __all_sync(0xffffffffu, ((((uint32_t)cv[0] ^ tag) | ((uint32_t)cv[1] ^ tag) | ((uint32_t)cv[2] ^ tag) | ((uint32_t)cv[3] ^ tag)) & 3) == 0); };
      if (!ready()) {
        int n = 0;
#pragma unroll 1
        do load_carry(i); while (!ready() && ++n <= (SPIN_LIMIT << 4));
      }
      float hr = __uint_as_float((uint32_t)cv[3] & ~3u), hi = __uint_as_float((uint32_t)(cv[3] >> 32));
#pragma unroll
      for (int m = 2; m >= 0; m--) {
        const float nr = fmaf(qr[i], hr, fmaf(-qi[i], hi, __uint_as_float((uint32_t)cv[m] & ~3u))), ni = fmaf(qr[i], hi, fmaf(qi[i], hr, __uint_as_float((uint32_t)(cv[m] >> 32))));
        hr = nr; hi = ni;
      }
      { float x, y; cmul(hr, hi, vr[i], vi[i], x, y); hr = x; hi = y; }
      const uint4 cf = lds128(ca + 512 * i);
      lr[i] = __uint_as_float(cf.x); li[i] = __uint_as_float(cf.y); gp[i] = cf.z; gm[i] = cf.w;
      hr += __shfl_xor_sync(0xffffffffu, hr, 8); hi += __shfl_xor_sync(0xffffffffu, hi, 8);
      hr = __shfl_sync(0xffffffffu, hr, g) + __shfl_sync(0xffffffffu, hr, g + 16); hi = __shfl_sync(0xffffffffu, hi, g) + __shfl_sync(0xffffffffu, hi, g + 16);
      cmul(wr[i], wi[i], hr, hi, sr[i], si[i]);
    };
    PMFENCE();
    carry_in(0);
#pragma unroll
    for (int u = 0; u < 8; u++) {
      const int i = u >> 2, i8 = u & 3;
      float* e = d + 64 * i;
      asm volatile("pmevent 0;" : "+f"(sr[i]), "+f"(si[i])::"memory");
      if (u == 1) load_carry(1);
      if (u == 3) carry_in(1);
#pragma unroll
      for (int s = 8 * i8; s < 8 * i8 + 8; s++) {
        const int ia = 4 * (s >> 1) + (s & 1);
        const float nr = fmaf(-li[i], si[i], fmaf(lr[i], sr[i], e[ia + RE])), ni = fmaf(li[i], sr[i], fmaf(lr[i], si[i], e[ia + IM]));
        sr[i] = nr; si[i] = ni;
        e[ia + RE] = nr; e[ia + IM] = ni;
      }
      uint32_t hq[8];
#pragma unroll
      for (int m = 0; m < 4; m++) {
        const float* f = e + 16 * i8 + 4 * m;
        const uint32_t x = pack_bf16(f[RE], f[RE + 1]), y = pack_bf16(f[IM], f[IM + 1]);
        hq[m] = bfma2(gp[i], x, bmul2(gm[i], y)); hq[4 + m] = bfnma2(gp[i], y, bmul2(gm[i], x));
      }
      uint4* o = hp + 512 * (i8 >> 1) + 256 * i + 32 * (i8 & 1);
      stg128(o, make_uint4(hq[0], hq[1], hq[2], hq[3]));
      stg128(o + 1024, make_uint4(hq[4], hq[5], hq[6], hq[7]));
#pragma unroll
      for (int m = 0; m < 8; m++) d[16 * u + m] = __uint_as_float(hq[m]);
      fence_regs<8>(d + 16 * u);
    }
    const int trow = 128 * tc + 64 * (w & 1) + 8 * (w >> 1) + g;
    const int dcol = 128 * j + 4 * c;
    asm volatile("bar.arrive %0, 160;" ::"r"(4 + wg) : "memory");
    if (wg == 0) {
      set_ra();
      {
        const uint32_t dt = sb + OFF_Q + 4096;
        mbar_wait(bars + (B_UF + 3) * 8, 0);
        const int n = t & 15, k = 2 * (n & 6) + 2 * (n >> 3) + (n & 1);
        const uint32_t dv = lds32(sb + OFF_DS + (t & ~15) * 4 + 4 * k) >> (16 - 16 * (k & 1));
#pragma unroll
        for (int u = 0; u < 2; u++) {
          const int m = (k >> 1) - 4 * u;
          sts128(dt + (t >> 4) * 512 + u * 256 + n * 16, make_uint4(m == 0 ? dv : 0, m == 1 ? dv : 0, m == 2 ? dv : 0, m == 3 ? dv : 0));
        }
        fence_proxy_async_smem();
        bar_sync(2, 256);
        mbar_wait(bars + (B_FULL + XPOS % STAGES) * 8, (XPOS / STAGES) & 1);
        const uint64_t dx = make_desc(sb + OFF_RING + (XPOS % STAGES) * STAGE_BYTES, 16, 1024, 1), dd = make_desc(dt, 256, 128, 0);
        wg_fence();
#pragma unroll
        for (int u = 0; u < 16; u++) {
          const uint64_t da = dx + ((u >> 2) & 1) * 1024 + (u >> 3) * 512 + (u & 3) * 2, db = dd + (u & 7) * 32;
          if (u & 1) ss_n16(d + 8 * u, da, db); else ss_n16_in(d + 8 * u, da, db, P.zero);
        }
        wg_commit();
        wg_wait<0>();
        rename_regs<128>(d);
        release(8 * (XPOS % STAGES));
        if (t == 0) mbar_arrive(bars + B_XI * 8);
      }
      so = 8 * (33 % STAGES); ph = (33 / STAGES) & 1; po = NOBAR;
      const uint64_t da0 = make_desc(sb + OFF_RING + 16384, 512, 1024, 2), db0 = make_desc(sb + OFF_RING, 16, 1024, 1);
#pragma unroll 1
      for (int kb = 0; kb < QSW; kb++) block(std::integral_constant<int, 1>(), da0, db0, false, 32 + kb);
#pragma unroll 1
      for (int kb = QSW; kb < 32 - TAILB; kb++) block(std::integral_constant<int, 2>(), da0, db0, false, 32 + kb);
      float* op = P.out + (size_t)trow * 2048 + 1024 + dcol;
      auto mma = [&](int i, int kb, int k0, int k1) {
        const int s = (33 + kb) % STAGES;
        wg_fence();
#pragma unroll
        for (int k = k0; k < k1; k++) wgmma_n128<1>(d + 64 * i, da0 + s * 2048 + 512 * i + 128 * k, db0 + (i ? 0 : P.zero) + s * 2048 + 2 * k, 1);
        wg_commit();
      };
      auto store = [&](int i, int J0, int J1) {
#pragma unroll
        for (int J = J0; J < J1; J++) {
#pragma unroll
          for (int h = 0; h < 2; h++) {
            const float* e = d + 64 * i + 8 * J + 2 * h;
            stg128(op + (size_t)(16 * i + 32 * h) * 2048 + 16 * J, make_uint4(__float_as_uint(e[0]), __float_as_uint(e[1]), __float_as_uint(e[4]), __float_as_uint(e[5])));
          }
        }
        PMFENCE();
      };
      constexpr int K0 = 32 - TAILB;
#pragma unroll
      for (int kb = K0; kb < 32; kb++) {
        mbar_wait(bars + (B_FULL + (33 + kb) % STAGES) * 8, ((33 + kb) / STAGES) & 1);
        if (TAILB == 5 && kb == K0) { mma(0, kb, 0, 2); wg_wait<1>(); release(po); mma(0, kb, 2, 4); }
        else mma(0, kb, 0, 4);
      }
      mma(1, K0, 0, 4);
      wg_wait<1>();
      fence_regs<64>(d);
#pragma unroll
      for (int kb = K0 + 1; kb < 32; kb++) {
        mma(1, kb, 0, 4);
        store(0, T_ST * (kb - K0 - 1), kb == 31 ? 8 : T_ST * (kb - K0));
      }
      wg_wait<0>();
      fence_regs<64>(d + 64);
      store(1, 0, 8);
      return;
    }
    asm volatile("setmaxnreg.dec.sync.aligned.u32 %0;" ::"n"(488 - 2 * GREG));
    fin_setup();
#pragma unroll
    for (int n = 0; n < 4; n += 2) {
      get_q(n, OFF_Q, B_QF, n >> 1);
      uint32_t dep = P.zero;
#pragma unroll
      for (int r = 0; r < 8; r++) dep &= q[n + (r >> 2)][r & 3].x;
      bar_sync(6 + dep, 128);
      if (w < 2 && elect_one()) load_q(5 + 2 * w - (n >> 1), OFF_Q, B_QF + n);
      __syncwarp();
    }
#pragma unroll 1
    for (int r = 0; r < 6; r++) mbar_wait(bars + (B_IN + r) * 8, 0);
    bar_sync(9, 256);
  }
  {
    const int w = warp & 3, h = wg & 1, lane = fl;
    const uint32_t ob0 = sb + (h ? OFF_F1 : OFF_K) + 1024 * w, ob1 = sb + (h ? OFF_VP : OFF_K + 4096) + 1024 * w;
    uint32_t y[2][8];
    auto get_y = [&](int n) { ldsm4t(y[n & 1], fa + n * fs); ldsm4t(y[n & 1] + 4, fa + n * fs + 32); };
    mbar_wait(bars + (B_HR + 1) * 8, 0);
    mbar_wait(bars + (B_IN + 6) * 8, 0);
    get_y(0);
#pragma unroll
    for (int n = 0; n < 4; n++) {
      uint32_t* o = y[n & 1];
#pragma unroll
      for (int r = 0; r < 4; r++) { o[2 * r] = bmul2(o[2 * r], q[n][r].x); o[2 * r + 1] = bmul2(o[2 * r + 1], q[n][r].y); }
      if (n > 0 && lane == 0) asm volatile("cp.async.bulk.wait_group.read 0;" ::: "memory");
      __syncwarp();
#pragma unroll
      for (int r = 0; r < 4; r++)
        sts128((r & 2 ? ob1 : ob0) + (r & 1) * 512 + lane * 16, make_uint4(o[2 * r] << 16, o[2 * r] & 0xffff0000u, o[2 * r + 1] << 16, o[2 * r + 1] & 0xffff0000u));
      fence_proxy_async_smem();
      __syncwarp();
      if (lane == 0) {
#pragma unroll
        for (int u = 0; u < 2; u++)
          asm volatile("cp.async.bulk.tensor.3d.global.shared::cta.bulk_group [%0, {%2, %3, %4}], [%1];"
                       ::"l"(&mO), "r"(u ? ob1 : ob0), "r"(32 * slot), "r"(32 * rank + 8 * w), "r"(8 * n + 4 * h + 2 * u) : "memory");
        asm volatile("cp.async.bulk.commit_group;" ::: "memory");
      }
      __syncwarp();
      if (n < 3) get_y(n + 1);
      if (n == 1 && !h) get_q(2, OFF_Q, B_QF + 2, 0);
    }
    if (warp == 8 && lane == 0) mbar_arrive_cta(bars + B_ACK * 8, rank ^ 1);
    if (lane == 0) asm volatile("cp.async.bulk.wait_group 0;" ::: "memory");
    mbar_wait(bars + B_ACK * 8, 0);
  }
}

typedef CUresult (*EncodeFn)(CUtensorMap*, CUtensorMapDataType, cuuint32_t, void*, const cuuint64_t*, const cuuint64_t*, const cuuint32_t*,
                             const cuuint32_t*, CUtensorMapInterleave, CUtensorMapSwizzle, CUtensorMapL2promotion, CUtensorMapFloatOOBfill);

bool encode(EncodeFn fn, CUtensorMap* m, int rank, const void* base, const cuuint64_t* dims, const cuuint64_t* strides, const cuuint32_t* box, CUtensorMapSwizzle swz,
            CUtensorMapL2promotion promo = CU_TENSOR_MAP_L2_PROMOTION_L2_128B) {
  const cuuint32_t es[5] = {1, 1, 1, 1, 1};
  return fn(m, CU_TENSOR_MAP_DATA_TYPE_BFLOAT16, rank, const_cast<void*>(base), dims, strides, box, es, CU_TENSOR_MAP_INTERLEAVE_NONE, swz,
            promo, CU_TENSOR_MAP_FLOAT_OOB_FILL_NONE) == CUDA_SUCCESS;
}

}

extern "C" void kernel_launch(void* const* d_in, const int* in_sizes, int n_in, void* d_out, int out_size) {
  (void)in_sizes; (void)n_in; (void)out_size;
  typedef const __nv_bfloat16* In;
  const In q = (In)d_in[0], k = (In)d_in[1], v = (In)d_in[2], ssm_k = (In)d_in[4], x = (In)d_in[6], B_re = (In)d_in[9], B_im = (In)d_in[10], C_re = (In)d_in[11], C_im = (In)d_in[12];
  Params P = {};
  P.shift_k = (In)d_in[3]; P.ssm_D = (In)d_in[5]; P.lam_re = (In)d_in[7]; P.lam_im = (In)d_in[8]; P.log_dt = (In)d_in[13]; P.Dskip = (In)d_in[14];
  P.out = (float*)d_out;
  for (int cl = 0; cl < 64; cl++) P.slot[cl >> 2] |= (cl < 4 ? 4 + cl : cl < 36 ? 8 * ((cl - 4) & 7) + ((cl - 4) >> 3) : 8 * (1 + (cl - 36) % 7) + 4 + (cl - 36) / 7) << (8 * (cl & 3));
  const bool swapB = (uintptr_t)B_im < (uintptr_t)B_re;

  EncodeFn fn = nullptr;
  cudaDriverEntryPointQueryResult qr;
  cudaGetDriverEntryPoint("cuTensorMapEncodeTiled", (void**)&fn, cudaEnableDefault, &qr);
  if (!fn) return;

  CUtensorMap mX, mB, mCre, mCim, mXs, mK, mV, mQ, mS, mO;
  bool ok = true;
  {
    const cuuint64_t dims[4] = {1024, 2, 64, 16}, str[3] = {2048, 32 * 2048, 2 * 2048};
    const cuuint32_t box[4] = {64, 2, 4, 16};
    ok &= encode(fn, &mX, 4, x, dims, str, box, CU_TENSOR_MAP_SWIZZLE_128B);
  }
  {
    const uintptr_t lo = swapB ? (uintptr_t)B_im : (uintptr_t)B_re, hi = swapB ? (uintptr_t)B_re : (uintptr_t)B_im;
    const cuuint64_t dims[4] = {1024, 8, 2, 128}, str[3] = {2048, (cuuint64_t)(hi - lo), 8 * 2048};
    const cuuint32_t box[4] = {64, 8, 2, 4};
    ok &= encode(fn, &mB, 4, (const void*)lo, dims, str, box, CU_TENSOR_MAP_SWIZZLE_128B);
  }
  {
    const cuuint64_t dims[5] = {1024, 2, 4, 2, 64}, str[4] = {2048, 4 * 2048, 2 * 2048, 16 * 2048};
    const cuuint32_t box[5] = {64, 2, 4, 2, 4};
    ok &= encode(fn, &mCre, 5, C_re, dims, str, box, CU_TENSOR_MAP_SWIZZLE_128B);
    ok &= encode(fn, &mCim, 5, C_im, dims, str, box, CU_TENSOR_MAP_SWIZZLE_128B);
  }
  {
    const cuuint64_t dims[4] = {1024, 8, 64, 4}, str[3] = {2048, 32 * 2048, 8 * 2048};
    const cuuint32_t box[4] = {64, 8, 4, 4};
    ok &= encode(fn, &mXs, 4, x, dims, str, box, CU_TENSOR_MAP_SWIZZLE_128B);
  }
  {
    const cuuint64_t dims[3] = {1024, 64, 32}, str[2] = {32 * 2048, 2048};
    const cuuint32_t box[3] = {16, 32, 4};
    const cuuint64_t dimq[4] = {1024, 8, 32, 8}, strq[3] = {32 * 2048, 2048, 256 * 2048};
    const cuuint32_t boxq[4] = {16, 8, 4, 4};
    ok &= encode(fn, &mQ, 4, q, dimq, strq, boxq, CU_TENSOR_MAP_SWIZZLE_NONE);
    ok &= encode(fn, &mK, 3, k, dims, str, box, CU_TENSOR_MAP_SWIZZLE_32B);
    ok &= encode(fn, &mV, 3, v, dims, str, box, CU_TENSOR_MAP_SWIZZLE_32B);
  }
  {
    const cuuint64_t dims[2] = {32, 65536}, str[1] = {64};
    const cuuint32_t box[2] = {32, 64};
    ok &= encode(fn, &mS, 2, ssm_k, dims, str, box, CU_TENSOR_MAP_SWIZZLE_64B);
  }
  {
    const cuuint64_t dims[3] = {2048, 64, 32}, str[2] = {32 * 8192, 8192};
    const cuuint32_t box[3] = {32, 8, 2};
    ok &= encode(fn, &mO, 3, d_out, dims, str, box, CU_TENSOR_MAP_SWIZZLE_NONE);
  }
  if (!ok) return;
  auto kern = swapB ? fused_kernel<1> : fused_kernel<0>;
  cudaFuncSetAttribute(kern, cudaFuncAttributeMaxDynamicSharedMemorySize, SMEM_BYTES);
  kern<<<NCTA, 512, SMEM_BYTES, cudaStreamPerThread>>>(P, mX, mB, mCre, mCim, mXs, mK, mV, mQ, mS, mO);
}
```

```cpp
#include <cuda_runtime.h>
#include <cuda_bf16.h>
#include <cuda.h>
#include <stdint.h>
#include <type_traits>

namespace {

constexpr int NCTA = 128;

constexpr int STAGES = 5, STAGE_BYTES = 32768;
constexpr int OFF_RING = 0;
constexpr int OFF_F1 = STAGES * STAGE_BYTES, OFF_F2 = OFF_F1 + 4096, OFF_K = OFF_F2 + 2048, OFF_VP = OFF_K + 8192, OFF_Q = OFF_VP + 4096, OFF_IN = OFF_Q + 8192;
constexpr int OFF_KV = OFF_K;
constexpr int U_CH = 528, U_N8 = 8 * U_CH, OFF_U = OFF_IN + U_N8;
constexpr int OFF_COEF = OFF_U + 8 * U_N8;
constexpr int OFF_DS = OFF_COEF + 2048, OFF_D = OFF_DS + 512;
constexpr int OFF_BAR = OFF_D + 64;
constexpr int SMEM_BYTES = OFF_BAR + 512;
static_assert(SMEM_BYTES <= 232448 && OFF_K % 1024 == 0 && (OFF_U + 3 * U_N8) % 512 == 0 && (4 * U_N8) % 512 == 0, "smem map");
constexpr int B_FULL = 0, B_XI = 5, B_HR = 6, B_HP = 8, B_KVF = 10, B_QF = 13, B_IN = 17, B_UF = 25, B_ACK = 29, B_KF = 30, B_ST = 40,
              B_EMPTY = 47, B_COEF = 52, B_KVE = 53, B_NONE = 56, B_EPOCH = 57;

constexpr int QD1 = 0x02;
constexpr int QD2 = 0x2a;
constexpr int QD3 = 0x02;
constexpr int QSW = 16;
constexpr int HEAD = 3;
constexpr int ST_T0 = 200;
constexpr int ST_DELAY = 300;
constexpr int XPOS = 32;
constexpr int K_T0 = 800;
constexpr int KV_T0 = 1500;
constexpr int KV_DT = 620;
constexpr int KV_DV = 450;
constexpr int POLL_NS = 30;
constexpr int GREEDY = 1;
constexpr int TAILB = 5;
constexpr int GREG = 168;
constexpr int COEF_T0 = 2500;
constexpr int T_ST = 2;
constexpr int PFC_T0 = 12500;
constexpr int PFC_T1 = 1500;
constexpr int PFC_DT = 250;
constexpr int KV_E = 6;
constexpr int KV_D2 = 300;
constexpr int CFM = 0x40f1;
constexpr int SPIN_LIMIT = 1 << 14;

struct Params {
  unsigned slot[16];
  unsigned zero;
  const __nv_bfloat16 *shift_k, *ssm_D, *lam_re, *lam_im, *log_dt, *Dskip;
  float* out;
};

__device__ __align__(1024) uint4 g_h[16 * 32 * 1024];
__device__ __align__(128) uint2 g_carry[32 * 16 * 32];
__device__ __align__(128) unsigned g_flagH[16 * 32];

__device__ __forceinline__ uint64_t make_desc(uint32_t addr, uint32_t lbo, uint32_t sbo, uint32_t swz) {
  return (uint64_t)((addr & 0x3FFFF) >> 4) | ((uint64_t)(lbo >> 4) << 16) | ((uint64_t)(sbo >> 4) << 32) | ((uint64_t)swz << 62);
}
__device__ __forceinline__ void wg_fence() { asm volatile("wgmma.fence.sync.aligned;" ::: "memory"); }
__device__ __forceinline__ void wg_commit() { asm volatile("wgmma.commit_group.sync.aligned;" ::: "memory"); }
template <int N> __device__ __forceinline__ void wg_wait() { asm volatile("wgmma.wait_group.sync.aligned %0;" ::"n"(N) : "memory"); }
__device__ __forceinline__ void mbar_init(uint32_t bar, int cnt) { asm volatile("mbarrier.init.shared::cta.b64 [%0], %1;" ::"r"(bar), "r"(cnt) : "memory"); }
__device__ __forceinline__ void mbar_expect(uint32_t bar, uint32_t bytes) { asm volatile("mbarrier.arrive.expect_tx.shared::cta.b64 _, [%0], %1;" ::"r"(bar), "r"(bytes) : "memory"); }
__device__ __forceinline__ bool mbar_try(uint32_t bar, uint32_t parity) {
  uint32_t ok;
  asm volatile("{\n.reg .pred p;\nmbarrier.try_wait.parity.shared::cta.b64 p, [%1], %2;\nselp.u32 %0, 1, 0, p;\n}\n" : "=r"(ok) : "r"(bar), "r"(parity) : "memory");
  return ok;
}
__device__ __forceinline__ void mbar_wait(uint32_t bar, uint32_t parity) {
  if (__builtin_expect(!mbar_try(bar, parity), 0)) {
#pragma unroll 1
    for (int n = 0; n < SPIN_LIMIT && !mbar_try(bar, parity); n++) {}
  }
}
__device__ __forceinline__ void mbar_arrive(uint32_t bar) { asm volatile("mbarrier.arrive.shared::cta.b64 _, [%0];" ::"r"(bar) : "memory"); }
__device__ __forceinline__ void mbar_arrive_cta(uint32_t bar, uint32_t cta) {
  asm volatile("{\n.reg .b32 ra;\nmapa.shared::cluster.u32 ra, %0, %1;\nmbarrier.arrive.shared::cluster.b64 _, [ra];\n}\n" ::"r"(bar), "r"(cta) : "memory");
}
__device__ __forceinline__ bool elect_one() {
  uint32_t p;
  asm volatile("{\n.reg .pred P;\nelect.sync _|P, 0xffffffff;\nselp.u32 %0, 1, 0, P;\n}\n" : "=r"(p));
  return p != 0;
}
__device__ __forceinline__ void bar_sync(int id, int n) { asm volatile("bar.sync %0, %1;" ::"r"(id), "r"(n) : "memory"); }
#define TMA_LD(dim) "cp.async.bulk.tensor." dim ".shared::cluster.global.mbarrier::complete_tx::bytes"
__device__ __forceinline__ void tma2d(uint32_t dst, const CUtensorMap* m, int c0, int c1, uint32_t bar) {
  asm volatile(TMA_LD("2d") " [%0], [%1, {%3, %4}], [%2];" ::"r"(dst), "l"(m), "r"(bar), "r"(c0), "r"(c1) : "memory");
}
__device__ __forceinline__ void tma3d(uint32_t dst, const CUtensorMap* m, int c0, int c1, int c2, uint32_t bar) {
  asm volatile(TMA_LD("3d") " [%0], [%1, {%3, %4, %5}], [%2];" ::"r"(dst), "l"(m), "r"(bar), "r"(c0), "r"(c1), "r"(c2) : "memory");
}
__device__ __forceinline__ void tma4d(uint32_t dst, const CUtensorMap* m, int c0, int c1, int c2, int c3, uint32_t bar) {
  asm volatile(TMA_LD("4d") " [%0], [%1, {%3, %4, %5, %6}], [%2];" ::"r"(dst), "l"(m), "r"(bar), "r"(c0), "r"(c1), "r"(c2), "r"(c3) : "memory");
}
__device__ __forceinline__ void tma4d_mc(uint32_t dst, const CUtensorMap* m, int c0, int c1, int c2, int c3, uint32_t bar) {
  asm volatile(TMA_LD("4d") ".multicast::cluster [%0], [%1, {%3, %4, %5, %6}], [%2], %7;" ::"r"(dst), "l"(m), "r"(bar), "r"(c0), "r"(c1), "r"(c2), "r"(c3), "h"((uint16_t)3) : "memory");
}
__device__ __forceinline__ void tma5d_mc(uint32_t dst, const CUtensorMap* m, int c0, int c1, int c2, int c3, int c4, uint32_t bar) {
  asm volatile(TMA_LD("5d") ".multicast::cluster [%0], [%1, {%3, %4, %5, %6, %7}], [%2], %8;" ::"r"(dst), "l"(m), "r"(bar), "r"(c0), "r"(c1), "r"(c2), "r"(c3), "r"(c4), "h"((uint16_t)3) : "memory");
}
__device__ __forceinline__ void bulk_load(uint32_t dst, const void* src, uint32_t bytes, uint32_t bar) {
  asm volatile("cp.async.bulk.shared::cluster.global.mbarrier::complete_tx::bytes [%0], [%1], %2, [%3];" ::"r"(dst), "l"(src), "r"(bytes), "r"(bar) : "memory");
}
__device__ __forceinline__ void bulk_send(uint32_t dst, uint32_t src, uint32_t bytes, uint32_t bar, uint32_t cta) {
  asm volatile("{\n.reg .b32 rd, rb;\nmapa.shared::cluster.u32 rd, %0, %3;\nmapa.shared::cluster.u32 rb, %2, %3;\n"
               "cp.async.bulk.shared::cluster.shared::cta.mbarrier::complete_tx::bytes [rd], [%1], %4, [rb];\n}\n"
               ::"r"(dst), "r"(src), "r"(bar), "r"(cta), "r"(bytes) : "memory");
}
__device__ __forceinline__ void fence_proxy_async_smem() { asm volatile("fence.proxy.async.shared::cta;" ::: "memory"); }
__device__ __forceinline__ void fence_proxy_async_global() { asm volatile("fence.proxy.async.global;" ::: "memory"); }
__device__ __forceinline__ uint32_t clk32() { uint32_t c; asm volatile("mov.u32 %0, %%clock;" : "=r"(c)::"memory"); return c; }
__device__ __forceinline__ void wait_until(uint32_t t0, uint32_t dt) { while (clk32() - t0 < dt) __nanosleep(32); }
__device__ __forceinline__ void spin_until(uint32_t t0, uint32_t dt) { while (clk32() - t0 < dt) {} }
__device__ __forceinline__ void prefetch_map(const CUtensorMap* m) { asm volatile("prefetch.tensormap [%0];" ::"l"(m) : "memory"); }
__device__ __forceinline__ unsigned ld_acquire(const unsigned* p) { unsigned v; asm volatile("ld.acquire.gpu.global.u32 %0, [%1];" : "=r"(v) : "l"(p) : "memory"); return v; }
__device__ __forceinline__ unsigned ld_relaxed(const unsigned* p) { unsigned v; asm volatile("ld.relaxed.gpu.global.u32 %0, [%1];" : "=r"(v) : "l"(p) : "memory"); return v; }
__device__ __forceinline__ uint32_t lds32(uint32_t a) { uint32_t v; asm volatile("ld.shared.u32 %0, [%1];" : "=r"(v) : "r"(a)); return v; }
__device__ __forceinline__ uint2 lds64(uint32_t a) { uint2 v; asm volatile("ld.shared.v2.u32 {%0,%1}, [%2];" : "=r"(v.x), "=r"(v.y) : "r"(a) : "memory"); return v; }
__device__ __forceinline__ uint4 lds128(uint32_t a) { uint4 v; asm volatile("ld.shared.v4.u32 {%0,%1,%2,%3}, [%4];" : "=r"(v.x), "=r"(v.y), "=r"(v.z), "=r"(v.w) : "r"(a) : "memory"); return v; }
__device__ __forceinline__ void sts32(uint32_t a, uint32_t v) { asm volatile("st.shared.u32 [%0], %1;" ::"r"(a), "r"(v) : "memory"); }
__device__ __forceinline__ void sts128(uint32_t a, uint4 v) { asm volatile("st.shared.v4.u32 [%0], {%1,%2,%3,%4};" ::"r"(a), "r"(v.x), "r"(v.y), "r"(v.z), "r"(v.w) : "memory"); }
__device__ __forceinline__ void ldsm4(uint32_t* r, uint32_t a) { asm volatile("ldmatrix.sync.aligned.m8n8.x4.shared.b16 {%0,%1,%2,%3}, [%4];" : "=r"(r[0]), "=r"(r[1]), "=r"(r[2]), "=r"(r[3]) : "r"(a) : "memory"); }
__device__ __forceinline__ void ldsm4t(uint32_t* r, uint32_t a) { asm volatile("ldmatrix.sync.aligned.m8n8.x4.trans.shared.b16 {%0,%1,%2,%3}, [%4];" : "=r"(r[0]), "=r"(r[1]), "=r"(r[2]), "=r"(r[3]) : "r"(a) : "memory"); }
__device__ __forceinline__ void stsm4t(uint32_t a, uint32_t r0, uint32_t r1, uint32_t r2, uint32_t r3) {
  asm volatile("stmatrix.sync.aligned.m8n8.x4.trans.shared.b16 [%0], {%1,%2,%3,%4};" ::"r"(a), "r"(r0), "r"(r1), "r"(r2), "r"(r3) : "memory");
}
__device__ __forceinline__ uint4 ldg128_nc(const void* p) { uint4 v; asm volatile("ld.global.nc.L1::no_allocate.v4.u32 {%0,%1,%2,%3}, [%4];" : "=r"(v.x), "=r"(v.y), "=r"(v.z), "=r"(v.w) : "l"(p)); return v; }
__device__ __forceinline__ void stg128(void* p, uint4 v) { asm volatile("st.global.L1::no_allocate.v4.u32 [%0], {%1,%2,%3,%4};" ::"l"(p), "r"(v.x), "r"(v.y), "r"(v.z), "r"(v.w) : "memory"); }
__device__ __forceinline__ uint32_t pack_bf16(float lo, float hi) { uint32_t r; asm("cvt.rn.bf16x2.f32 %0, %1, %2;" : "=r"(r) : "f"(hi), "f"(lo)); return r; }
__device__ __forceinline__ uint32_t bmul2(uint32_t a, uint32_t b) { uint32_t r; asm("mul.rn.bf16x2 %0, %1, %2;" : "=r"(r) : "r"(a), "r"(b)); return r; }
__device__ __forceinline__ uint32_t bfma2(uint32_t a, uint32_t b, uint32_t c) { uint32_t r; asm("fma.rn.bf16x2 %0, %1, %2, %3;" : "=r"(r) : "r"(a), "r"(b), "r"(c)); return r; }
__device__ __forceinline__ float bf2f(__nv_bfloat16 v) { return __bfloat162float(v); }

#define R8(d, o) "+f"(d[o]), "+f"(d[o + 1]), "+f"(d[o + 2]), "+f"(d[o + 3]), "+f"(d[o + 4]), "+f"(d[o + 5]), "+f"(d[o + 6]), "+f"(d[o + 7])
#define R16(d, o) R8(d, o), R8(d, o + 8)
#define R64(d, o) R16(d, o), R16(d, o + 16), R16(d, o + 32), R16(d, o + 48)
template <int TA> __device__ __forceinline__ void wgmma_n128(float* d, uint64_t da, uint64_t db, int scale_d) {
  asm volatile("{\n.reg .pred p;\nsetp.ne.b32 p, %66, 0;\n"
    "wgmma.mma_async.sync.aligned.m64n128k16.f32.bf16.bf16 {"
    "%0,%1,%2,%3,%4,%5,%6,%7,%8,%9,%10,%11,%12,%13,%14,%15,%16,%17,%18,%19,%20,%21,%22,%23,%24,%25,%26,%27,%28,%29,%30,%31,"
    "%32,%33,%34,%35,%36,%37,%38,%39,%40,%41,%42,%43,%44,%45,%46,%47,%48,%49,%50,%51,%52,%53,%54,%55,%56,%57,%58,%59,%60,%61,%62,%63"
    "}, %64, %65, p, 1, 1, %67, 0;\n}\n"
    : R64(d, 0)
    : "l"(da), "l"(db), "r"(scale_d), "n"(TA));
}
template <int N> __device__ __forceinline__ void fence_regs(float* d) {
#pragma unroll
  for (int i = 0; i < N; i++) asm volatile("" : "+f"(d[i])::"memory");
}
#define PMFENCE() asm volatile("pmevent 0;" ::: "memory")
__device__ __forceinline__ void cmul(float ar, float ai, float br, float bi, float& cr, float& ci) {
  cr = ar * br - ai * bi; ci = ar * bi + ai * br;
}
__device__ __forceinline__ void csq(float& r, float& i) { const float x = fmaf(r, r, -i * i), y = r * i; r = x; i = y + y; }

#define W8(d, o) "=f"(d[o]), "=f"(d[o + 1]), "=f"(d[o + 2]), "=f"(d[o + 3]), "=f"(d[o + 4]), "=f"(d[o + 5]), "=f"(d[o + 6]), "=f"(d[o + 7])
#define L16 "{%0,%1,%2,%3,%4,%5,%6,%7,%8,%9,%10,%11,%12,%13,%14,%15}"
#define L32 "{%0,%1,%2,%3,%4,%5,%6,%7,%8,%9,%10,%11,%12,%13,%14,%15,%16,%17,%18,%19,%20,%21,%22,%23,%24,%25,%26,%27,%28,%29,%30,%31}"
template <int ACC, int TB> __device__ __forceinline__ void rs_n32(float* d, const uint32_t* a, uint64_t db) {
  if constexpr (ACC) asm volatile("wgmma.mma_async.sync.aligned.m64n32k16.f32.bf16.bf16 " L16 ", {%16,%17,%18,%19}, %20, 1, 1, 1, %21;" : R16(d, 0) : "r"(a[0]), "r"(a[1]), "r"(a[2]), "r"(a[3]), "l"(db), "n"(TB));
  else asm volatile("wgmma.mma_async.sync.aligned.m64n32k16.f32.bf16.bf16 " L16 ", {%16,%17,%18,%19}, %20, 0, 1, 1, %21;" : W8(d, 0), W8(d, 8) : "r"(a[0]), "r"(a[1]), "r"(a[2]), "r"(a[3]), "l"(db), "n"(TB));
}
template <int ACC, int TB> __device__ __forceinline__ void rs_n64(float* d, const uint32_t* a, uint64_t db) {
  if constexpr (ACC) asm volatile("wgmma.mma_async.sync.aligned.m64n64k16.f32.bf16.bf16 " L32 ", {%32,%33,%34,%35}, %36, 1, 1, 1, %37;" : R16(d, 0), R16(d, 16) : "r"(a[0]), "r"(a[1]), "r"(a[2]), "r"(a[3]), "l"(db), "n"(TB));
  else asm volatile("wgmma.mma_async.sync.aligned.m64n64k16.f32.bf16.bf16 " L32 ", {%32,%33,%34,%35}, %36, 0, 1, 1, %37;" : W8(d, 0), W8(d, 8), W8(d, 16), W8(d, 24) : "r"(a[0]), "r"(a[1]), "r"(a[2]), "r"(a[3]), "l"(db), "n"(TB));
}
template <int ACC> __device__ __forceinline__ void ss_n32_tt(float* d, uint64_t da, uint64_t db) {
  if constexpr (ACC) asm volatile("wgmma.mma_async.sync.aligned.m64n32k16.f32.bf16.bf16 " L16 ", %16, %17, 1, 1, 1, 1, 1;" : R16(d, 0) : "l"(da), "l"(db));
  else asm volatile("wgmma.mma_async.sync.aligned.m64n32k16.f32.bf16.bf16 " L16 ", %16, %17, 0, 1, 1, 1, 1;" : W8(d, 0), W8(d, 8) : "l"(da), "l"(db));
}
__device__ __forceinline__ void stsm4(uint32_t a, uint32_t r0, uint32_t r1, uint32_t r2, uint32_t r3) {
  asm volatile("stmatrix.sync.aligned.m8n8.x4.shared.b16 [%0], {%1,%2,%3,%4};" ::"r"(a), "r"(r0), "r"(r1), "r"(r2), "r"(r3) : "memory");
}
template <int N> __device__ __forceinline__ void fence_u32(uint32_t* d) {
#pragma unroll
  for (int i = 0; i < N; i++) asm volatile("" : "+r"(d[i])::"memory");
}
__device__ __forceinline__ void pack32(uint32_t* f, const float* z) {
#pragma unroll
  for (int i = 0; i < 16; i++) f[i] = pack_bf16(z[2 * i], z[2 * i + 1]);
}
template <int INV> __device__ __forceinline__ void twiddle(uint32_t* f, const uint32_t* tp, const uint32_t* ts) {
#pragma unroll
  for (int i = 0; i < 8; i++) {
    uint32_t x = f[2 * i + INV], y = f[2 * i + 1 - INV];
    x = bfma2(tp[i & 3], y, x); y = bfma2(ts[i & 3], x, y); x = bfma2(tp[i & 3], y, x);
    f[2 * i + INV] = x; f[2 * i + 1 - INV] = y;
  }
}
__device__ __forceinline__ uint32_t bfnma2(uint32_t a, uint32_t b, uint32_t c) { uint32_t r; asm("{\n.reg .b32 t;\nmul.bf16x2 t, %1, %2;\nsub.bf16x2 %0, %3, t;\n}" : "=r"(r) : "r"(a), "r"(b), "r"(c)); return r; }
__device__ __forceinline__ uint32_t bfms2(uint32_t a, uint32_t b, uint32_t c) { uint32_t r; asm("{\n.reg .b32 t;\nmul.bf16x2 t, %1, %2;\nsub.bf16x2 %0, t, %3;\n}" : "=r"(r) : "r"(a), "r"(b), "r"(c)); return r; }
template <int ADD> __device__ __forceinline__ void bimac(uint32_t* o, const uint32_t* a, const uint32_t* b, const uint32_t* c) {
#pragma unroll
  for (int J = 0; J < 2; J++) {
    const uint32_t Pr = a[2 * J], Pi = a[2 * J + 1], Qr = a[2 * J + 4], Qi = a[2 * J + 5], pr = b[2 * J], pi = b[2 * J + 1], qr = b[2 * J + 4], qi = b[2 * J + 5];
    uint32_t x0, x1, x2, x3;
    if (ADD == 0) { x0 = bmul2(Pr, pr); x1 = bmul2(Pr, pi); x2 = bmul2(Pr, qr); x3 = bmul2(Pr, qi); }
    if (ADD == 1) { x0 = bfma2(Pr, pr, c[2 * J]); x1 = bfma2(Pr, pi, c[2 * J + 1]); x2 = bfma2(Pr, qr, c[2 * J + 4]); x3 = bfma2(Pr, qi, c[2 * J + 5]); }
    if (ADD == 2) { x0 = bfma2(Pr, pr, c[2 * J + 1]); x1 = bfms2(Pr, pi, c[2 * J]); x2 = bfma2(Pr, qr, c[2 * J + 5]); x3 = bfms2(Pr, qi, c[2 * J + 4]); }
    x0 = bfnma2(Pi, pi, x0); x1 = bfma2(Pi, pr, x1); x2 = bfnma2(Pi, qi, x2); x3 = bfma2(Pi, qr, x3);
    x0 = bfnma2(Qr, qr, x0); x1 = bfnma2(Qr, qi, x1); x2 = bfma2(Qr, pr, x2); x3 = bfma2(Qr, pi, x3);
    x0 = bfma2(Qi, qi, x0); x1 = bfnma2(Qi, qr, x1); x2 = bfnma2(Qi, pi, x2); x3 = bfma2(Qi, pr, x3);
    o[2 * J] = x0; o[2 * J + 1] = x1; o[2 * J + 4] = x2; o[2 * J + 5] = x3;
  }
}
__device__ __forceinline__ void sincos8k(int n, float& s, float& c) {
  const float x = (float)((n << 19) >> 19) * (6.283185307179586f / 8192.f);
  s = __sinf(x); c = __cosf(x);
}
__device__ __forceinline__ void fft_tables(uint32_t f1a, uint32_t f2a, int w, int lane, uint32_t* tp, uint32_t* ts, float& d0r, float& d0i) {
  const int c = lane & 3, f1 = 8 * w + (lane >> 2);
#pragma unroll 1
  for (int J = 3; J >= 0; J--) {
    const int a = 8 * J + 2 * c;
    float s0, c0, s1, c1;
    sincos8k(64 * (4 * f1 + 1) * a + 31 * (4 * f1 - 63), d0i, d0r); sincos8k(64 * (4 * f1 + 1) * (a + 1) + 31 * (4 * f1 - 63), s1, c1);
    d0r *= 0.125f; d0i *= 0.125f;
    sts32(f1a + w * 1024 + J * 128 + lane * 4, pack_bf16(d0r, 0.125f * c1)); sts32(f1a + w * 1024 + 512 + J * 128 + lane * 4, pack_bf16(d0i, 0.125f * s1));
    sincos8k(128 * (2 * (a & 15) + 1) * f1 - 128 * (a & 16), s0, c0); sincos8k(128 * (2 * (a & 15) + 3) * f1 - 128 * (a & 16), s1, c1);
    sts32(f2a + w * 512 + J * 128 + lane * 4, pack_bf16(c0, c1));
    sincos8k((4 * f1 - 63) * (2 * a - 31), s0, c0); sincos8k((4 * f1 - 63) * (2 * a - 29), s1, c1);
#pragma unroll
    for (int i = 3; i > 0; i--) { ts[i] = ts[i - 1]; tp[i] = tp[i - 1]; }
    ts[0] = pack_bf16(s0, s1); tp[0] = pack_bf16(-__fdividef(s0, 1.f + c0), -__fdividef(s1, 1.f + c1));
  }
  if (c != 0) d0r = d0i = 0.f;
}

__device__ __forceinline__ void ss_n16_in(float* d, uint64_t da, uint64_t db, uint32_t zero) {
  asm volatile("{\n.reg .pred p;\nsetp.ne.b32 p, %10, 0;\nwgmma.mma_async.sync.aligned.m64n16k16.f32.bf16.bf16 {%0,%1,%2,%3,%4,%5,%6,%7}, %8, %9, p, 1, 1, 0, 0;\n}\n" : R8(d, 0) : "l"(da), "l"(db), "r"(zero));
}
__device__ __forceinline__ void ss_n16(float* d, uint64_t da, uint64_t db) {
  asm volatile("wgmma.mma_async.sync.aligned.m64n16k16.f32.bf16.bf16 {%0,%1,%2,%3,%4,%5,%6,%7}, %8, %9, 0, 1, 1, 0, 0;" : W8(d, 0) : "l"(da), "l"(db));
}
template <int N> __device__ __forceinline__ void rename_regs(float* d) {
#pragma unroll
  for (int i = 0; i < N; i++) { float t; asm volatile("mov.b32 %0, %1;" : "=f"(t) : "f"(d[i]) : "memory"); d[i] = t; }
}

template <int SWAPB>
__global__ void __cluster_dims__(2, 1, 1) __launch_bounds__(512, 1)
fused_kernel(const __grid_constant__ Params P, const __grid_constant__ CUtensorMap mX, const __grid_constant__ CUtensorMap mB,
             const __grid_constant__ CUtensorMap mCre, const __grid_constant__ CUtensorMap mCim, const __grid_constant__ CUtensorMap mXs,
             const __grid_constant__ CUtensorMap mK, const __grid_constant__ CUtensorMap mV, const __grid_constant__ CUtensorMap mQ, const __grid_constant__ CUtensorMap mS,
             const __grid_constant__ CUtensorMap mO) {
  extern __shared__ __align__(1024) uint8_t smem_raw[];
  if (threadIdx.x == 0) { prefetch_map(&mX); prefetch_map(&mB); }
  const uint32_t sb = (uint32_t)__cvta_generic_to_shared(smem_raw);
  const uint32_t bars = sb + OFF_BAR;
  const int slot = (P.slot[blockIdx.x >> 3] >> (4 * (blockIdx.x & 6))) & 63, rank = blockIdx.x & 1;
  const int j = slot & 7, tc = 2 * (slot >> 3) + rank, b = 2 * slot + rank;
  const int tid = threadIdx.x;
  const int warp = __shfl_sync(0xffffffffu, tid >> 5, 0);
  const int wg = warp >> 2;
  const uint32_t c_start = clk32();
  auto kblock = [&](int n) { return ((n & 14) == 0 || (n & 14) == 2 * j ? n ^ (2 * j) : n) & 31; };
  auto send_y = [&](int r) {
    const uint32_t src = sb + OFF_U + 4 * (rank ^ 1) * U_N8 + r * U_CH, dst = r >= 2 ? sb + OFF_U + 4 * rank * U_N8 + (r - 2) * U_CH : sb + OFF_IN + 96 + r * 2064;
#pragma unroll 1
    for (int n = 0; n < 4; n++) bulk_send(dst + n * (r >= 2 ? U_N8 : 512), src + n * U_N8, 512, bars + (B_IN + r) * 8, rank ^ 1);
  };
  auto load_q = [&](int i, int off, int bar) {
    const uint32_t fb = bars + bar * 8 + 4 * (i & 2);
    mbar_expect(fb, 4096); tma4d(sb + off + 2048 * (i & 2), &mQ, 16 * slot, 0, 4 * i, 4 * rank, fb);
  };
  auto head = [&](int n) {
    const uint32_t fb = bars + (B_FULL + n) * 8, dst = sb + OFF_RING + n * STAGE_BYTES;
    mbar_expect(fb, STAGE_BYTES);
    tma4d(dst + 16384, &mX, 64 * n, 0, 4 * tc, 0, fb);
    tma4d(dst, &mB, 64 * n, 0, 0, 8 * j, fb);
    tma4d(dst + 8192, &mB, 64 * n, 0, 0, 8 * j + 4, fb);
  };
  if (warp == 0 && elect_one()) {
#pragma unroll
    for (int s = 0; s < STAGES; s++) mbar_init(bars + (B_FULL + s) * 8, 1);
    asm volatile("fence.mbarrier_init.release.cluster;" ::: "memory");
    head(0);
  }
  if (wg == 3 && elect_one()) {
    if (warp < 15) {
#pragma unroll
      for (int s = 0; s < 13; s++) mbar_init(bars + 8 * B_XI + (warp & 3) * 104 + 8 * s, 1);
    } else {
#pragma unroll
      for (int s = B_XI + 39; s <= B_NONE; s++) mbar_init(bars + 8 * s, s < B_EMPTY ? 1 : s < B_COEF ? 2 : s == B_COEF ? 128 : 4);
    }
    asm volatile("fence.mbarrier_init.release.cluster;" ::: "memory");
  }
  __syncwarp();
  asm volatile("barrier.cluster.arrive.relaxed.aligned;" ::: "memory");
  if (warp == 0 && elect_one()) {
#pragma unroll 1
    for (int n = 1; n < HEAD; n++) { spin_until(c_start, ST_T0 + n * ST_DELAY); head(n); }
  }
  __syncwarp();
  int fl;
  uint32_t fa, fs;
  uint2 q[4][4];
  auto fin_setup = [&]() {
    asm volatile("mov.u32 %0, %%laneid;" : "=r"(fl));
    const int lc = 2 * (fl & 2) + (fl & 1) + ((fl >> 2) & 2);
    const bool own = ((fl >> 2) & 1) == rank, spare = !own && lc < 2;
    fa = (spare ? sb + OFF_IN + 96 + lc * 2064 : sb + OFF_U + (own ? 4 * rank * U_N8 : 4 * (rank ^ 1) * U_N8 - 2 * U_CH) + lc * U_CH) + (warp & 3) * 128 + (fl >> 4) * 16 + (wg & 1) * 64;
    fs = spare ? 512 : U_N8;
  };
  auto get_q = [&](int n, int off, int bar, int ph) {
#pragma unroll
    for (int u = 0; u < 2; u++) {
      mbar_wait(bars + (bar + u) * 8, ph);
#pragma unroll
      for (int r = 0; r < 4; r++) q[n + u][r] = lds64(sb + off + 4096 * u + 1024 * (warp & 3) + 256 * r + 8 * fl);
    }
  };
#define CLUSTER_WAIT() asm volatile("barrier.cluster.wait.aligned;" ::: "memory")

  if (wg == 3) {
    asm volatile("setmaxnreg.dec.sync.aligned.u32 24;");
    CLUSTER_WAIT();
    if (warp < 14) {
      if (elect_one()) {
        uint32_t so = 8 * (HEAD % STAGES), ph = HEAD < STAGES;
        auto step = [&](auto issue) {
          mbar_wait(bars + B_EMPTY * 8 + so, ph);
          issue(sb + OFF_RING + (so << 12), bars + B_FULL * 8 + so);
          so += 8;
          if (so == 8 * STAGES) { so = 0; ph ^= 1; }
        };
        if (warp == 12) {
          auto g1 = [&](int n0, int n1, int grp) {
#pragma unroll 1
            for (int n = n0; n < n1; n++) step([&](uint32_t dst, uint32_t fb) { mbar_expect(fb, STAGE_BYTES); tma4d_mc(dst + rank * 8192, &mB, n * 64, 0, 0, grp + 4 * rank, fb); });
          };
#pragma unroll 1
          for (int n = HEAD; n < STAGES; n++) { spin_until(c_start, ST_T0 + n * ST_DELAY); g1(n, n + 1, 8 * j); }
          g1(STAGES, 16, 8 * j);
          g1(0, XPOS - 16, 8 * j + 64);
          step([&](uint32_t dst, uint32_t fb) { mbar_expect(fb, STAGE_BYTES); tma4d(dst, &mXs, 128 * j, 0, 4 * tc, 0, fb); });
#pragma unroll 1
          for (int n = 0; n < 32; n += 2) {
            const int col = kblock(n) * 32;
#pragma unroll
            for (int part = 0; part < 2; part++)
              step([&](uint32_t dst, uint32_t fb) { mbar_expect(fb, STAGE_BYTES); tma5d_mc(dst + rank * 8192, part ? &mCim : &mCre, col, 0, 0, 0, 8 * j + 4 * rank, fb); });
          }
        } else {
          auto g1 = [&](int n0, int n1, int nb) {
#pragma unroll 1
            for (int n = n0; n < n1; n++) step([&](uint32_t dst, uint32_t fb) { tma4d(dst + 16384, &mX, n * 64, 0, 4 * tc, 0, fb); });
          };
          auto g2 = [&](int n0, int n1) {
#pragma unroll 1
            for (int n = n0; n < n1; n++) step([&](uint32_t dst, uint32_t fb) { bulk_load(dst + 16384, g_h + (32 * tc + kblock(n)) * 1024, 16384, fb); });
          };
#pragma unroll 1
          for (int n = HEAD; n < STAGES; n++) { spin_until(c_start, ST_T0 + n * ST_DELAY); g1(n, n + 1, 0); }
          g1(STAGES, 16, 0);
          g1(0, XPOS - 16, 16);
          step([&](uint32_t dst, uint32_t fb) { tma4d(dst + 16384, &mXs, 128 * j + 64, 0, 4 * tc, 0, fb); });
#pragma unroll 1
          for (int v = 0; v < 2; v++) {
            mbar_wait(bars + (B_HP + v) * 8, 0);
            fence_proxy_async_global();
            g2(16 * v, 16 * v + 2);
            mbar_wait(bars + (B_HR + v) * 8, 0);
            fence_proxy_async_global();
            g2(16 * v + 2, 16 * v + 16);
          }
        }
      }
    } else if (warp == 15) {
      mbar_wait(bars + B_COEF * 8, 0);
      const unsigned epoch = lds32(bars + B_EPOCH * 8);
#pragma unroll 1
      for (int v = 0; v < 2; v++) {
        unsigned* fp = &g_flagH[tc * 32 + v];
        if (elect_one()) {
          wait_until(v ? clk32() : c_start, (v ? PFC_T1 : PFC_T0) + (slot >> 3) * PFC_DT);
#pragma unroll
          for (int part = 0; part < 2; part++)
            asm volatile("cp.async.bulk.prefetch.tensor.5d.L2.global [%0, {%1, %2, %2, %2, %3}];" ::"l"(part ? &mCim : &mCre), "r"(512 * v + 8 * (slot & 56)), "r"(0), "r"(8 * j + 4 * rank) : "memory");
        }
        __syncwarp();
        bar_sync(4 + v, 160);
        if (elect_one()) {
          asm volatile("red.release.gpu.global.add.u32 [%0], 1;" ::"l"(fp) : "memory");
          mbar_arrive(bars + (B_HP + v) * 8);
          int it = 0;
          while (ld_acquire(fp) != 8 * epoch && ++it < (SPIN_LIMIT << 4)) __nanosleep(POLL_NS);
          mbar_arrive(bars + (B_HR + v) * 8);
        }
        __syncwarp();
      }
    } else if (elect_one()) {
      const int ch0 = 16 * slot;
      auto load_k = [&](int s, uint32_t dst) { const uint32_t fb = bars + (B_KF + s) * 8; mbar_expect(fb, 4096); tma2d(dst, &mS, 0, 64 * (8 * b + s), fb); };
      prefetch_map(&mS); prefetch_map(&mK); prefetch_map(&mV);
      wait_until(c_start, K_T0);
      load_k(0, sb + OFF_U + (4 * rank + 3) * U_N8); load_k(1, sb + OFF_U + (4 * rank + 3) * U_N8 - 4096);
      {
        uint32_t so = 16, ph = 1;
#pragma unroll 1
        for (int e = 0; e < 9; e++) {
          const uint32_t fb = bars + B_KVF * 8 + so, dst = sb + OFF_KV + (so << 10);
          wait_until(c_start, KV_T0 + (e ? 2 * e - 1 : 0) * KV_DT - (e > KV_E ? e - KV_E : 0) * 2 * (KV_DT - KV_D2));
          mbar_wait(bars + B_KVE * 8 + so, ph);
          const uint32_t c1 = clk32();
          mbar_expect(fb, e ? 8192 : 4096);
          tma3d(dst, &mK, ch0, 32 * rank - (e == 0), (4 * e - 4) & 31, fb);
          if (e > 0) { wait_until(c1, KV_DV); tma3d(dst + 4096, &mV, ch0, 32 * rank, 4 * e - 4, fb); }
          so += 8;
          if (so == 24) so = 0;
          if (so == 16) ph ^= 1;
        }
      }
      prefetch_map(&mCre); prefetch_map(&mCim); prefetch_map(&mXs); prefetch_map(&mQ); prefetch_map(&mO);
      mbar_wait(bars + B_KVE * 8, 0);
      load_k(2, sb + OFF_K); load_k(3, sb + OFF_K + 4096);
      mbar_wait(bars + (B_UF + 3) * 8, 0);
#pragma unroll 1
      for (int ch = 0; ch < 7; ch++) {
        mbar_wait(bars + (B_ST + ch) * 8, 0);
        if (ch > 2) mbar_wait(bars + (B_IN + ch - 3) * 8, 0);
        if (ch < 4) load_k(ch + 4, sb + OFF_K + (ch & 1) * 4096);
        else if (ch < 6) load_q(2 * (ch & 1), OFF_K, B_KF + 8);
        if (ch > 0) send_y(ch - 1);
        if (ch == 2) load_q(1, OFF_Q, B_QF);
        if (ch == 3) asm volatile("cp.async.bulk.prefetch.tensor.4d.L2.global [%0, {%1, %2, %3, %4}];" ::"l"(&mQ), "r"(16 * (slot & ~3)), "r"(0), "r"(16 + 4 * (slot & 3)), "r"(4 * rank) : "memory");
        if (ch == 4) { mbar_wait(bars + B_XI * 8, 0); load_q(3, OFF_Q, B_QF); }
      }
    }
    return;
  } else if (wg == 2) {
    asm volatile("setmaxnreg.inc.sync.aligned.u32 %0;" ::"n"(488 - 2 * GREG));
    const int t = tid & 127, w = warp & 3, lane = t & 31, c = lane & 3;
    const uint4 s2[2] = {ldg128_nc(P.shift_k + (8 * b + 2 * c) * 4), ldg128_nc(P.shift_k + (8 * (b ^ 1) + 2 * c) * 4)};
    const uint32_t dskip = __bfloat16_as_ushort(P.ssm_D[8 * b + (t & 7)]);
    uint32_t tp[4] = {}, ts[4] = {};
    float d0r, d0i;
    fft_tables(sb + OFF_F1, sb + OFF_F2, w, lane, tp, ts, d0r, d0i);
    CLUSTER_WAIT();
    if (t < 12) mbar_expect(bars + (B_IN + t) * 8, t < 6 ? 2048 : t < 8 ? 4 * (U_CH + 512) : U_N8);
    if (t < 8) sts32(sb + OFF_D + 8 * t, dskip << 16);
    const uint64_t dF1b = make_desc(sb + OFF_F1, 512, 128, 0);
    const uint64_t dF2f = make_desc(sb + OFF_F2, 512, 128, 0), dF2i = make_desc(sb + OFF_F2, 128, 512, 0);
    uint32_t f1[8];
#pragma unroll
    for (int i = 0; i < 8; i++) f1[i] = lds32(sb + OFF_F1 + w * 1024 + (i & 1) * 512 + (i >> 1) * 128 + lane * 4);
    auto T1k = [&](float* z, uint64_t dk) { wg_fence(); rs_n64<0, 1>(z, f1, dk); rs_n64<1, 1>(z, f1 + 4, dk + 64); wg_commit(); };
    auto T1u = [&](float* z, uint64_t du) { wg_fence(); rs_n64<0, 0>(z, f1, du); rs_n64<1, 0>(z, f1 + 4, du + 16); wg_commit(); };
    auto T2 = [&](float* s, const uint32_t* f) {
      wg_fence();
      rs_n32<0, 1>(s, f, dF2f); rs_n32<0, 1>(s + 16, f + 8, dF2f); rs_n32<1, 1>(s, f + 4, dF2f + 64); rs_n32<1, 1>(s + 16, f + 12, dF2f + 64);
      wg_commit();
    };
    auto product = [&](uint32_t* pr, const uint32_t* kh, const uint32_t* uh) {
      bimac<0>(pr, kh, uh, pr); bimac<2>(pr + 8, kh + 8, uh, pr); bimac<1>(pr + 8, kh, uh + 8, pr + 8);
      fence_u32<16>(pr);
    };
    float zk[32] = {};
    uint32_t pr[16];
    {
      uint32_t kh0[16];
      {
        float z0[32], sk[32];
        uint32_t fk[16];
        const uint64_t dk = make_desc(sb + OFF_U + (4 * rank + 3) * U_N8, 2048, 512, 2);
        fence_proxy_async_smem();
        bar_sync(7, 128);
        mbar_wait(bars + B_KF * 8, 0);
        T1k(z0, dk);
        mbar_wait(bars + (B_KF + 1) * 8, 0);
        T1k(zk, dk - 256);
        wg_wait<0>(); fence_regs<32>(z0); fence_regs<32>(zk);
        const float dd = __uint_as_float(lds32(sb + OFF_D));
        z0[0] = fmaf(d0r, dd, z0[0]); z0[2] = fmaf(d0i, dd, z0[2]);
        pack32(fk, z0); twiddle<0>(fk, tp, ts); fence_u32<16>(fk);
        T2(sk, fk);
        wg_wait<0>(); fence_regs<32>(sk); fence_u32<16>(fk);
        pack32(kh0, sk); fence_u32<16>(kh0);
      }
      {
        uint32_t sk[2][4], kx[2][8];
#pragma unroll
        for (int o = 0; o < 2; o++) {
          sk[o][0] = __byte_perm(s2[o].x, s2[o].z, 0x5410); sk[o][1] = __byte_perm(s2[o].x, s2[o].z, 0x7632);
          sk[o][2] = __byte_perm(s2[o].y, s2[o].w, 0x5410); sk[o][3] = __byte_perm(s2[o].y, s2[o].w, 0x7632);
        }
        const uint32_t la = sb + OFF_KV + (lane >> 3) * 1024 + (8 * w + (lane & 7)) * 32 + ((rank ^ ((lane >> 2) & 1)) << 4);
        const uint32_t uo = (lane & 7) * U_CH + w * 128 + (lane >> 3) * 16;
        mbar_wait(bars + (B_KVF + 2) * 8, 0);
        ldsm4(kx[0], la + 16384); ldsm4(kx[1], (la ^ 16) + 16384);
        if (lane == 0) mbar_arrive(bars + (B_KVE + 2) * 8 + (kx[0][1] & kx[1][1] & P.zero));
        uint32_t so = 0, ph = 0;
#pragma unroll 1
        for (int n = 0; n < 4; n++) {
          const uint32_t own = sb + OFF_U + (4 * rank + n) * U_N8, box = n < 3 ? sb + OFF_U + (4 * (rank ^ 1) + n + 1) * U_N8 : sb + OFF_IN;
#pragma unroll
          for (int e = 0; e < 2; e++) {
            uint32_t vx[2][4];
            mbar_wait(bars + B_KVF * 8 + so, ph);
#pragma unroll
            for (int o = 0; o < 2; o++) { ldsm4(kx[o] + 4, (la ^ (16 * o)) + (so << 10)); ldsm4(vx[o], (la ^ (16 * o)) + (so << 10) + 4096); }
            if (lane == 0) mbar_arrive(bars + B_KVE * 8 + so + (kx[0][4] & kx[1][4] & vx[0][0] & vx[1][0] & P.zero));
#pragma unroll
            for (int o = 0; o < 2; o++) {
#pragma unroll
              for (int i = 0; i < 4; i++) vx[o][i] = bmul2(bfma2(kx[o][i + 4], sk[o][0], bfma2(kx[o][i + 3], sk[o][1], bfma2(kx[o][i + 2], sk[o][2], bmul2(kx[o][i + 1], sk[o][3])))), vx[o][i]);
              stsm4t((o ? box : own) + uo + e * 64, vx[o][0], vx[o][1], vx[o][2], vx[o][3]);
              kx[o][1] = kx[o][5]; kx[o][2] = kx[o][6]; kx[o][3] = kx[o][7];
            }
            so += 8;
            if (so == 24) so = 0;
            if (so == 16) ph ^= 1;
          }
          fence_proxy_async_smem();
          bar_sync(7, 128);
          if (w == 0 && elect_one()) {
            if (n > 0) mbar_wait(bars + B_UF * 8 + 8 * (n - 1), 0);
            bulk_send(own, box, U_N8, bars + B_UF * 8 + 8 * n, rank ^ 1);
          }
          __syncwarp();
        }
      }
      float zu[32], su[32];
      uint32_t fu[16], uh[16];
#pragma unroll
      for (int n = 0; n < 4; n++) mbar_wait(bars + (B_UF + n) * 8, 0);
      T1u(zu, make_desc(sb + OFF_U, 128, U_N8, 0));
      wg_wait<0>(); fence_regs<32>(zu);
      pack32(fu, zu); twiddle<0>(fu, tp, ts); fence_u32<16>(fu);
      T2(su, fu);
      wg_wait<0>(); fence_regs<32>(su); fence_u32<16>(fu);
      pack32(uh, su);
      product(pr, kh0, uh);
    }
    {
#define CF(i) do { if ((CFM >> (i)) & 1) PMFENCE(); } while (0)
      const uint32_t vs = w < 2 ? 512 : U_N8, vi = (w >> 1) * U_CH;
      uint32_t va = (w < 2 ? sb + OFF_VP : sb + OFF_U) + ((lane >> 4) & 1) * vs + (w & 1) * 256 + (lane & 15) * 16;
      const uint32_t ya = sb + OFF_U + (2 * w + ((lane >> 3) & 1)) * U_N8 + (lane >> 4) * 128 + (lane & 7) * 16;
      uint64_t du = make_desc(sb + OFF_U, 128, U_N8, 0), dk = make_desc(sb + OFF_K, 2048, 512, 2);
      const uint64_t dv = make_desc(sb + OFF_VP, 128, 512, 0), dks = 2 * dk + 256;
      uint32_t yp[8] = {};
      uint32_t yq = sb + OFF_Q + lane * 16, yi = ya - yq;
      auto store_y = [&]() { stsm4(yq, yp[0], yp[1], yp[2], yp[3]); stsm4(yq + 256, yp[4], yp[5], yp[6], yp[7]); };
      auto step = [&](uint32_t c8, auto fwd) {
        constexpr bool FWD = decltype(fwd)::value;
        float zu[32], sk[32], su[32], v[32], y[16];
        uint32_t kh[16], uh[16], fk[16], fu[16], fv[16];
        wg_fence();
        rs_n32<0, 0>(v, pr, dF2i); rs_n32<0, 0>(v + 16, pr + 8, dF2i); rs_n32<1, 0>(v, pr + 4, dF2i + 16); rs_n32<1, 0>(v + 16, pr + 12, dF2i + 16);
        wg_commit();
        CF(0);
        const float dd = FWD ? __uint_as_float(lds32(sb + OFF_D + 8 + c8)) : 0.f;
        store_y();
        if (FWD) {
          zk[0] = fmaf(d0r, dd, zk[0]); zk[2] = fmaf(d0i, dd, zk[2]);
          pack32(fk, zk); twiddle<0>(fk, tp, ts); fence_u32<16>(fk);
          T2(sk, fk);
          CF(2);
          mbar_wait(bars + (B_KF + 2) * 8 + c8, 0);
          wg_wait<1>();
        } else {
#pragma unroll
          for (int r = 3; r < 6; r++) mbar_wait(bars + (B_IN + r) * 8, 0);
          wg_wait<0>();
        }
        fence_regs<32>(v); fence_u32<16>(pr);
        pack32(fv, v); fence_u32<16>(fv);
        CF(4);
        if (FWD) T1u(zu, du + U_CH / 16);
        CF(5);
        if (FWD) { wg_wait<1>(); fence_regs<32>(sk); fence_u32<16>(fk); pack32(kh, sk); }
        twiddle<1>(fv, tp, ts);
        fence_u32<16>(fv);
        if (FWD) fence_u32<16>(kh);
        CF(7);
        if (FWD) T1k(zk, dk);
#pragma unroll
        for (int i = 0; i < 4; i++) stsm4(va + 2 * i * vs, fv[4 * i], fv[4 * i + 1], fv[4 * i + 2], fv[4 * i + 3]);
        if (FWD) {
          CF(8);
          wg_wait<1>(); fence_regs<32>(zu);
          pack32(fu, zu); twiddle<0>(fu, tp, ts); fence_u32<16>(fu);
          T2(su, fu);
          CF(10);
        }
        fence_proxy_async_smem();
        bar_sync(7, 128);
        wg_fence();
        ss_n32_tt<0>(y, dv, dF1b); ss_n32_tt<1>(y, dv + 16, dF1b + 64); ss_n32_tt<1>(y, du, dF1b + 128); ss_n32_tt<1>(y, du + 16, dF1b + 192);
        wg_commit();
        CF(12);
        if (FWD) {
          wg_wait<1>(); fence_regs<32>(su); fence_u32<16>(fu); fence_regs<32>(zk);
          if (t == 0) mbar_arrive(bars + B_ST * 8 + c8);
          pack32(uh, su);
          bimac<0>(pr, kh, uh, pr); bimac<2>(pr + 8, kh + 8, uh, pr); fence_u32<16>(pr);
          CF(14);
          wg_wait<0>(); fence_regs<16>(y);
          bimac<1>(pr + 8, kh, uh + 8, pr + 8); fence_u32<8>(pr + 8);
          du += U_CH / 16; dk = dks - dk;
          va += vi;
        }
        if (!FWD) {
          PMFENCE();
          fin_setup(); get_q(0, OFF_K, B_KF + 8, 0);
#pragma unroll
          for (int r = 0; r < 8; r++) q[2 + (r >> 2)][r & 3] = make_uint2(0, 0);
          wg_wait<0>(); fence_regs<16>(y);
        }
#pragma unroll
        for (int i = 0; i < 8; i++) yp[i] = pack_bf16(y[2 * i], y[2 * i + 1]);
        fence_u32<8>(yp);
        yq += yi; yi = U_CH;
      };
#pragma unroll 1
      for (uint32_t c8 = 0; c8 < 56; c8 += 8) step(c8, std::true_type());
      step(56, std::false_type());
      store_y();
    }
    fence_proxy_async_smem();
    bar_sync(7, 128);
    if (elect_one()) bulk_send(sb + OFF_U + (4 * rank + w) * U_N8 + 4 * U_CH, sb + OFF_U + (4 * (rank ^ 1) + w) * U_N8 + 6 * U_CH, U_CH + 512, bars + (B_IN + 6) * 8, rank ^ 1);
    __syncwarp();
    asm volatile("bar.arrive 9, 256;" ::: "memory");
  } else {
    asm volatile("setmaxnreg.inc.sync.aligned.u32 %0;" ::"n"(GREG));
    const int t = tid & 127, w = warp & 3, lane = t & 31, g = lane >> 2, c = lane & 3;
    if (wg == 1) {
      wait_until(c_start, COEF_T0);
      const int p = 64 * j + (t & 63) + 8 * (t & 64);
      const float Lr = bf2f(P.lam_re[p]), Li = bf2f(P.lam_im[p]);
      const uint32_t ds = __bfloat16_as_ushort(P.Dskip[128 * j + t]);
      const unsigned epoch = (ld_relaxed(&g_flagH[tc * 32]) >> 3) + 1;
      const float dt = bf2f(__float2bfloat16_rn(expf(bf2f(P.log_dt[p]))));
      const float e = expf(dt * Lr);
      float sn, cs;
      {
        const double z = (double)(dt * Li) * 0.15915494309189535;
        sincospif(2.f * (float)(z - rint(z)), &sn, &cs);
      }
      const float lr = e * cs, li = e * sn;
      const float nr = lr - 1.0f, ni = li;
      const bool big = fabsf(Lr) >= fabsf(Li);
      const float la = big ? Lr : Li, lb = big ? Li : Lr, r = __fdiv_rn(lb, la), inv = __frcp_rn(fmaf(lb, r, la));
      const float br = (big ? fmaf(ni, r, nr) : fmaf(nr, r, ni)) * inv, bi = (big ? fmaf(-nr, r, ni) : fmaf(ni, r, -nr)) * inv;
      sts128(sb + OFF_COEF + t * 16, make_uint4(__float_as_uint(lr), __float_as_uint(li), pack_bf16(2.f * br, 2.f * br), pack_bf16(-2.f * bi, -2.f * bi)));
      sts32(sb + OFF_DS + 4 * t, ds << 16);
      if (t == 0) sts32(bars + B_EPOCH * 8, epoch);
    }
    CLUSTER_WAIT();
    if (wg == 1) mbar_arrive(bars + B_COEF * 8);
    float d[128];
    uint32_t so = 0, ph = 0, po = 0;
    uint32_t ra;
    auto set_ra = [&]() { asm volatile("mapa.shared::cluster.u32 %0, %1, %2;" : "=r"(ra) : "r"(bars + B_EMPTY * 8), "r"((t & 1) ? rank ^ 1 : rank)); };
    set_ra();
    auto release = [&](uint32_t off) { if (t < 2) asm volatile("mbarrier.arrive.shared::cluster.b64 _, [%0];" ::"r"(ra + off) : "memory"); };
    constexpr uint32_t NOBAR = 8 * (B_NONE - B_EMPTY);
    auto block = [&](auto ta, uint64_t da0, uint64_t db0, bool zero, int nn) {
      constexpr int PH = decltype(ta)::value, TA = PH > 0, KS = TA ? 128 : 2, QD = PH == 0 ? QD1 : PH == 1 ? QD2 : QD3;
      mbar_wait(bars + B_FULL * 8 + so, ph);
      const uint64_t da = da0 + (so << 8), db = db0 + (so << 8);
      bool rel = false;
#pragma unroll
      for (int i = 0; i < 8; i++) {
        if (i == 0 || ((QD >> (i - 1)) & 1)) wg_fence();
        wgmma_n128<TA>(d + 64 * (i & 1), da + 512 * (i & 1) + KS * (i >> 1), db + 2 * (i >> 1), i < 2 ? !zero : 1);
        if (i == 7 || ((QD >> i) & 1)) wg_commit();
        if ((QD >> i) & 1) { wg_wait<1>(); if (!rel) release(po); rel = true; }
      }
      po = so;
      so += 8;
      if (so == 8 * STAGES) { so = 0; ph ^= 1; }
    };
    {
      so = wg ? 8 * (16 % STAGES) : 0; ph = wg ? (16 / STAGES) & 1 : 0; po = NOBAR;
      const uint64_t da0 = make_desc(sb + OFF_RING, 16, 1024, 1), db0 = make_desc(sb + OFF_RING + 16384, 16, 1024, 1);
      if (wg == 1) bar_sync(1, 256);
#pragma unroll 1
      for (int kb = 0; kb < 16; kb++) {
        block(std::integral_constant<int, 0>(), da0, db0, kb == 0, 16 * wg + kb);
      }
      asm volatile("bar.arrive %0, 256;" ::"r"(1 + wg) : "memory");
    }
    mbar_wait(bars + B_COEF * 8, 0);
    const uint32_t ca = sb + OFF_COEF + (64 * wg + 8 * w + g) * 16;
    const uint32_t tag = __shfl_sync(0xffffffffu, lds32(bars + B_EPOCH * 8) & 3, 0);
    constexpr int RE = SWAPB ? 2 : 0, IM = 2 - RE;
    const int ct = lane >> 3;
    const uint2* cp = g_carry + __shfl_sync(0xffffffffu, ((16 * wg + 2 * j) * 16 + tc - 1 - ct) * 32 + 8 * w + (lane & 7), lane);
    const uint2* sp = g_carry + __shfl_sync(0xffffffffu, ((16 * wg + 2 * j) * 16 + tc) * 32 + 8 * w + g, lane);
    unsigned long long cv[4];
    const int nv = tc - ct;
    auto load_carry = [&](int i) {
#pragma unroll
      for (int m = 0; m < 4; m++)
        asm volatile("{\n.reg .pred p;\nsetp.gt.s32 p, %2, %3;\n@p ld.relaxed.gpu.global.b64 %0, [%1];\n}\n" : "+l"(cv[m]) : "l"(cp + 512 * i - 128 * m), "r"(nv), "r"(4 * m) : "memory");
    };
    float lr[2], li[2], pr[2], pi[2], wr[2], wi[2], vr[2], vi[2], qr[2], qi[2], gr[2], gi[2];
#pragma unroll
    for (int i = 0; i < 2; i++) {
      const uint2 cf = lds64(ca + 512 * i);
      pr[i] = lr[i] = __uint_as_float(cf.x); pi[i] = li[i] = __uint_as_float(cf.y);
#pragma unroll
      for (int s = 0; s < 4; s++) csq(pr[i], pi[i]);
      gr[i] = pr[i]; gi[i] = pi[i];
      csq(pr[i], pi[i]);
      asm volatile("" : "+f"(pr[i]), "+f"(pi[i]));
    }
    PMFENCE();
    wg_wait<0>();
    fence_regs<128>(d);
    release(po);
#pragma unroll
    for (int i = 0; i < 2; i++) {
      float* e = d + 64 * i;
      auto chain = [&](int s0, int s1, float& sr, float& si) {
        sr = e[2 * s0 + RE]; si = e[2 * s0 + IM];
#pragma unroll
        for (int s = s0 + 1; s < s1; s++) {
          const int ia = 4 * (s >> 1) + (s & 1);
          const float nr = fmaf(-li[i], si, fmaf(lr[i], sr, e[ia + RE])), ni = fmaf(li[i], sr, fmaf(lr[i], si, e[ia + IM]));
          sr = nr; si = ni;
        }
      };
      float sr, si;
      if (i == 1) { cv[0] = cv[1] = cv[2] = cv[3] = tag; asm volatile("" : "+l"(cv[0]), "+l"(cv[1]), "+l"(cv[2]), "+l"(cv[3])); }
      if ((GREEDY >> i) & 1) {
        float ar, ai;
        chain(0, 16, ar, ai); chain(16, 32, sr, si);
        sr = fmaf(gr[i], ar, fmaf(-gi[i], ai, sr)); si = fmaf(gr[i], ai, fmaf(gi[i], ar, si));
      } else chain(0, 32, sr, si);
      if (i == 1) { asm volatile("pmevent 0;" : "+f"(sr), "+f"(si)::"memory"); load_carry(0); PMFENCE(); }
      float ur[3], ui[3], er = 0.f, ei = 0.f;
#pragma unroll
      for (int m = 0; m < 3; m++) { ur[m] = __shfl_up_sync(0xffffffffu, sr, m + 1, 4); ui[m] = __shfl_up_sync(0xffffffffu, si, m + 1, 4); }
      if (c == 3) { er = ur[2]; ei = ui[2]; }
#pragma unroll
      for (int m = 1; m >= 0; m--) {
        const float nr = fmaf(pr[i], er, fmaf(-pi[i], ei, ur[m])), ni = fmaf(pr[i], ei, fmaf(pi[i], er, ui[m]));
        if (c > m) { er = nr; ei = ni; }
      }
      sr = fmaf(pr[i], er, fmaf(-pi[i], ei, sr)); si = fmaf(pr[i], ei, fmaf(pi[i], er, si));
      asm volatile("{\n.reg .pred p;\n.reg .b64 v;\nsetp.eq.u32 p, %3, 3;\nmov.b64 v, {%1,%2};\n@p st.relaxed.gpu.global.b64 [%0], v;\n}\n"
                   ::"l"(sp + 512 * i), "r"((__float_as_uint(sr) & ~3u) | tag), "r"(__float_as_uint(si)), "r"(c) : "memory");
      e[RE] = fmaf(lr[i], er, fmaf(-li[i], ei, e[RE])); e[IM] = fmaf(lr[i], ei, fmaf(li[i], er, e[IM]));
      PMFENCE();
      asm volatile("" : "+f"(e[RE]), "+f"(e[IM]));
    }
#pragma unroll
    for (int i = 0; i < 2; i++) {
      qr[i] = pr[i]; qi[i] = pi[i];
      csq(qr[i], qi[i]);
      wr[i] = (c & 1) ? pr[i] : 1.f; wi[i] = (c & 1) ? pi[i] : 0.f;
      if (c & 2) { float x, y; cmul(wr[i], wi[i], qr[i], qi[i], x, y); wr[i] = x; wi[i] = y; }
      vr[i] = wr[i]; vi[i] = wi[i];
      csq(vr[i], vi[i]); csq(vr[i], vi[i]);
      csq(qr[i], qi[i]); csq(qr[i], qi[i]); csq(qr[i], qi[i]);
      const int src = 4 * (lane & 7) + ct;
      vr[i] = __shfl_sync(0xffffffffu, vr[i], src); vi[i] = __shfl_sync(0xffffffffu, vi[i], src);
      qr[i] = __shfl_sync(0xffffffffu, qr[i], src); qi[i] = __shfl_sync(0xffffffffu, qi[i], src);
    }
    uint4* hp = g_h + (32 * tc + 16 * wg + 2 * j) * 1024 + 64 * w + 4 * g + (c ^ (g >> 1));
    float sr[2], si[2];
    uint32_t gp[2], gm[2];
    auto carry_in = [&](int i) {
      auto ready = [&]() { return __all_sync(0xffffffffu, ((((uint32_t)cv[0] ^ tag) | ((uint32_t)cv[1] ^ tag) | ((uint32_t)cv[2] ^ tag) | ((uint32_t)cv[3] ^ tag)) & 3) == 0); };
      if (!ready()) {
        int n = 0;
#pragma unroll 1
        do load_carry(i); while (!ready() && ++n <= (SPIN_LIMIT << 4));
      }
      float hr = __uint_as_float((uint32_t)cv[3] & ~3u), hi = __uint_as_float((uint32_t)(cv[3] >> 32));
#pragma unroll
      for (int m = 2; m >= 0; m--) {
        const float nr = fmaf(qr[i], hr, fmaf(-qi[i], hi, __uint_as_float((uint32_t)cv[m] & ~3u))), ni = fmaf(qr[i], hi, fmaf(qi[i], hr, __uint_as_float((uint32_t)(cv[m] >> 32))));
        hr = nr; hi = ni;
      }
      { float x, y; cmul(hr, hi, vr[i], vi[i], x, y); hr = x; hi = y; }
      const uint4 cf = lds128(ca + 512 * i);
      lr[i] = __uint_as_float(cf.x); li[i] = __uint_as_float(cf.y); gp[i] = cf.z; gm[i] = cf.w;
      hr += __shfl_xor_sync(0xffffffffu, hr, 8); hi += __shfl_xor_sync(0xffffffffu, hi, 8);
      hr = __shfl_sync(0xffffffffu, hr, g) + __shfl_sync(0xffffffffu, hr, g + 16); hi = __shfl_sync(0xffffffffu, hi, g) + __shfl_sync(0xffffffffu, hi, g + 16);
      cmul(wr[i], wi[i], hr, hi, sr[i], si[i]);
    };
    PMFENCE();
    carry_in(0);
#pragma unroll
    for (int u = 0; u < 8; u++) {
      const int i = u >> 2, i8 = u & 3;
      float* e = d + 64 * i;
      asm volatile("pmevent 0;" : "+f"(sr[i]), "+f"(si[i])::"memory");
      if (u == 1) load_carry(1);
      if (u == 3) carry_in(1);
#pragma unroll
      for (int s = 8 * i8; s < 8 * i8 + 8; s++) {
        const int ia = 4 * (s >> 1) + (s & 1);
        const float nr = fmaf(-li[i], si[i], fmaf(lr[i], sr[i], e[ia + RE])), ni = fmaf(li[i], sr[i], fmaf(lr[i], si[i], e[ia + IM]));
        sr[i] = nr; si[i] = ni;
        e[ia + RE] = nr; e[ia + IM] = ni;
      }
      uint32_t hq[8];
#pragma unroll
      for (int m = 0; m < 4; m++) {
        const float* f = e + 16 * i8 + 4 * m;
        const uint32_t x = pack_bf16(f[RE], f[RE + 1]), y = pack_bf16(f[IM], f[IM + 1]);
        hq[m] = bfma2(gp[i], x, bmul2(gm[i], y)); hq[4 + m] = bfnma2(gp[i], y, bmul2(gm[i], x));
      }
      uint4* o = hp + 512 * (i8 >> 1) + 256 * i + 32 * (i8 & 1);
      stg128(o, make_uint4(hq[0], hq[1], hq[2], hq[3]));
      stg128(o + 1024, make_uint4(hq[4], hq[5], hq[6], hq[7]));
#pragma unroll
      for (int m = 0; m < 8; m++) d[16 * u + m] = __uint_as_float(hq[m]);
      fence_regs<8>(d + 16 * u);
    }
    const int trow = 128 * tc + 64 * (w & 1) + 8 * (w >> 1) + g;
    const int dcol = 128 * j + 4 * c;
    asm volatile("bar.arrive %0, 160;" ::"r"(4 + wg) : "memory");
    if (wg == 0) {
      set_ra();
      {
        const uint32_t dt = sb + OFF_Q + 4096;
        mbar_wait(bars + (B_UF + 3) * 8, 0);
        const int n = t & 15, k = 2 * (n & 6) + 2 * (n >> 3) + (n & 1);
        const uint32_t dv = lds32(sb + OFF_DS + (t & ~15) * 4 + 4 * k) >> (16 - 16 * (k & 1));
#pragma unroll
        for (int u = 0; u < 2; u++) {
          const int m = (k >> 1) - 4 * u;
          sts128(dt + (t >> 4) * 512 + u * 256 + n * 16, make_uint4(m == 0 ? dv : 0, m == 1 ? dv : 0, m == 2 ? dv : 0, m == 3 ? dv : 0));
        }
        fence_proxy_async_smem();
        bar_sync(2, 256);
        mbar_wait(bars + (B_FULL + XPOS % STAGES) * 8, (XPOS / STAGES) & 1);
        const uint64_t dx = make_desc(sb + OFF_RING + (XPOS % STAGES) * STAGE_BYTES, 16, 1024, 1), dd = make_desc(dt, 256, 128, 0);
        wg_fence();
#pragma unroll
        for (int u = 0; u < 16; u++) {
          const uint64_t da = dx + ((u >> 2) & 1) * 1024 + (u >> 3) * 512 + (u & 3) * 2, db = dd + (u & 7) * 32;
          if (u & 1) ss_n16(d + 8 * u, da, db); else ss_n16_in(d + 8 * u, da, db, P.zero);
        }
        wg_commit();
        wg_wait<0>();
        rename_regs<128>(d);
        release(8 * (XPOS % STAGES));
        if (t == 0) mbar_arrive(bars + B_XI * 8);
      }
      so = 8 * (33 % STAGES); ph = (33 / STAGES) & 1; po = NOBAR;
      const uint64_t da0 = make_desc(sb + OFF_RING + 16384, 512, 1024, 2), db0 = make_desc(sb + OFF_RING, 16, 1024, 1);
#pragma unroll 1
      for (int kb = 0; kb < QSW; kb++) block(std::integral_constant<int, 1>(), da0, db0, false, 32 + kb);
#pragma unroll 1
      for (int kb = QSW; kb < 32 - TAILB; kb++) block(std::integral_constant<int, 2>(), da0, db0, false, 32 + kb);
      float* op = P.out + (size_t)trow * 2048 + 1024 + dcol;
      auto mma = [&](int i, int kb, int k0, int k1) {
        const int s = (33 + kb) % STAGES;
        wg_fence();
#pragma unroll
        for (int k = k0; k < k1; k++) wgmma_n128<1>(d + 64 * i, da0 + s * 2048 + 512 * i + 128 * k, db0 + (i ? 0 : P.zero) + s * 2048 + 2 * k, 1);
        wg_commit();
      };
      auto store = [&](int i, int J0, int J1) {
#pragma unroll
        for (int J = J0; J < J1; J++) {
#pragma unroll
          for (int h = 0; h < 2; h++) {
            const float* e = d + 64 * i + 8 * J + 2 * h;
            stg128(op + (size_t)(16 * i + 32 * h) * 2048 + 16 * J, make_uint4(__float_as_uint(e[0]), __float_as_uint(e[1]), __float_as_uint(e[4]), __float_as_uint(e[5])));
          }
        }
        PMFENCE();
      };
      constexpr int K0 = 32 - TAILB;
#pragma unroll
      for (int kb = K0; kb < 32; kb++) {
        mbar_wait(bars + (B_FULL + (33 + kb) % STAGES) * 8, ((33 + kb) / STAGES) & 1);
        if (TAILB == 5 && kb == K0) { mma(0, kb, 0, 2); wg_wait<1>(); release(po); mma(0, kb, 2, 4); }
        else mma(0, kb, 0, 4);
      }
      mma(1, K0, 0, 4);
      wg_wait<1>();
      fence_regs<64>(d);
#pragma unroll
      for (int kb = K0 + 1; kb < 32; kb++) {
        mma(1, kb, 0, 4);
        store(0, T_ST * (kb - K0 - 1), kb == 31 ? 8 : T_ST * (kb - K0));
      }
      wg_wait<0>();
      fence_regs<64>(d + 64);
      store(1, 0, 8);
      return;
    }
    asm volatile("setmaxnreg.dec.sync.aligned.u32 %0;" ::"n"(488 - 2 * GREG));
    fin_setup();
#pragma unroll
    for (int n = 0; n < 4; n += 2) {
      get_q(n, OFF_Q, B_QF, n >> 1);
      uint32_t dep = P.zero;
#pragma unroll
      for (int r = 0; r < 8; r++) dep &= q[n + (r >> 2)][r & 3].x;
      bar_sync(6 + dep, 128);
      if (w < 2 && elect_one()) load_q(5 + 2 * w - (n >> 1), OFF_Q, B_QF + n);
      __syncwarp();
    }
#pragma unroll 1
    for (int r = 0; r < 6; r++) mbar_wait(bars + (B_IN + r) * 8, 0);
    bar_sync(9, 256);
  }
  {
    const int w = warp & 3, h = wg & 1, lane = fl;
    const uint32_t ob0 = sb + (h ? OFF_F1 : OFF_K) + 1024 * w, ob1 = sb + (h ? OFF_VP : OFF_K + 4096) + 1024 * w;
    uint32_t y[2][8];
    auto get_y = [&](int n) { ldsm4t(y[n & 1], fa + n * fs); ldsm4t(y[n & 1] + 4, fa + n * fs + 32); };
    mbar_wait(bars + (B_HR + 1) * 8, 0);
    mbar_wait(bars + (B_IN + 6) * 8, 0);
    get_y(0);
#pragma unroll
    for (int n = 0; n < 4; n++) {
      uint32_t* o = y[n & 1];
#pragma unroll
      for (int r = 0; r < 4; r++) { o[2 * r] = bmul2(o[2 * r], q[n][r].x); o[2 * r + 1] = bmul2(o[2 * r + 1], q[n][r].y); }
      if (n > 0 && lane == 0) asm volatile("cp.async.bulk.wait_group.read 0;" ::: "memory");
      __syncwarp();
#pragma unroll
      for (int r = 0; r < 4; r++)
        sts128((r & 2 ? ob1 : ob0) + (r & 1) * 512 + lane * 16, make_uint4(o[2 * r] << 16, o[2 * r] & 0xffff0000u, o[2 * r + 1] << 16, o[2 * r + 1] & 0xffff0000u));
      fence_proxy_async_smem();
      __syncwarp();
      if (lane == 0) {
#pragma unroll
        for (int u = 0; u < 2; u++)
          asm volatile("cp.async.bulk.tensor.3d.global.shared::cta.bulk_group [%0, {%2, %3, %4}], [%1];"
                       ::"l"(&mO), "r"(u ? ob1 : ob0), "r"(32 * slot), "r"(32 * rank + 8 * w), "r"(8 * n + 4 * h + 2 * u) : "memory");
        asm volatile("cp.async.bulk.commit_group;" ::: "memory");
      }
      __syncwarp();
      if (n < 3) get_y(n + 1);
      if (n == 1 && !h) get_q(2, OFF_Q, B_QF + 2, 0);
    }
    if (warp == 8 && lane == 0) mbar_arrive_cta(bars + B_ACK * 8, rank ^ 1);
    if (lane == 0) asm volatile("cp.async.bulk.wait_group 0;" ::: "memory");
    mbar_wait(bars + B_ACK * 8, 0);
  }
}

typedef CUresult (*EncodeFn)(CUtensorMap*, CUtensorMapDataType, cuuint32_t, void*, const cuuint64_t*, const cuuint64_t*, const cuuint32_t*,
                             const cuuint32_t*, CUtensorMapInterleave, CUtensorMapSwizzle, CUtensorMapL2promotion, CUtensorMapFloatOOBfill);

bool encode(EncodeFn fn, CUtensorMap* m, int rank, const void* base, const cuuint64_t* dims, const cuuint64_t* strides, const cuuint32_t* box, CUtensorMapSwizzle swz,
            CUtensorMapL2promotion promo = CU_TENSOR_MAP_L2_PROMOTION_L2_128B) {
  const cuuint32_t es[5] = {1, 1, 1, 1, 1};
  return fn(m, CU_TENSOR_MAP_DATA_TYPE_BFLOAT16, rank, const_cast<void*>(base), dims, strides, box, es, CU_TENSOR_MAP_INTERLEAVE_NONE, swz,
            promo, CU_TENSOR_MAP_FLOAT_OOB_FILL_NONE) == CUDA_SUCCESS;
}

}

extern "C" void kernel_launch(void* const* d_in, const int* in_sizes, int n_in, void* d_out, int out_size) {
  (void)in_sizes; (void)n_in; (void)out_size;
  typedef const __nv_bfloat16* In;
  const In q = (In)d_in[0], k = (In)d_in[1], v = (In)d_in[2], ssm_k = (In)d_in[4], x = (In)d_in[6], B_re = (In)d_in[9], B_im = (In)d_in[10], C_re = (In)d_in[11], C_im = (In)d_in[12];
  Params P = {};
  P.shift_k = (In)d_in[3]; P.ssm_D = (In)d_in[5]; P.lam_re = (In)d_in[7]; P.lam_im = (In)d_in[8]; P.log_dt = (In)d_in[13]; P.Dskip = (In)d_in[14];
  P.out = (float*)d_out;
  for (int cl = 0; cl < 64; cl++) P.slot[cl >> 2] |= (cl < 4 ? 4 + cl : cl < 36 ? 8 * ((cl - 4) & 7) + ((cl - 4) >> 3) : 8 * (1 + (cl - 36) % 7) + 4 + (cl - 36) / 7) << (8 * (cl & 3));
  const bool swapB = (uintptr_t)B_im < (uintptr_t)B_re;

  EncodeFn fn = nullptr;
  cudaDriverEntryPointQueryResult qr;
  cudaGetDriverEntryPoint("cuTensorMapEncodeTiled", (void**)&fn, cudaEnableDefault, &qr);
  if (!fn) return;

  CUtensorMap mX, mB, mCre, mCim, mXs, mK, mV, mQ, mS, mO;
  bool ok = true;
  {
    const cuuint64_t dims[4] = {1024, 2, 64, 16}, str[3] = {2048, 32 * 2048, 2 * 2048};
    const cuuint32_t box[4] = {64, 2, 4, 16};
    ok &= encode(fn, &mX, 4, x, dims, str, box, CU_TENSOR_MAP_SWIZZLE_128B);
  }
  {
    const uintptr_t lo = swapB ? (uintptr_t)B_im : (uintptr_t)B_re, hi = swapB ? (uintptr_t)B_re : (uintptr_t)B_im;
    const cuuint64_t dims[4] = {1024, 8, 2, 128}, str[3] = {2048, (cuuint64_t)(hi - lo), 8 * 2048};
    const cuuint32_t box[4] = {64, 8, 2, 4};
    ok &= encode(fn, &mB, 4, (const void*)lo, dims, str, box, CU_TENSOR_MAP_SWIZZLE_128B);
  }
  {
    const cuuint64_t dims[5] = {1024, 2, 4, 2, 64}, str[4] = {2048, 4 * 2048, 2 * 2048, 16 * 2048};
    const cuuint32_t box[5] = {64, 2, 4, 2, 4};
    ok &= encode(fn, &mCre, 5, C_re, dims, str, box, CU_TENSOR_MAP_SWIZZLE_128B);
    ok &= encode(fn, &mCim, 5, C_im, dims, str, box, CU_TENSOR_MAP_SWIZZLE_128B);
  }
  {
    const cuuint64_t dims[4] = {1024, 8, 64, 4}, str[3] = {2048, 32 * 2048, 8 * 2048};
    const cuuint32_t box[4] = {64, 8, 4, 4};
    ok &= encode(fn, &mXs, 4, x, dims, str, box, CU_TENSOR_MAP_SWIZZLE_128B);
  }
  {
    const cuuint64_t dims[3] = {1024, 64, 32}, str[2] = {32 * 2048, 2048};
    const cuuint32_t box[3] = {16, 32, 4};
    const cuuint64_t dimq[4] = {1024, 8, 32, 8}, strq[3] = {32 * 2048, 2048, 256 * 2048};
    const cuuint32_t boxq[4] = {16, 8, 4, 4};
    ok &= encode(fn, &mQ, 4, q, dimq, strq, boxq, CU_TENSOR_MAP_SWIZZLE_NONE);
    ok &= encode(fn, &mK, 3, k, dims, str, box, CU_TENSOR_MAP_SWIZZLE_32B);
    ok &= encode(fn, &mV, 3, v, dims, str, box, CU_TENSOR_MAP_SWIZZLE_32B);
  }
  {
    const cuuint64_t dims[2] = {32, 65536}, str[1] = {64};
    const cuuint32_t box[2] = {32, 64};
    ok &= encode(fn, &mS, 2, ssm_k, dims, str, box, CU_TENSOR_MAP_SWIZZLE_64B);
  }
  {
    const cuuint64_t dims[3] = {2048, 64, 32}, str[2] = {32 * 8192, 8192};
    const cuuint32_t box[3] = {32, 8, 2};
    ok &= encode(fn, &mO, 3, d_out, dims, str, box, CU_TENSOR_MAP_SWIZZLE_NONE);
  }
  if (!ok) return;
  auto kern = swapB ? fused_kernel<1> : fused_kernel<0>;
  cudaFuncSetAttribute(kern, cudaFuncAttributeMaxDynamicSharedMemorySize, SMEM_BYTES);
  kern<<<NCTA, 512, SMEM_BYTES, cudaStreamPerThread>>>(P, mX, mB, mCre, mCim, mXs, mK, mV, mQ, mS, mO);
}
```
